```python
import torch

def _softmax(x, axis=-1):
    return torch.softmax(x, dim=axis)

def _gelu(x):
    return torch.nn.functional.gelu(x, approximate='tanh')

def _silu(x):
    return torch.nn.functional.silu(x)

def _sigmoid(x):
    return torch.sigmoid(x)

def _layernorm(x, axis=-1, eps=1e-05):
    m = x.mean(dim=axis, keepdim=True)
    v = x.var(dim=axis, keepdim=True, unbiased=False)
    return (x - m) / torch.sqrt(v + eps)

def _scatter_add(tgt, idx, src, axis=0):
    return tgt.clone().index_add_(axis, idx, src)

def _segment_sum(src, seg, n):
    out = torch.zeros((n,) + src.shape[1:], dtype=src.dtype)
    return out.index_add_(0, seg, src)

def _pad(x, pw):
    flat = tuple((v for pair in reversed(pw) for v in pair))
    return torch.nn.functional.pad(x, flat)
kernel_name = 'recurrent_scan__mha_block_cached__mixer_gmlp__prompt'

def setup_inputs():

    _w = lambda a: (lambda t: t.to(torch.bfloat16) if t.is_floating_point() else t)(torch.as_tensor(a))

    def _A_setup():
        B, Sq, D = (1, 2048, 1024)
        H, Sk, Dh = (32, 2048, 128)
        return {'x': _w((lambda *s: torch.randn(*s, dtype=torch.bfloat16) * 0.05)(B, Sq, D)), 'k_cache': _w((lambda *s: torch.randn(*s, dtype=torch.bfloat16) * 0.8)(B, H, Sk, Dh)), 'v_cache': _w((lambda *s: torch.randn(*s, dtype=torch.bfloat16) * 0.2)(B, H, Sk, Dh)), 'wq': _w((lambda *s: torch.randn(*s, dtype=torch.bfloat16) * 0.8)(D, H * Dh) * D ** (-0.5)), 'wo': _w((lambda *s: torch.randn(*s, dtype=torch.bfloat16) * 0.2)(H * Dh, D) * (H * Dh) ** (-0.5))}
    _A_in = _A_setup()

    def _B_setup():
        B, S, D, F = (1, 2048, 1024, 3584)
        Fh = F // 2
        return {'x': _w((lambda *s: torch.randn(*s, dtype=torch.bfloat16) * 0.05)(B, S, D)), 'w_in': _w((lambda *s: torch.randn(*s, dtype=torch.bfloat16) * 0.4)(D, 2 * Fh)), 'w_sp': _w(0.01 * (lambda *s: torch.randn(*s, dtype=torch.bfloat16) * 0.4)(S, S)), 'b_sp': _w(1.0 + 0.01 * (lambda *s: torch.randn(*s, dtype=torch.bfloat16) * 0.1)(S)), 'w_out': _w((lambda *s: torch.randn(*s, dtype=torch.bfloat16) * 0.1)(Fh, D))}
    _B_in = _B_setup()
    return {'A_x': _A_in['x'], 'A_k_cache': _A_in['k_cache'], 'A_v_cache': _A_in['v_cache'], 'A_wq': _A_in['wq'], 'A_wo': _A_in['wo'], 'B_x': _B_in['x'], 'B_w_in': _B_in['w_in'], 'B_w_sp': _B_in['w_sp'], 'B_b_sp': _B_in['b_sp'], 'B_w_out': _B_in['w_out']}

def reference(A_x, A_k_cache, A_v_cache, A_wq, A_wo, B_x, B_w_in, B_w_sp, B_b_sp, B_w_out):

    def _A_ref(x, k_cache, v_cache, wq, wo):
        B, Sq, D = x.shape
        H, Dh = (32, 128)
        q = (lambda x, *d: x.permute(*d))((x @ wq).reshape(B, Sq, H, Dh), 0, 2, 1, 3)
        scores = torch.einsum('bhqd,bhkd->bhqk', q, k_cache) * Dh ** (-0.5)
        p = _softmax(scores, axis=-1)
        o = torch.einsum('bhqk,bhkd->bhqd', p, v_cache)
        return (lambda x, *d: x.permute(*d))(o, 0, 2, 1, 3).reshape(B, Sq, H * Dh) @ wo

    def _B_ref(x, w_in, w_sp, b_sp, w_out):
        B, S, D = x.shape
        F = w_in.shape[-1]
        Fh = F // 2
        z = _gelu(torch.einsum('bsd,df->bsf', x, w_in))
        z1 = z[..., :Fh].clone()
        z2 = _layernorm(z[..., Fh:], axis=-1)
        g = torch.einsum('ts,bsf->btf', w_sp, z2) + b_sp[None, :, None]
        return torch.einsum('bsf,fd->bsd', z1 * g, w_out)
    x = A_x
    xn = _layernorm(x, axis=-1)
    s = _A_ref(xn, A_k_cache, A_v_cache, A_wq, A_wo)
    g = _silu(_B_ref(xn, B_w_in, B_w_sp, B_b_sp, B_w_out))
    return x + s * g
```

```cpp
#include <cuda_runtime.h>
#include <cuda_bf16.h>
#include <cuda.h>
#include <stdint.h>
#include <stdio.h>

typedef __nv_bfloat16 bf16;

constexpr int SEQ = 2048, DM = 1024, NH = 32, HD = 4096, FF = 3584, FH = 1792;

__device__ __align__(1024) bf16 g_xn[SEQ * DM];
__device__ __align__(1024) bf16 g_q[SEQ * HD];
__device__ __align__(1024) bf16 g_o[SEQ * HD];
__device__ __align__(1024) bf16 g_z2[SEQ * FH];
__device__ __align__(1024) bf16 g_u[SEQ * FH];
__device__ __align__(1024) float4 g_stats[SEQ * 8];
__device__ __align__(1024) bf16 g_g[SEQ * DM];
__device__ __align__(1024) bf16 g_sa[SEQ * DM];
constexpr int F_XN = 0;
constexpr int F_Z2 = 512;
constexpr int F_Q = 768;
constexpr int F_U = 1024;
constexpr int F_O = 1536;
constexpr int F_S = 2048;
constexpr int F_TOTAL = 2112;
__device__ __align__(1024) unsigned g_flags[F_TOTAL];
__device__ unsigned g_done;
__device__ unsigned g_epoch;

__device__ __forceinline__ uint32_t smem_u32(const void* p) { return (uint32_t)__cvta_generic_to_shared(p); }
__device__ __forceinline__ void mbar_init(uint32_t bar, uint32_t cnt) { asm volatile("mbarrier.init.shared::cta.b64 [%0], %1;" :: "r"(bar), "r"(cnt)); }
__device__ __forceinline__ void mbar_expect_tx(uint32_t bar, uint32_t bytes) { asm volatile("mbarrier.arrive.expect_tx.shared::cta.b64 _, [%0], %1;" :: "r"(bar), "r"(bytes) : "memory"); }
__device__ __forceinline__ void mbar_arrive(uint32_t bar) { asm volatile("mbarrier.arrive.shared::cta.b64 _, [%0];" :: "r"(bar) : "memory"); }
__device__ __forceinline__ void mbar_arrive_cta(uint32_t bar, uint32_t cta) {
  asm volatile("{\n.reg .b32 ra;\nmapa.shared::cluster.u32 ra, %0, %1;\nmbarrier.arrive.shared::cluster.b64 _, [ra];\n}" :: "r"(bar), "r"(cta) : "memory");
}
__device__ __forceinline__ void mbar_arrive_cta_release(uint32_t bar, uint32_t cta) {
  asm volatile("{\n.reg .b32 ra;\nmapa.shared::cluster.u32 ra, %0, %1;\nmbarrier.arrive.release.cluster.shared::cluster.b64 _, [ra];\n}" :: "r"(bar), "r"(cta) : "memory");
}
__device__ __forceinline__ bool mbar_test(uint32_t bar, uint32_t parity) {
  uint32_t ok;
  asm volatile("{\n.reg .pred P1;\nmbarrier.test_wait.parity.shared::cta.b64 P1, [%1], %2;\nselp.u32 %0, 1, 0, P1;\n}" : "=r"(ok) : "r"(bar), "r"(parity) : "memory");
  return ok;
}
__device__ __forceinline__ bool mbar_try(uint32_t bar, uint32_t parity) {
  uint32_t ok;
  asm volatile("{\n.reg .pred P1;\nmbarrier.try_wait.parity.shared::cta.b64 P1, [%1], %2;\nselp.u32 %0, 1, 0, P1;\n}" : "=r"(ok) : "r"(bar), "r"(parity) : "memory");
  return ok;
}
constexpr uint32_t SPIN_LIMIT = 1u << 22;
__device__ __forceinline__ void trap_if(bool c) { asm volatile("{\n.reg .pred P;\nsetp.ne.u32 P, %0, 0;\n@P trap;\n}" :: "r"((uint32_t)c)); }
__device__ __forceinline__ void mbar_wait(uint32_t bar, uint32_t parity) {
  asm volatile("{\n.reg .pred P1;\n.reg .u32 n;\nmbarrier.try_wait.parity.shared::cta.b64 P1, [%0], %1;\n@P1 bra DONE;\nmov.u32 n, 0;\n"
               "LOOP:\nmbarrier.try_wait.parity.shared::cta.b64 P1, [%0], %1;\n@P1 bra DONE;\nadd.u32 n, n, 1;\nsetp.gt.u32 P1, n, %2;\n@P1 trap;\nbra LOOP;\nDONE:\n}"
               :: "r"(bar), "r"(parity), "n"(SPIN_LIMIT) : "memory");
}
__device__ __forceinline__ void mbar_spin(uint32_t bar, uint32_t parity) {
  asm volatile("{\n.reg .pred P1;\nLOOP:\nmbarrier.try_wait.parity.shared::cta.b64 P1, [%0], %1;\n@!P1 bra LOOP;\n}" :: "r"(bar), "r"(parity) : "memory");
}
__device__ __forceinline__ bool mbar_try_long(uint32_t bar, uint32_t parity) {
  uint32_t ok;
  asm volatile("{\n.reg .pred P1;\nmbarrier.try_wait.parity.shared::cta.b64 P1, [%1], %2, %3;\nselp.u32 %0, 1, 0, P1;\n}" : "=r"(ok) : "r"(bar), "r"(parity), "r"(1000000) : "memory");
  return ok;
}
__device__ __forceinline__ void mbar_wait_sleep(uint32_t bar, uint32_t parity) {
  uint32_t n = 0;
  while (!mbar_try(bar, parity)) { trap_if(++n > SPIN_LIMIT); __nanosleep(100); }
}
__device__ __forceinline__ void mbar_wait_cluster(uint32_t bar, uint32_t parity) {
  asm volatile("{\n.reg .pred P1;\n.reg .u32 n;\nmov.u32 n, 0;\n"
               "LOOP:\nmbarrier.try_wait.parity.acquire.cluster.shared::cta.b64 P1, [%0], %1;\n@P1 bra DONE;\nadd.u32 n, n, 1;\nsetp.gt.u32 P1, n, %2;\n@P1 trap;\nbra LOOP;\nDONE:\n}"
               :: "r"(bar), "r"(parity), "n"(SPIN_LIMIT) : "memory");
}
__device__ __forceinline__ void tma_load_2d(uint32_t dst, const CUtensorMap* tm, int c0, int c1, uint32_t bar) {
  asm volatile("cp.async.bulk.tensor.2d.shared::cluster.global.mbarrier::complete_tx::bytes [%0], [%1, {%3, %4}], [%2];"
    :: "r"(dst), "l"(tm), "r"(bar), "r"(c0), "r"(c1) : "memory");
}
__device__ __forceinline__ void tma_load_2d_mc(uint32_t dst, const CUtensorMap* tm, int c0, int c1, uint32_t bar) {
  asm volatile("cp.async.bulk.tensor.2d.shared::cluster.global.mbarrier::complete_tx::bytes.multicast::cluster [%0], [%1, {%3, %4}], [%2], %5;"
    :: "r"(dst), "l"(tm), "r"(bar), "r"(c0), "r"(c1), "h"((uint16_t)3) : "memory");
}
__device__ __forceinline__ uint64_t policy_evict_first() { uint64_t p; asm volatile("createpolicy.fractional.L2::evict_first.b64 %0, 1.0;" : "=l"(p)); return p; }
__device__ __forceinline__ void tma_load_2d_hint(uint32_t dst, const CUtensorMap* tm, int c0, int c1, uint32_t bar, uint64_t pol) {
  asm volatile("cp.async.bulk.tensor.2d.shared::cluster.global.mbarrier::complete_tx::bytes.L2::cache_hint [%0], [%1, {%3, %4}], [%2], %5;"
    :: "r"(dst), "l"(tm), "r"(bar), "r"(c0), "r"(c1), "l"(pol) : "memory");
}
__device__ __forceinline__ void tma_load_2d_mc_hint(uint32_t dst, const CUtensorMap* tm, int c0, int c1, uint32_t bar, uint64_t pol) {
  asm volatile("cp.async.bulk.tensor.2d.shared::cluster.global.mbarrier::complete_tx::bytes.multicast::cluster.L2::cache_hint [%0], [%1, {%3, %4}], [%2], %5, %6;"
    :: "r"(dst), "l"(tm), "r"(bar), "r"(c0), "r"(c1), "h"((uint16_t)3), "l"(pol) : "memory");
}
__device__ __forceinline__ void tma_prefetch_2d(const CUtensorMap* tm, int c0, int c1) {
  asm volatile("cp.async.bulk.prefetch.tensor.2d.L2.global [%0, {%1, %2}];" :: "l"(tm), "r"(c0), "r"(c1) : "memory");
}
__device__ __forceinline__ void tma_prefetch_3d(const CUtensorMap* tm, int c1, int c2) {
  asm volatile("cp.async.bulk.prefetch.tensor.3d.L2.global [%0, {%1, %2, %3}];" :: "l"(tm), "r"(0), "r"(c1), "r"(c2) : "memory");
}
__device__ __forceinline__ void l2_prefetch(const void* p, uint32_t bytes) { asm volatile("cp.async.bulk.prefetch.L2.global [%0], %1;" :: "l"(p), "r"(bytes) : "memory"); }
__device__ __forceinline__ void tma_load_3d(uint32_t dst, const CUtensorMap* tm, int c1, int c2, uint32_t bar) {
  asm volatile("cp.async.bulk.tensor.3d.shared::cluster.global.mbarrier::complete_tx::bytes [%0], [%1, {%3, %4, %5}], [%2];"
    :: "r"(dst), "l"(tm), "r"(bar), "r"(0), "r"(c1), "r"(c2) : "memory");
}
__device__ __forceinline__ void tma_load_3d_mc(uint32_t dst, const CUtensorMap* tm, int c1, int c2, uint32_t bar) {
  asm volatile("cp.async.bulk.tensor.3d.shared::cluster.global.mbarrier::complete_tx::bytes.multicast::cluster [%0], [%1, {%3, %4, %5}], [%2], %6;"
    :: "r"(dst), "l"(tm), "r"(bar), "r"(0), "r"(c1), "r"(c2), "h"((uint16_t)3) : "memory");
}
__device__ __forceinline__ void tma_store_2d(const CUtensorMap* tm, uint32_t src, int c0, int c1) {
  asm volatile("cp.async.bulk.tensor.2d.global.shared::cta.bulk_group [%0, {%2, %3}], [%1];" :: "l"(tm), "r"(src), "r"(c0), "r"(c1) : "memory");
}
__device__ __forceinline__ void bulk_commit() { asm volatile("cp.async.bulk.commit_group;" ::: "memory"); }
template <int N> __device__ __forceinline__ void bulk_wait_read() { asm volatile("cp.async.bulk.wait_group.read %0;" :: "n"(N) : "memory"); }
template <int N> __device__ __forceinline__ void bulk_wait() { asm volatile("cp.async.bulk.wait_group %0;" :: "n"(N) : "memory"); }
__device__ __forceinline__ void fence_async_smem() { asm volatile("fence.proxy.async.shared::cta;" ::: "memory"); }
__device__ __forceinline__ void fence_async_global() { asm volatile("fence.proxy.async.global;" ::: "memory"); }
__device__ __forceinline__ void wgmma_fence() { asm volatile("wgmma.fence.sync.aligned;" ::: "memory"); }
__device__ __forceinline__ void wgmma_commit() { asm volatile("wgmma.commit_group.sync.aligned;" ::: "memory"); }
template <int N> __device__ __forceinline__ void wgmma_wait() { asm volatile("wgmma.wait_group.sync.aligned %0;" :: "n"(N) : "memory"); }
__device__ __forceinline__ uint64_t make_desc(uint32_t addr, uint32_t lbo, uint32_t sbo) {
  return (uint64_t)((addr & 0x3FFFF) >> 4) | ((uint64_t)(lbo >> 4) << 16) | ((uint64_t)(sbo >> 4) << 32) | (1ull << 62);
}
template <int N> __device__ __forceinline__ void fence_regs(float (&d)[N]) {
#pragma unroll
  for (int i = 0; i < N; i++) asm volatile("" : "+f"(d[i]) :: "memory");
}
template <int N> __device__ __forceinline__ void fence_regs(uint32_t (&d)[N]) {
#pragma unroll
  for (int i = 0; i < N; i++) asm volatile("" : "+r"(d[i]) :: "memory");
}
__device__ __forceinline__ void named_sync(int id) { asm volatile("bar.sync %0, 256;" :: "r"(id) : "memory"); }
__device__ __forceinline__ void named_arrive(int id) { asm volatile("bar.arrive %0, 256;" :: "r"(id) : "memory"); }
__device__ __forceinline__ void cluster_sync_all() { asm volatile("barrier.cluster.arrive.release.aligned;\nbarrier.cluster.wait.acquire.aligned;" ::: "memory"); }
__device__ __forceinline__ uint32_t cluster_rank() { uint32_t r; asm volatile("mov.u32 %0, %%cluster_ctarank;" : "=r"(r)); return r; }
__device__ __forceinline__ unsigned ld_acquire(const unsigned* p) { unsigned v; asm volatile("ld.acquire.gpu.global.u32 %0, [%1];" : "=r"(v) : "l"(p) : "memory"); return v; }
__device__ __forceinline__ void red_release(unsigned* p, unsigned v) { asm volatile("red.release.gpu.global.add.u32 [%0], %1;" :: "l"(p), "r"(v) : "memory"); }
__device__ __forceinline__ void flag_wait(const unsigned* p, unsigned target) {
  uint32_t n = 0;
  while (ld_acquire(p) < target) { trap_if(++n > SPIN_LIMIT); __nanosleep(20); }
}
__device__ __forceinline__ void st_relaxed_v4(float4* p, float a, float b, float c) {
  asm volatile("st.relaxed.gpu.global.v4.f32 [%0], {%1, %2, %3, %3};" :: "l"(p), "f"(a), "f"(b), "f"(c) : "memory");
}
__device__ __forceinline__ float4 ld_relaxed_v4(const float4* p) {
  float4 v; asm volatile("ld.relaxed.gpu.global.v4.f32 {%0, %1, %2, %3}, [%4];" : "=f"(v.x), "=f"(v.y), "=f"(v.z), "=f"(v.w) : "l"(p) : "memory"); return v;
}
__device__ __forceinline__ uint32_t pack_bf16(float lo, float hi) { uint32_t r; asm("cvt.rn.bf16x2.f32 %0, %1, %2;" : "=r"(r) : "f"(hi), "f"(lo)); return r; }
__device__ __forceinline__ float bf_lo(uint32_t v) { return __uint_as_float(v << 16); }
__device__ __forceinline__ float bf_hi(uint32_t v) { return __uint_as_float(v & 0xffff0000u); }
__device__ __forceinline__ float ex2(float x) { float y; asm("ex2.approx.ftz.f32 %0, %1;" : "=f"(y) : "f"(x)); return y; }
__device__ __forceinline__ float tanh_fast(float x) { float y; asm("tanh.approx.f32 %0, %1;" : "=f"(y) : "f"(x)); return y; }
__device__ __forceinline__ void stmatrix_x4(uint32_t addr, uint32_t a, uint32_t b, uint32_t c, uint32_t d) {
  asm volatile("stmatrix.sync.aligned.m8n8.x4.shared.b16 [%0], {%1, %2, %3, %4};" :: "r"(addr), "r"(a), "r"(b), "r"(c), "r"(d) : "memory");
}
__device__ __forceinline__ void ldmatrix_x4(uint32_t addr, uint32_t& a, uint32_t& b, uint32_t& c, uint32_t& d) {
  asm volatile("ldmatrix.sync.aligned.m8n8.x4.shared.b16 {%0, %1, %2, %3}, [%4];" : "=r"(a), "=r"(b), "=r"(c), "=r"(d) : "r"(addr) : "memory");
}
__device__ __forceinline__ uint32_t lane_id() { uint32_t l; asm volatile("mov.u32 %0, %%laneid;" : "=r"(l)); return l; }
__device__ __forceinline__ bool elect_one() {
  uint32_t r;
  asm volatile("{\n.reg .pred P;\nelect.sync _|P, 0xffffffff;\nselp.u32 %0, 1, 0, P;\n}" : "=r"(r));
  return r;
}
__device__ __forceinline__ uint64_t gtime() { uint64_t t; asm volatile("mov.u64 %0, %%globaltimer;" : "=l"(t)); return t; }

__device__ __forceinline__ void wgmma_m64n128k16_ss_tb0(float (&d)[64], uint64_t da, uint64_t db, int scale_d) {
  asm volatile("{\n.reg .pred p;\nsetp.ne.b32 p, %66, 0;\n"
    "wgmma.mma_async.sync.aligned.m64n128k16.f32.bf16.bf16 "
    "{%0, %1, %2, %3, %4, %5, %6, %7, %8, %9, %10, %11, %12, %13, %14, %15, %16, %17, %18, %19, %20, %21, %22, %23, %24, %25, %26, %27, %28, %29, %30, %31, %32, %33, %34, %35, %36, %37, %38, %39, %40, %41, %42, %43, %44, %45, %46, %47, %48, %49, %50, %51, %52, %53, %54, %55, %56, %57, %58, %59, %60, %61, %62, %63}, "
    "%64, %65, p, 1, 1, 0, 0;\n}\n"
    : "+f"(d[0]), "+f"(d[1]), "+f"(d[2]), "+f"(d[3]), "+f"(d[4]), "+f"(d[5]), "+f"(d[6]), "+f"(d[7]), "+f"(d[8]), "+f"(d[9]), "+f"(d[10]), "+f"(d[11]), "+f"(d[12]), "+f"(d[13]), "+f"(d[14]), "+f"(d[15]), "+f"(d[16]), "+f"(d[17]), "+f"(d[18]), "+f"(d[19]), "+f"(d[20]), "+f"(d[21]), "+f"(d[22]), "+f"(d[23]), "+f"(d[24]), "+f"(d[25]), "+f"(d[26]), "+f"(d[27]), "+f"(d[28]), "+f"(d[29]), "+f"(d[30]), "+f"(d[31]), "+f"(d[32]), "+f"(d[33]), "+f"(d[34]), "+f"(d[35]), "+f"(d[36]), "+f"(d[37]), "+f"(d[38]), "+f"(d[39]), "+f"(d[40]), "+f"(d[41]), "+f"(d[42]), "+f"(d[43]), "+f"(d[44]), "+f"(d[45]), "+f"(d[46]), "+f"(d[47]), "+f"(d[48]), "+f"(d[49]), "+f"(d[50]), "+f"(d[51]), "+f"(d[52]), "+f"(d[53]), "+f"(d[54]), "+f"(d[55]), "+f"(d[56]), "+f"(d[57]), "+f"(d[58]), "+f"(d[59]), "+f"(d[60]), "+f"(d[61]), "+f"(d[62]), "+f"(d[63])
    : "l"(da), "l"(db), "r"(scale_d));
}
__device__ __forceinline__ void wgmma_m64n256k16_ss_tb1(float (&d)[128], uint64_t da, uint64_t db, int scale_d) {
  asm volatile("{\n.reg .pred p;\nsetp.ne.b32 p, %130, 0;\n"
    "wgmma.mma_async.sync.aligned.m64n256k16.f32.bf16.bf16 "
    "{%0, %1, %2, %3, %4, %5, %6, %7, %8, %9, %10, %11, %12, %13, %14, %15, %16, %17, %18, %19, %20, %21, %22, %23, %24, %25, %26, %27, %28, %29, %30, %31, %32, %33, %34, %35, %36, %37, %38, %39, %40, %41, %42, %43, %44, %45, %46, %47, %48, %49, %50, %51, %52, %53, %54, %55, %56, %57, %58, %59, %60, %61, %62, %63, %64, %65, %66, %67, %68, %69, %70, %71, %72, %73, %74, %75, %76, %77, %78, %79, %80, %81, %82, %83, %84, %85, %86, %87, %88, %89, %90, %91, %92, %93, %94, %95, %96, %97, %98, %99, %100, %101, %102, %103, %104, %105, %106, %107, %108, %109, %110, %111, %112, %113, %114, %115, %116, %117, %118, %119, %120, %121, %122, %123, %124, %125, %126, %127}, "
    "%128, %129, p, 1, 1, 0, 1;\n}\n"
    : "+f"(d[0]), "+f"(d[1]), "+f"(d[2]), "+f"(d[3]), "+f"(d[4]), "+f"(d[5]), "+f"(d[6]), "+f"(d[7]), "+f"(d[8]), "+f"(d[9]), "+f"(d[10]), "+f"(d[11]), "+f"(d[12]), "+f"(d[13]), "+f"(d[14]), "+f"(d[15]), "+f"(d[16]), "+f"(d[17]), "+f"(d[18]), "+f"(d[19]), "+f"(d[20]), "+f"(d[21]), "+f"(d[22]), "+f"(d[23]), "+f"(d[24]), "+f"(d[25]), "+f"(d[26]), "+f"(d[27]), "+f"(d[28]), "+f"(d[29]), "+f"(d[30]), "+f"(d[31]), "+f"(d[32]), "+f"(d[33]), "+f"(d[34]), "+f"(d[35]), "+f"(d[36]), "+f"(d[37]), "+f"(d[38]), "+f"(d[39]), "+f"(d[40]), "+f"(d[41]), "+f"(d[42]), "+f"(d[43]), "+f"(d[44]), "+f"(d[45]), "+f"(d[46]), "+f"(d[47]), "+f"(d[48]), "+f"(d[49]), "+f"(d[50]), "+f"(d[51]), "+f"(d[52]), "+f"(d[53]), "+f"(d[54]), "+f"(d[55]), "+f"(d[56]), "+f"(d[57]), "+f"(d[58]), "+f"(d[59]), "+f"(d[60]), "+f"(d[61]), "+f"(d[62]), "+f"(d[63]), "+f"(d[64]), "+f"(d[65]), "+f"(d[66]), "+f"(d[67]), "+f"(d[68]), "+f"(d[69]), "+f"(d[70]), "+f"(d[71]), "+f"(d[72]), "+f"(d[73]), "+f"(d[74]), "+f"(d[75]), "+f"(d[76]), "+f"(d[77]), "+f"(d[78]), "+f"(d[79]), "+f"(d[80]), "+f"(d[81]), "+f"(d[82]), "+f"(d[83]), "+f"(d[84]), "+f"(d[85]), "+f"(d[86]), "+f"(d[87]), "+f"(d[88]), "+f"(d[89]), "+f"(d[90]), "+f"(d[91]), "+f"(d[92]), "+f"(d[93]), "+f"(d[94]), "+f"(d[95]), "+f"(d[96]), "+f"(d[97]), "+f"(d[98]), "+f"(d[99]), "+f"(d[100]), "+f"(d[101]), "+f"(d[102]), "+f"(d[103]), "+f"(d[104]), "+f"(d[105]), "+f"(d[106]), "+f"(d[107]), "+f"(d[108]), "+f"(d[109]), "+f"(d[110]), "+f"(d[111]), "+f"(d[112]), "+f"(d[113]), "+f"(d[114]), "+f"(d[115]), "+f"(d[116]), "+f"(d[117]), "+f"(d[118]), "+f"(d[119]), "+f"(d[120]), "+f"(d[121]), "+f"(d[122]), "+f"(d[123]), "+f"(d[124]), "+f"(d[125]), "+f"(d[126]), "+f"(d[127])
    : "l"(da), "l"(db), "r"(scale_d));
}
__device__ __forceinline__ void wgmma_m64n128k16_rs_tb1(float (&d)[64], uint32_t a0, uint32_t a1, uint32_t a2, uint32_t a3, uint64_t db, int scale_d) {
  asm volatile("{\n.reg .pred p;\nsetp.ne.b32 p, %69, 0;\n"
    "wgmma.mma_async.sync.aligned.m64n128k16.f32.bf16.bf16 "
    "{%0, %1, %2, %3, %4, %5, %6, %7, %8, %9, %10, %11, %12, %13, %14, %15, %16, %17, %18, %19, %20, %21, %22, %23, %24, %25, %26, %27, %28, %29, %30, %31, %32, %33, %34, %35, %36, %37, %38, %39, %40, %41, %42, %43, %44, %45, %46, %47, %48, %49, %50, %51, %52, %53, %54, %55, %56, %57, %58, %59, %60, %61, %62, %63}, "
    "{%64, %65, %66, %67}, %68, p, 1, 1, 1;\n}\n"
    : "+f"(d[0]), "+f"(d[1]), "+f"(d[2]), "+f"(d[3]), "+f"(d[4]), "+f"(d[5]), "+f"(d[6]), "+f"(d[7]), "+f"(d[8]), "+f"(d[9]), "+f"(d[10]), "+f"(d[11]), "+f"(d[12]), "+f"(d[13]), "+f"(d[14]), "+f"(d[15]), "+f"(d[16]), "+f"(d[17]), "+f"(d[18]), "+f"(d[19]), "+f"(d[20]), "+f"(d[21]), "+f"(d[22]), "+f"(d[23]), "+f"(d[24]), "+f"(d[25]), "+f"(d[26]), "+f"(d[27]), "+f"(d[28]), "+f"(d[29]), "+f"(d[30]), "+f"(d[31]), "+f"(d[32]), "+f"(d[33]), "+f"(d[34]), "+f"(d[35]), "+f"(d[36]), "+f"(d[37]), "+f"(d[38]), "+f"(d[39]), "+f"(d[40]), "+f"(d[41]), "+f"(d[42]), "+f"(d[43]), "+f"(d[44]), "+f"(d[45]), "+f"(d[46]), "+f"(d[47]), "+f"(d[48]), "+f"(d[49]), "+f"(d[50]), "+f"(d[51]), "+f"(d[52]), "+f"(d[53]), "+f"(d[54]), "+f"(d[55]), "+f"(d[56]), "+f"(d[57]), "+f"(d[58]), "+f"(d[59]), "+f"(d[60]), "+f"(d[61]), "+f"(d[62]), "+f"(d[63])
    : "r"(a0), "r"(a1), "r"(a2), "r"(a3), "l"(db), "r"(scale_d));
}
__device__ __forceinline__ void wgmma_m64n128k16_ss_tb1(float (&d)[64], uint64_t da, uint64_t db, int scale_d) {
  asm volatile("{\n.reg .pred p;\nsetp.ne.b32 p, %66, 0;\n"
    "wgmma.mma_async.sync.aligned.m64n128k16.f32.bf16.bf16 "
    "{%0, %1, %2, %3, %4, %5, %6, %7, %8, %9, %10, %11, %12, %13, %14, %15, %16, %17, %18, %19, %20, %21, %22, %23, %24, %25, %26, %27, %28, %29, %30, %31, %32, %33, %34, %35, %36, %37, %38, %39, %40, %41, %42, %43, %44, %45, %46, %47, %48, %49, %50, %51, %52, %53, %54, %55, %56, %57, %58, %59, %60, %61, %62, %63}, "
    "%64, %65, p, 1, 1, 0, 1;\n}\n"
    : "+f"(d[0]), "+f"(d[1]), "+f"(d[2]), "+f"(d[3]), "+f"(d[4]), "+f"(d[5]), "+f"(d[6]), "+f"(d[7]), "+f"(d[8]), "+f"(d[9]), "+f"(d[10]), "+f"(d[11]), "+f"(d[12]), "+f"(d[13]), "+f"(d[14]), "+f"(d[15]), "+f"(d[16]), "+f"(d[17]), "+f"(d[18]), "+f"(d[19]), "+f"(d[20]), "+f"(d[21]), "+f"(d[22]), "+f"(d[23]), "+f"(d[24]), "+f"(d[25]), "+f"(d[26]), "+f"(d[27]), "+f"(d[28]), "+f"(d[29]), "+f"(d[30]), "+f"(d[31]), "+f"(d[32]), "+f"(d[33]), "+f"(d[34]), "+f"(d[35]), "+f"(d[36]), "+f"(d[37]), "+f"(d[38]), "+f"(d[39]), "+f"(d[40]), "+f"(d[41]), "+f"(d[42]), "+f"(d[43]), "+f"(d[44]), "+f"(d[45]), "+f"(d[46]), "+f"(d[47]), "+f"(d[48]), "+f"(d[49]), "+f"(d[50]), "+f"(d[51]), "+f"(d[52]), "+f"(d[53]), "+f"(d[54]), "+f"(d[55]), "+f"(d[56]), "+f"(d[57]), "+f"(d[58]), "+f"(d[59]), "+f"(d[60]), "+f"(d[61]), "+f"(d[62]), "+f"(d[63])
    : "l"(da), "l"(db), "r"(scale_d));
}

enum { TM_XN, TM_WSP, TM_U, TM_O, TM_Q, TM_X, TM_SA, TM_G, TM_K, TM_V, TM_WO2, TM_WIN, TM_WQ, TM_Z2, TM_WOUT, TM_WO,
       TS_Q, TS_O, TS_Z2, TS_U, TS_OUT, TS_SA, TS_G, TM_COUNT };
enum { T_Z2 = 0, T_Q = 1, T_U = 2, T_ATT = 3, T_SA = 4, T_FIN = 5, T_END = 7 };
constexpr int NCLUSTER = 66, MAXI = 14;
struct alignas(64) Params {
  CUtensorMap tm[TM_COUNT];
  const bf16* x;
  const bf16* b_sp;
  uint16_t items[NCLUSTER][MAXI];
};

constexpr uint32_t G_STAGE = 49152, G_A = 16384, KV_SLOT = 32768;
constexpr uint32_t OFF_Q1 = 163840, OFF_Q0 = 196608, OFF_BAR = 229376, SMEM_BYTES = OFF_BAR + 256 + 1024;
constexpr uint32_t B_GF = 0, B_GE = 32, B_KF = 64, B_KE = 104, B_QF = 144, B_QE = 160, B_XF = 176, B_XR = 184, B_SIG = 192, B_DONE = 200;
#define SA_HEADS 20
#define OUT_PF 8
constexpr float SM_C = 0.08838834764831845f * 1.4426950408889634f;
constexpr float GELU_A = 0.7978845608028654f, GELU_B = 0.7978845608028654f * 0.044715f;
constexpr float SM_THR = 1024.f;

#define TRACE(w, i)
#define FT(c, tag)

struct Ring { uint32_t s, ph; };
template <int N> __device__ __forceinline__ void ring_adv(Ring& r) { if (++r.s == N) { r.s = 0; r.ph ^= 1; } }

struct Cons {
  uint32_t sb;
  uint32_t rank;
  int w;
  int warp;
  Ring g;
  uint32_t gd;
  uint32_t pend;
};

__device__ __forceinline__ void flush_pending(Cons& c) {
  if (elect_one()) {
    bulk_wait<0>();
    if (c.pend == 2) { mbar_arrive_cta(c.sb + OFF_BAR + B_XF, 0); mbar_arrive_cta(c.sb + OFF_BAR + B_XF, 1); }
    else if (c.pend != 1) mbar_arrive(c.pend);
    mbar_arrive(c.sb + OFF_BAR + B_SIG);
  }
  c.pend = 0;
  __syncwarp();
}
__device__ __forceinline__ void wait_full_flush(Cons& c, uint32_t bar, uint32_t ph, bool force) {
  if (c.pend != 0) {
    bool fl = force || !mbar_test(bar, ph);
    if (__any_sync(0xffffffffu, fl)) flush_pending(c);
  }
  mbar_spin(bar, ph);
}

__device__ __forceinline__ void release_slot(const Cons& c, uint32_t bar, bool mc) {
  if (lane_id() == 0 && (c.warp & 3) < 2) mbar_arrive_cta(bar, mc ? (uint32_t)(c.warp & 1) : c.rank);
}
constexpr uint64_t DESC_HI = (uint64_t)0x40000040u << 32;

template <bool FIRST> __device__ __forceinline__ void gemm_step(float (&acc)[128], Cons& c, bool force_flush) {
  wait_full_flush(c, c.sb + OFF_BAR + B_GF + 8 * c.g.s, c.g.ph, force_flush);
  const uint32_t st = c.gd + c.g.s * (G_STAGE >> 4);
  const uint32_t da = st + c.w * 512 + (1u << 16), db = st + (G_A >> 4) + ((8192u >> 4) << 16);
  wgmma_fence();
#pragma unroll
  for (int kk = 0; kk < 4; kk++) wgmma_m64n256k16_ss_tb1(acc, DESC_HI | (da + kk * 2), DESC_HI | (db + kk * 128), !(FIRST && kk == 0));
  wgmma_commit();
}

__device__ __forceinline__ void store_chunk(const Cons& c, uint32_t buf, const uint32_t* pk, const CUtensorMap* tm, int col, int row) {
  const uint32_t ln = lane_id();
  const uint32_t a = buf + ((ln & 15) << 7);
  const uint32_t x = ln & 7, hi = ln >> 4;
#pragma unroll
  for (int i = 0; i < 4; i++) stmatrix_x4(a + (((2 * i + hi) ^ x) << 4), pk[4 * i], pk[4 * i + 1], pk[4 * i + 2], pk[4 * i + 3]);
  fence_async_smem();
  __syncwarp();
  if (elect_one()) { tma_store_2d(tm, buf, col, row); bulk_commit(); }
}
__device__ __forceinline__ void store_pair(uint32_t buf, const uint32_t* pk, const CUtensorMap* tm, int col, int row) {
  const uint32_t ln = lane_id();
  const uint32_t a = buf + ((ln & 15) << 7);
  const uint32_t x = ln & 7, hi = ln >> 4;
#pragma unroll
  for (int i = 0; i < 8; i++) stmatrix_x4(a + (i >> 2) * 16384 + (((2 * (i & 3) + hi) ^ x) << 4), pk[4 * i], pk[4 * i + 1], pk[4 * i + 2], pk[4 * i + 3]);
  fence_async_smem();
  __syncwarp();
  if (elect_one()) { tma_store_2d(tm, buf, col, row); tma_store_2d(tm, buf + 16384, col + 64, row); bulk_commit(); }
}
template <int N> __device__ __forceinline__ void stage_wait(const Cons& c) { if (elect_one()) bulk_wait_read<N>(); __syncwarp(); }

__device__ __forceinline__ float act2_fn(float x, float a, float b) {
  return fmaf(x, tanh_fast(x * fmaf(x * x, b, a)), x);
}
__device__ __forceinline__ float quad_sum(float v) { v += __shfl_xor_sync(0xffffffffu, v, 1); v += __shfl_xor_sync(0xffffffffu, v, 2); return v; }
__device__ __forceinline__ float quad_max(float v) { v = fmaxf(v, __shfl_xor_sync(0xffffffffu, v, 1)); v = fmaxf(v, __shfl_xor_sync(0xffffffffu, v, 2)); return v; }

struct Shadow {
  int act;
  int store;
  int row, col;
  float ca, cb;
};
__device__ __forceinline__ void rotate16(uint32_t (&h)[64]) {
#pragma unroll
  for (int i = 0; i < 16; i++)
    asm volatile("{\n.reg .b32 t;\nmov.b32 t, %0;\nmov.b32 %0, %1;\nmov.b32 %1, %2;\nmov.b32 %2, %3;\nmov.b32 %3, t;\n}" : "+r"(h[i]), "+r"(h[i + 16]), "+r"(h[i + 32]), "+r"(h[i + 48]));
}
__device__ __forceinline__ void store_held(Cons& c, const Params& p, uint32_t (&held)[64], int ts, int row, int col, int ch) {
  stage_wait<1>(c);
  store_chunk(c, c.sb + OFF_Q0 + c.warp * 2048 + (ch & 1) * 16384, held, &p.tm[ts], col + ch * 64, row + c.warp * 16);
}

template <int O>
__device__ __forceinline__ void act_block(uint32_t (&held)[64], const Shadow& sh, bool first, float& u0, float& u1, float& s0, float& s1, float& q0, float& q1) {
#pragma unroll
  for (int i = O; i < O + 4; i += 2) {
    const float a0 = act2_fn(bf_lo(held[i]), sh.ca, sh.cb), a1 = act2_fn(bf_hi(held[i]), sh.ca, sh.cb);
    const float b0 = act2_fn(bf_lo(held[i + 1]), sh.ca, sh.cb), b1 = act2_fn(bf_hi(held[i + 1]), sh.ca, sh.cb);
    if (i == 0 && first) { u0 = a0; u1 = b0; }
    float d;
    d = a0 - u0; s0 += d; q0 = fmaf(d, d, q0); d = a1 - u0; s0 += d; q0 = fmaf(d, d, q0);
    d = b0 - u1; s1 += d; q1 = fmaf(d, d, q1); d = b1 - u1; s1 += d; q1 = fmaf(d, d, q1);
    held[i] = pack_bf16(a0, a1); held[i + 1] = pack_bf16(b0, b1);
  }
}

__device__ __forceinline__ void gemm_seg(float (&acc)[128], uint32_t (&held)[64], Cons& c, const Params& p, Shadow& sh, int nsteps, float tag) {
  const bool elected = lane_id() == 0 && (c.warp & 3) < 2;
  uint32_t rel;
  asm("mapa.shared::cluster.u32 %0, %1, %2;" : "=r"(rel) : "r"(c.sb + OFF_BAR + B_GE), "r"((uint32_t)(c.warp & 1)));
  gemm_step<true>(acc, c, false);
  uint32_t prev = c.g.s;
  ring_adv<4>(c.g);
  int k = 1;
#define G_STEP(FLUSH)                                                                                                   \
  { gemm_step<false>(acc, c, FLUSH);                                                                                    \
    FT(c, 70);                                                                                                          \
    wgmma_wait<1>();                                                                                                    \
    if (elected) asm volatile("mbarrier.arrive.shared::cluster.b64 _, [%0];" :: "r"(rel + 8 * prev) : "memory");        \
    prev = c.g.s;                                                                                                       \
    ring_adv<4>(c.g);                                                                                                   \
    k++; }
  if (sh.act != 0) {
    float u0 = 0.f, u1 = 0.f, s0 = 0.f, s1 = 0.f, q0 = 0.f, q1 = 0.f;
#pragma unroll 1
    while (true) {
      act_block<0>(held, sh, k == 1, u0, u1, s0, s1, q0, q1);
      G_STEP(false)
      act_block<4>(held, sh, false, u0, u1, s0, s1, q0, q1);
      G_STEP(true)
      act_block<8>(held, sh, false, u0, u1, s0, s1, q0, q1);
      G_STEP(false)
      act_block<12>(held, sh, false, u0, u1, s0, s1, q0, q1);
      rotate16(held);
      if (k == 16) break;
      G_STEP(false)
    }
    if (sh.act == 2) {
      const int ln = lane_id(), row0 = sh.row + c.warp * 16 + (ln >> 2), ql = ln & 3;
      const float m0 = fmaf(s0, 1.f / 64, u0), m1 = fmaf(s1, 1.f / 64, u1);
      q0 -= s0 * s0 * (1.f / 64); q1 -= s1 * s1 * (1.f / 64);
      const float mu0 = quad_sum(m0) * 0.25f, mu1 = quad_sum(m1) * 0.25f;
      q0 = quad_sum(fmaf(64.f * (m0 - mu0), m0 - mu0, q0)); q1 = quad_sum(fmaf(64.f * (m1 - mu1), m1 - mu1, q1));
      if (ql < 2) st_relaxed_v4(&g_stats[(row0 + 8 * ql) * 8 + (sh.col >> 8)], ql ? mu1 : mu0, ql ? q1 : q0, tag);
    }
  }
  if (sh.store >= 0) {
    float a0 = 0.f, a1 = 0.f, r0 = 1.f, r1 = 1.f;
    if (sh.store == TS_Z2) {
      const int ln = lane_id(), row0 = sh.row + c.warp * 16 + (ln >> 2), ql = ln & 3;
      float4 t[4];
      while (true) {
        bool ok = true;
#pragma unroll
        for (int i = 0; i < 4; i++) {
          t[i] = ld_relaxed_v4(&g_stats[(row0 + 8 * (i >> 1)) * 8 + min(ql + 4 * (i & 1), 6)]);
          ok = ok && __float_as_uint(t[i].z) == __float_as_uint(tag);
        }
        if (__all_sync(0xffffffffu, ok)) break;
        __nanosleep(100);
      }
      const float wl = ql == 3 ? 0.f : 1.f;
      const float u0 = quad_sum(fmaf(wl, t[1].x, t[0].x)) * (1.f / 7), u1 = quad_sum(fmaf(wl, t[3].x, t[2].x)) * (1.f / 7);
      float d;
      d = t[0].x - u0; float v0 = fmaf(256.f * d, d, t[0].y);
      d = t[1].x - u0; v0 = fmaf(wl, fmaf(256.f * d, d, t[1].y), v0);
      d = t[2].x - u1; float v1 = fmaf(256.f * d, d, t[2].y);
      d = t[3].x - u1; v1 = fmaf(wl, fmaf(256.f * d, d, t[3].y), v1);
      r0 = rsqrtf(fmaxf(quad_sum(v0), 0.f) * (1.f / FH) + 4e-5f); r1 = rsqrtf(fmaxf(quad_sum(v1), 0.f) * (1.f / FH) + 4e-5f);
      a0 = u0; a1 = u1;
    }
#pragma unroll 1
    for (int ch = 0; ch < 4; ch++) {
      G_STEP(false)
      if (sh.store == TS_Z2) {
#pragma unroll
        for (int i = 0; i < 8; i++) {
          held[2 * i] = pack_bf16((bf_lo(held[2 * i]) - a0) * r0, (bf_hi(held[2 * i]) - a0) * r0);
          held[2 * i + 1] = pack_bf16((bf_lo(held[2 * i + 1]) - a1) * r1, (bf_hi(held[2 * i + 1]) - a1) * r1);
        }
      }
      G_STEP(true)
      store_held(c, p, held, sh.store, sh.row, sh.col, ch);
      rotate16(held);
    }
    c.pend = 1;
  }
  const int flush_at = k + 2;
#pragma unroll 1
  while (k < nsteps) G_STEP(k >= flush_at)
  wgmma_wait<0>();
  fence_regs(acc);
  if (elected) asm volatile("mbarrier.arrive.shared::cluster.b64 _, [%0];" :: "r"(rel + 8 * prev) : "memory");
  sh.store = sh.act == 2 ? TS_Z2 : -1;
  sh.act = 0;
}

__device__ __forceinline__ void softmax_exp(const float (&S)[64], uint32_t (&P)[32], float m0, float m1, float& s0, float& s1) {
  float a0 = 0.f, a1 = 0.f, b0 = 0.f, b1 = 0.f;
#pragma unroll
  for (int j = 0; j < 16; j++) {
    const float p0 = ex2(fmaf(S[4 * j], SM_C, -m0)), p1 = ex2(fmaf(S[4 * j + 1], SM_C, -m0));
    const float p2 = ex2(fmaf(S[4 * j + 2], SM_C, -m1)), p3 = ex2(fmaf(S[4 * j + 3], SM_C, -m1));
    a0 += p0; b0 += p1; a1 += p2; b1 += p3;
    P[2 * j] = pack_bf16(p0, p1); P[2 * j + 1] = pack_bf16(p2, p3);
  }
  s0 = a0 + b0; s1 = a1 + b1;
}
__device__ __forceinline__ void row_max(const float (&S)[64], float& x0, float& x1) {
  float a0 = fmaxf(S[0], S[1]), a1 = fmaxf(S[2], S[3]);
#pragma unroll
  for (int j = 1; j < 16; j++) { a0 = fmaxf(a0, fmaxf(S[4 * j], S[4 * j + 1])); a1 = fmaxf(a1, fmaxf(S[4 * j + 2], S[4 * j + 3])); }
  x0 = fmaxf(quad_max(a0) * SM_C, -1e38f); x1 = fmaxf(quad_max(a1) * SM_C, -1e38f);
}

__device__ __forceinline__ void issue_qk(float (&S)[64], uint32_t da, uint32_t db) {
#pragma unroll
  for (int kk = 0; kk < 8; kk++) {
    const uint32_t o = (kk >> 2) * 1024 + (kk & 3) * 2;
    wgmma_m64n128k16_ss_tb0(S, DESC_HI | (da + o), DESC_HI | (db + o), kk > 0);
  }
}
__device__ __forceinline__ void issue_pv(float (&O)[64], const uint32_t (&P)[32], uint32_t db, int acc) {
#pragma unroll
  for (int kk = 0; kk < 8; kk++) wgmma_m64n128k16_rs_tb1(O, P[4 * kk], P[4 * kk + 1], P[4 * kk + 2], P[4 * kk + 3], DESC_HI | (db + kk * 128), (acc || kk > 0));
}

#define FA(k)
__device__ __forceinline__ void att_epilogue(Cons& c, const Params& p, float (&O)[64], float l0, float l1, uint32_t qbuf, int item) {
  const int h = (item >> 5) & 31, m = (item & 31) * 2 + c.rank;
  const float i0 = __fdividef(1.f, quad_sum(l0)), i1 = __fdividef(1.f, quad_sum(l1));
  const uint32_t base = c.sb + (qbuf ? OFF_Q1 : OFF_Q0) + c.warp * 2048;
  uint32_t pk[32];
#pragma unroll
  for (int j = 0; j < 16; j++) {
    pk[2 * j] = pack_bf16(O[4 * j] * i0, O[4 * j + 1] * i0);
    pk[2 * j + 1] = pack_bf16(O[4 * j + 2] * i1, O[4 * j + 3] * i1);
  }
  store_pair(base, pk, &p.tm[TS_O], h * 128, m * 128 + c.warp * 16);
  c.pend = c.sb + OFF_BAR + B_QE + 8 * qbuf;
}

#define ATT_ISSUE(PIN, ACC)                                                        \
  named_sync(1 + c.w);                                                             \
  FA(1);                                                                           \
  wgmma_fence();                                                                   \
  issue_qk(S, qd, kd); wgmma_commit();                                             \
  if (g > 1) release_slot(c, vrel, true);                                          \
  mbar_spin(vbar, vph);                                                            \
  issue_pv(O, PIN, vd, ACC); wgmma_commit();                                       \
  named_arrive(2 - c.w);                                                           \
  FA(2);                                                                           \
  krel = kbar + (B_KE - B_KF); vrel = vbar + (B_KE - B_KF);                        \
  g++;                                                                             \
  if (g < total) { kd = kd0 + kv.s * (KV_SLOT >> 4); kbar = bars + B_KF + 8 * kv.s; kph = kv.ph; ring_adv<5>(kv); } \
  vd = vd0 + kv.s * (KV_SLOT >> 4); vbar = bars + B_KF + 8 * kv.s; vph = kv.ph; ring_adv<5>(kv); \
  wgmma_wait<1>();                                                                 \
  fence_regs(S);                                                                   \
  FA(3);                                                                           \
  kready = mbar_test(kbar, kph);                                                   \
  if (g <= total) release_slot(c, krel, true);

#define ATT_REFRESH()                                                              \
  { float x0, x1;                                                                  \
    row_max(S, x0, x1);                                                            \
    x0 = fmaxf(x0, m0); x1 = fmaxf(x1, m1);                                        \
    f0 = ex2(m0 - x0); f1 = ex2(m1 - x1);                                          \
    m0 = x0; m1 = x1; l0 *= f0; l1 *= f1; }

#define ATT_SOFTMAX(POUT)                                                          \
  _Pragma("unroll 1")                                                              \
  while (true) {                                                                   \
    if (__builtin_expect(fresh, 0)) ATT_REFRESH();                                 \
    softmax_exp(S, POUT, m0, m1, s0, s1);                                          \
    bad = !(s0 <= SM_THR && s1 <= SM_THR);                                         \
    slow = fresh || __any_sync(0xffffffffu, bad || !kready);                       \
    if (__builtin_expect(!slow, 1)) break;                                         \
    if (fresh || !__any_sync(0xffffffffu, bad)) break;                             \
    fresh = true;                                                                  \
  }                                                                                \
  l0 += s0; l1 += s1;

#define ATT_RESCALE()                                                              \
  { _Pragma("unroll")                                                              \
    for (int i = 0; i < 16; i++) { O[4 * i] *= f0; O[4 * i + 1] *= f0; O[4 * i + 2] *= f1; O[4 * i + 3] *= f1; } }

__device__ __forceinline__ void att_run(Cons& c, const Params& p, const uint16_t* items, int n) {
  const uint32_t bars = c.sb + OFF_BAR;
  float S[64], O[64];
  uint32_t P0[32], P1[32];
#pragma unroll
  for (int i = 0; i < 64; i++) O[i] = 0.f;
#pragma unroll
  for (int i = 0; i < 32; i++) P1[i] = 0u;
  fence_regs(O); fence_regs(P1);
  float m0 = 0.f, m1 = 0.f, l0 = 0.f, l1 = 0.f, f0 = 1.f, f1 = 1.f, s0, s1, pl0 = 0.f, pl1 = 0.f;
  const int total = 16 * n;
  int g = 0;
  Ring kv = {1, 0};
  uint32_t kbar = bars + B_KF, kph = 0, vbar = bars + B_KF, vph = 0, krel, vrel = 0;
  const uint32_t kd0 = (uint32_t)make_desc(c.sb, 16, 1024), vd0 = (uint32_t)make_desc(c.sb, 16384, 1024);
  uint32_t qd = kd0 + ((OFF_Q1 + c.w * 8192) >> 4), kd = kd0, vd = vd0;
  bool fresh, kready, bad, slow;
  if (elect_one()) { bulk_wait_read<0>(); mbar_arrive(bars + B_QE); }
  __syncwarp();
  if (c.w == 1) named_arrive(1);
  wait_full_flush(c, bars + B_QF + 8, 0, false);
  wait_full_flush(c, bars + B_KF, 0, false);
#pragma unroll 1
  while (true) {
    FA(0);
    ATT_ISSUE(P1, 1)
    const bool first = ((g - 1) & 15) == 0;
    fresh = first;
    if (first) { pl0 = l0; pl1 = l1; m0 = m1 = -1e38f; l0 = l1 = 0.f; }
    ATT_SOFTMAX(P0)
    wgmma_wait<0>(); fence_regs(O); fence_regs(P1);
    FA(4);
    if (__builtin_expect(slow || c.pend != 0, 0)) {
      if (first) {
        if (g > 1) {
          const int t = ((g - 1) >> 4) - 1;
          if (g > total) release_slot(c, vrel, true);
          att_epilogue(c, p, O, pl0, pl1, (t & 1) ^ 1, items[t]);
          TRACE(c.w, c.tr + t + 1); FT(c, 24);
          if (g > total) break;
        }
      } else {
        if (fresh) ATT_RESCALE();
        if (c.pend != 0) flush_pending(c);
      }
      mbar_spin(kbar, kph);
    }
    FA(0);
    ATT_ISSUE(P0, (g & 15) != 1)
    fresh = false;
    ATT_SOFTMAX(P1)
    wgmma_wait<0>(); fence_regs(O); fence_regs(P0);
    FA(4);
    if (__builtin_expect(slow || (g & 15) == 0, 0)) {
      if (fresh) ATT_RESCALE();
      mbar_spin(kbar, kph);
      if ((g & 15) == 0 && g < total) {
        const int t = g >> 4;
        const uint32_t qb = (t & 1) ^ 1;
        mbar_spin(bars + B_QF + 8 * qb, (t >> 1) & 1);
        qd = kd0 + (((qb ? OFF_Q1 : OFF_Q0) + c.w * 8192) >> 4);
      }
    }
  }
  if (c.w == 0) named_sync(1);
  fence_regs(S); fence_regs(P1);
}

__global__ void __cluster_dims__(2, 1, 1) __launch_bounds__(384, 1) fused_kernel(const __grid_constant__ Params p) {
  extern __shared__ uint8_t smem_raw[];
  const uint32_t sb = (smem_u32(smem_raw) + 1023) & ~1023u;
  const uint32_t bars = sb + OFF_BAR;
  const int tid = threadIdx.x, lane = tid & 31;
  const int warp_id = __shfl_sync(0xffffffffu, tid >> 5, 0), wg = warp_id >> 2;
  const uint32_t rank = blockIdx.x & 1;
  const uint16_t* items = p.items[blockIdx.x >> 1];
  const int gw = blockIdx.x * 8 + warp_id - 4;
  uint4 xv[2][4];
  if (wg != 0 && gw < SEQ / 2) {
#pragma unroll
    for (int rr = 0; rr < 2; rr++)
#pragma unroll
      for (int i = 0; i < 4; i++) xv[rr][i] = __ldg(reinterpret_cast<const uint4*>(p.x + (size_t)(gw * 2 + rr) * DM) + i * 32 + lane);
  }
  if (warp_id == 1 && lane < TM_COUNT) asm volatile("prefetch.tensormap [%0];" :: "l"(&p.tm[lane]) : "memory");
  if (tid == 0) {
    for (int i = 0; i < 4; i++) { mbar_init(bars + B_GF + 8 * i, 1); mbar_init(bars + B_GE + 8 * i, 4); }
    for (int i = 0; i < 5; i++) { mbar_init(bars + B_KF + 8 * i, 1); mbar_init(bars + B_KE + 8 * i, 4); }
    for (int i = 0; i < 2; i++) { mbar_init(bars + B_QF + 8 * i, 1); mbar_init(bars + B_QE + 8 * i, 8); }
    mbar_init(bars + B_XF, 16); mbar_init(bars + B_SIG, 8); mbar_init(bars + B_DONE, 8);
    asm volatile("fence.mbarrier_init.release.cluster;" ::: "memory");
  }
  asm volatile("barrier.cluster.arrive.relaxed.aligned;" ::: "memory");

  if (wg == 0) {
    asm volatile("setmaxnreg.dec.sync.aligned.u32 40;");
    asm volatile("barrier.cluster.wait.acquire.aligned;" ::: "memory");
    if (warp_id == 0) {
      Ring g = {0, 1};
      int it = 0;
      if (elect_one()) {
#pragma unroll 1
        for (;; it++) {
          const int item = items[it], type = item >> 12, b = item & 31, row = (((item >> 5) & 31) * 2 + rank) * 128;
          if (type >= T_ATT) break;
#pragma unroll 1
          for (int seg = 0; seg < (type == T_U ? 2 : 1); seg++) {
            const CUtensorMap* tA = &p.tm[seg ? TM_WSP : TM_XN];
            const CUtensorMap* tB = &p.tm[seg ? TM_Z2 : (type == T_Q ? TM_WQ : TM_WIN)];
            const int bchunk = b * 4 + (type == T_Z2 ? 28 : 0) + rank * 2;
            const unsigned* fl = seg ? &g_flags[F_Z2 + b * 32] : &g_flags[F_XN + (row >> 2)];
            const unsigned tgt = seg ? 16 : 128;
            int k = 0;
            if (it == 0 && seg == 0) {
              for (; k < 4; k++) {
                mbar_expect_tx(bars + B_GF + 8 * k, G_STAGE);
                tma_load_3d_mc(sb + k * G_STAGE + G_A + rank * 16384, tB, k * 64, bchunk, bars + B_GF + 8 * k);
              }
              g.ph ^= 1;
            }
            flag_wait(fl, tgt);
            fence_async_global();
            for (int x = 0; x < k; x++) tma_load_2d(sb + x * G_STAGE, tA, x * 64, row, bars + B_GF + 8 * x);
#pragma unroll 1
            for (; k < (seg ? 32 : 16); k++) {
              mbar_wait(bars + B_GE + 8 * g.s, g.ph);
              const uint32_t st = sb + g.s * G_STAGE, fb = bars + B_GF + 8 * g.s;
              mbar_expect_tx(fb, G_STAGE);
              tma_load_2d(st, tA, k * 64, row, fb);
              tma_load_3d_mc(st + G_A + rank * 16384, tB, k * 64, bchunk, fb);
              ring_adv<4>(g);
            }
          }
        }
      }
      it = __shfl_sync(0xffffffffu, it, 0); g.ph = __shfl_sync(0xffffffffu, g.ph, 0);
      int n = 0;
      while ((items[it + n] >> 12) == T_ATT) n++;
      Ring kv = {0, 1};
      if (elect_one()) {
        const uint64_t pol = policy_evict_first();
        int prow = 0;
#pragma unroll 1
        for (int x = -1; x <= 32 * n; x++) {
          const int gb = x >> 1, t = x < 0 ? 0 : gb >> 4;
          const int hrow = ((items[it + t] >> 5) & 31) * SEQ;
          const bool isv = (x & 1) || x == 32 * n;
          if (x >= 0 && x != 1) {
            mbar_wait(bars + B_KE + 8 * kv.s, kv.ph);
            mbar_expect_tx(bars + B_KF + 8 * kv.s, KV_SLOT);
            tma_load_2d_mc_hint(sb + kv.s * KV_SLOT + rank * 16384, &p.tm[isv ? TM_V : TM_K], rank * 64, isv ? prow : hrow + (gb & 15) * 128,
                                bars + B_KF + 8 * kv.s, pol);
            ring_adv<5>(kv);
          }
          if (x & 1) prow = hrow + (gb & 15) * 128;
          if (x < 0 || ((x & 31) == 11 && t + 1 < n)) {
            const int tq = x < 0 ? 0 : t + 1;
            const int im = items[it + tq], h = (im >> 5) & 31, m = (im & 31) * 2 + rank;
            const uint32_t qb = (tq & 1) ^ 1;
            flag_wait(&g_flags[F_Q + m * 16 + (h >> 1)], 1);
            fence_async_global();
            if (x < 0) {
              tma_prefetch_2d(&p.tm[TM_K], rank * 64, hrow); tma_prefetch_2d(&p.tm[TM_K], rank * 64, hrow + 128);
              tma_prefetch_2d(&p.tm[TM_V], rank * 64, hrow);
              tma_prefetch_2d(&p.tm[TM_Q], h * 128, m * 128); tma_prefetch_2d(&p.tm[TM_Q], h * 128 + 64, m * 128);
              for (int i = 0; i < 4; i++) mbar_wait(bars + B_GE + 8 * i, g.ph);
            }
            mbar_wait(bars + B_QE + 8 * qb, ((tq >> 1) & 1) ^ qb);
            const uint32_t dst = sb + (qb ? OFF_Q1 : OFF_Q0), fb = bars + B_QF + 8 * qb;
            mbar_expect_tx(fb, 32768);
            tma_load_2d_hint(dst, &p.tm[TM_Q], h * 128, m * 128, fb, pol);
            tma_load_2d_hint(dst + 16384, &p.tm[TM_Q], h * 128 + 64, m * 128, fb, pol);
          }
        }
      }
      __syncwarp();
      it += n;
      uint32_t ready = 0;
      auto wait_head = [&](int m, int h) {
        if ((ready >> h) & 1) return;
        uint32_t cnt = 0;
        while (true) {
          ready = __ballot_sync(0xffffffffu, ld_acquire(&g_flags[F_O + m * 32 + lane]) != 0);
          if ((ready >> h) & 1) break;
          trap_if(++cnt > SPIN_LIMIT);
          __nanosleep(20);
        }
        fence_async_global();
      };
      int item = items[it];
      if ((item >> 12) == T_SA) {
        const int m = ((item >> 5) & 31) * 2 + rank, b = item & 31;
        if (lane == 0) flag_wait(&g_flags[F_U + m * 32], 7);
        __syncwarp();
        fence_async_global();
#pragma unroll 1
        for (int i = -OUT_PF; i < 28 + 2 * SA_HEADS; i++) {
          if (i >= 0) {
            const bool so = i >= 28;
            const int k = so ? i - 28 : i;
            if (so) wait_head(m, k >> 1);
            if (elect_one()) {
              if (i == 0) { Ring h = kv; for (int x = 0; x < 5; x++) { mbar_wait(bars + B_KE + 8 * h.s, h.ph); ring_adv<5>(h); } }
              if (i == 3) mbar_wait(bars + B_XF, 0);
              mbar_wait(bars + B_GE + 8 * g.s, g.ph);
              const uint32_t st = sb + g.s * G_STAGE, fb = bars + B_GF + 8 * g.s;
              mbar_expect_tx(fb, G_STAGE);
              tma_load_2d(st, &p.tm[so ? TM_O : TM_U], k * 64, m * 128, fb);
              tma_load_3d_mc(st + G_A + rank * 16384, &p.tm[so ? TM_WO : TM_WOUT], k * 64, b * 4 + rank * 2, fb);
            }
            ring_adv<4>(g);
          }
          const int ip = i + OUT_PF;
          if (ip < 28 + 2 * SA_HEADS && elect_one()) {
            const bool so = ip >= 28;
            const int k = so ? ip - 28 : ip;
            if ((ip & 3) == b && (!so || ((ready >> (k >> 1)) & 1))) tma_prefetch_2d(&p.tm[so ? TM_O : TM_U], k * 64, m * 128);
            if ((ip & 7) == (m >> 1)) tma_prefetch_3d(&p.tm[so ? TM_WO : TM_WOUT], k * 64, b * 4 + rank * 2);
          }
          __syncwarp();
        }
        item = items[++it];
      }
      if ((item >> 12) == T_FIN) {
        const int m = (item >> 5) & 31, col = (item & 31) * 256 + rank * 128;
        ready = 0;
#pragma unroll 1
        for (int i = 2 * SA_HEADS; i < 67; i++) {
          if (i < 64) wait_head(m, i >> 1);
          if (elect_one()) {
            if (i == 2 * SA_HEADS) {
              for (int h = SA_HEADS + (m & 7); h < NH; h += 8) tma_prefetch_2d(&p.tm[TM_WO2], col + (m >> 3) * 64, h * 128);
              tma_prefetch_2d(&p.tm[TM_X], col, m * 128); tma_prefetch_2d(&p.tm[TM_X], col + 64, m * 128);
              for (int x = 0; x < 4; x++) { mbar_wait(bars + B_GE + 8 * g.s, g.ph); ring_adv<4>(g); }
            }
            if (i == 65) { flag_wait(&g_flags[F_S + m * 4 + (item & 31)], 2); fence_async_global(); }
            mbar_wait(bars + B_KE + 8 * kv.s, kv.ph);
            const uint32_t dst = sb + kv.s * KV_SLOT, fb = bars + B_KF + 8 * kv.s;
            mbar_expect_tx(fb, KV_SLOT);
            if (i < 64 && !(i & 1)) {
              tma_load_2d_mc(dst + rank * 16384, &p.tm[TM_O], (i + rank) * 64, m * 128, fb);
            } else {
              const CUtensorMap* tm = &p.tm[i < 64 ? TM_WO2 : TM_X + (i - 64)];
              const int row = i < 64 ? (i >> 1) * 128 : m * 128;
              tma_load_2d(dst, tm, col, row, fb);
              tma_load_2d(dst + 16384, tm, col + 64, row, fb);
            }
            ring_adv<5>(kv);
          }
          __syncwarp();
        }
      }
    } else if (warp_id == 1) {
      if (lane == 0) {
        uint32_t ph = 0;
        for (int it = 0;; it++) {
          const int item = items[(items[0] >> 12) == T_Z2 && it < 2 ? it ^ 1 : it], type = item >> 12, a = (item >> 5) & 31, b = item & 31;
          if (type >= T_FIN) break;
          unsigned* f = type == T_Z2 ? &g_flags[F_Z2 + b * 32] : type == T_Q ? &g_flags[F_Q + (a * 2 + rank) * 16 + b]
                      : type == T_U ? &g_flags[F_U + (a * 2 + rank) * 32] : type == T_ATT ? &g_flags[F_O + (b * 2 + rank) * 32 + a]
                      : &g_flags[F_S + (a * 2 + rank) * 4 + b];
          for (int r = type == T_SA ? 2 : 1; r > 0; r--) {
            mbar_wait_sleep(bars + B_SIG, ph);
            ph ^= 1;
            red_release(f, 1);
          }
        }
      }
      __syncwarp();
    } else if (warp_id == 2) {
      if (lane == 0) {
        const uint64_t t0 = gtime();
        while (!mbar_try_long(bars + B_DONE, 0)) trap_if(gtime() - t0 > 2000000000ull);
      }
      __syncwarp();
    }
    cluster_sync_all();
    if (warp_id == 0) {
      unsigned last = 0;
      if (lane == 0) { __threadfence(); last = atomicInc(&g_done, gridDim.x - 1) == gridDim.x - 1; }
      last = __shfl_sync(0xffffffffu, last, 0);
      if (last) {
        for (int i = lane; i < F_TOTAL / 4; i += 32) reinterpret_cast<uint4*>(g_flags)[i] = make_uint4(0, 0, 0, 0);
        if (lane == 0) g_epoch = g_epoch + 1;
      }
    }
  } else {
    asm volatile("setmaxnreg.inc.sync.aligned.u32 232;");
    Cons c;
    c.sb = sb; c.rank = rank; c.w = wg - 1; c.warp = warp_id - 4;
    c.g = {0, 0}; c.pend = 0; c.gd = (sb & 0x3FFFF) >> 4;
    TRACE(c.w, 0);
    FT(c, 1);
    const unsigned epoch = __ldcg(&g_epoch);
    if (gw < SEQ / 2) {
#pragma unroll 1
      for (int rr = 0; rr < 2; rr++) {
        float f[32];
#pragma unroll
        for (int i = 0; i < 4; i++) {
          const uint4 v = rr ? xv[1][i] : xv[0][i];
          f[8 * i + 0] = bf_lo(v.x); f[8 * i + 1] = bf_hi(v.x); f[8 * i + 2] = bf_lo(v.y); f[8 * i + 3] = bf_hi(v.y);
          f[8 * i + 4] = bf_lo(v.z); f[8 * i + 5] = bf_hi(v.z); f[8 * i + 6] = bf_lo(v.w); f[8 * i + 7] = bf_hi(v.w);
        }
        float s = 0.f;
#pragma unroll
        for (int i = 0; i < 32; i++) s += f[i];
#pragma unroll
        for (int o = 16; o; o >>= 1) s += __shfl_xor_sync(0xffffffffu, s, o);
        const float mean = s * (1.f / DM);
        float q = 0.f;
#pragma unroll
        for (int i = 0; i < 32; i++) { f[i] -= mean; q = fmaf(f[i], f[i], q); }
#pragma unroll
        for (int o = 16; o; o >>= 1) q += __shfl_xor_sync(0xffffffffu, q, o);
        const float rs = rsqrtf(q * (1.f / DM) + 1e-5f);
#pragma unroll
        for (int i = 0; i < 4; i++) {
          uint4 o;
          o.x = pack_bf16(f[8 * i] * rs, f[8 * i + 1] * rs); o.y = pack_bf16(f[8 * i + 2] * rs, f[8 * i + 3] * rs);
          o.z = pack_bf16(f[8 * i + 4] * rs, f[8 * i + 5] * rs); o.w = pack_bf16(f[8 * i + 6] * rs, f[8 * i + 7] * rs);
          reinterpret_cast<uint4*>(g_xn + (size_t)(gw * 2 + rr) * DM)[i * 32 + lane] = o;
        }
      }
      __syncwarp();
      if (lane == 0) red_release(&g_flags[F_XN + (gw >> 6) * 32], 2);
    }
    asm volatile("barrier.cluster.wait.acquire.aligned;" ::: "memory");
    const float tag = __uint_as_float(epoch + 1);
    const uint32_t stg = sb + OFF_Q0 + c.warp * 2048;
    int natt = 0;
    int it = 0;
    uint32_t held[64];
#pragma unroll
    for (int i = 0; i < 64; i++) held[i] = 0u;
    Shadow sh = {0, -1, 0, 0, 0.f, 0.f};
#pragma unroll 1
    while (true) {
      const int item = items[it], type = item >> 12, a = (item >> 5) & 31, b = item & 31;
      if (type == T_END) break;
      TRACE(c.w, 1 + it);
      FT(c, 2);
      if (type == T_ATT) {
        int n = 1;
        while ((items[it + n] >> 12) == T_ATT) n++;
        att_run(c, p, items + it, n);
#pragma unroll
        for (int i = 0; i < 64; i++) held[i] = 0u;
        natt = n;
        it += n;
        continue;
      }
      if (type == T_FIN) {
        float acc[64];
        Ring kv = {(uint32_t)(32 * natt) % 5, ((uint32_t)(32 * natt) / 5) & 1};
#pragma unroll 1
        for (int h = SA_HEADS; h < NH; h++) {
          const uint32_t sa = kv.s; wait_full_flush(c, bars + B_KF + 8 * kv.s, kv.ph, false); ring_adv<5>(kv);
          const uint32_t sw = kv.s; wait_full_flush(c, bars + B_KF + 8 * kv.s, kv.ph, false); ring_adv<5>(kv);
          const uint32_t da = c.gd + sa * (KV_SLOT >> 4) + c.w * 512 + (1u << 16), db = c.gd + sw * (KV_SLOT >> 4) + ((16384u >> 4) << 16);
          wgmma_fence();
          if (h == SA_HEADS) wgmma_m64n128k16_ss_tb1(acc, DESC_HI | da, DESC_HI | db, 0);
          else wgmma_m64n128k16_ss_tb1(acc, DESC_HI | da, DESC_HI | db, 1);
#pragma unroll
          for (int kk = 1; kk < 8; kk++) wgmma_m64n128k16_ss_tb1(acc, DESC_HI | (da + (kk >> 2) * 1024 + (kk & 3) * 2), DESC_HI | (db + kk * 128), 1);
          wgmma_commit();
          FT(c, 70);
          if (c.pend != 0) flush_pending(c);
          if (h + 1 < NH) {
            wgmma_wait<0>();
            release_slot(c, bars + B_KE + 8 * sa, true); release_slot(c, bars + B_KE + 8 * sw, true);
          }
        }
        const uint32_t ln = lane_id();
        uint32_t in[3][32];
#pragma unroll
        for (int t = 0; t < 3; t++) {
          mbar_spin(bars + B_KF + 8 * kv.s, kv.ph);
          const uint32_t xa = sb + kv.s * KV_SLOT + c.warp * 2048 + ((ln & 15) << 7);
#pragma unroll
          for (int i = 0; i < 8; i++)
            ldmatrix_x4(xa + (i >> 2) * 16384 + (((2 * (i & 3) + (ln >> 4)) ^ (ln & 7)) << 4), in[t][4 * i], in[t][4 * i + 1], in[t][4 * i + 2], in[t][4 * i + 3]);
          ring_adv<5>(kv);
        }
        wgmma_wait<0>();
        fence_regs(acc);
        TRACE(c.w, 32 + it);
        FT(c, 3);
#pragma unroll
        for (int i = 0; i < 32; i++)
          in[0][i] = pack_bf16(fmaf(0.5f * (acc[2 * i] + bf_lo(in[1][i])), bf_lo(in[2][i]), bf_lo(in[0][i])),
                               fmaf(0.5f * (acc[2 * i + 1] + bf_hi(in[1][i])), bf_hi(in[2][i]), bf_hi(in[0][i])));
        stage_wait<0>(c);
        store_pair(stg, in[0], &p.tm[TS_OUT], b * 256 + rank * 128, a * 128 + c.warp * 16);
        break;
      }
      float acc[128];
      const bool sa = type == T_SA;
      if (sa) c.pend = 2;
      bool more = type >= T_U;
      int nsteps = sa ? 28 : 16;
      const bool direct = sh.act == 2 || (items[it + 1] >> 12) >= T_ATT;
      uint32_t bias0 = 0, bias1 = 0;
#pragma unroll 1
      while (true) {
        gemm_seg(acc, held, c, p, sh, nsteps, tag);
        if (!more && direct) break;
#pragma unroll
        for (int i = 0; i < 64; i++) held[i] = pack_bf16(acc[2 * i], acc[2 * i + 1]);
        if (!more) break;
        more = false;
        nsteps = sa ? 2 * SA_HEADS : 32;
        sh.act = 1; sh.ca = sa ? 0.5f : GELU_A; sh.cb = sa ? 0.f : GELU_B;
        if (sa) {
          sh.store = TS_G; sh.row = (a * 2 + rank) * 128; sh.col = b * 256;
        } else {
          const int row0 = (a * 2 + rank) * 128 + c.warp * 16 + (lane_id() >> 2);
          asm volatile("ld.global.nc.u16 %0, [%1];" : "=r"(bias0) : "l"(p.b_sp + row0));
          asm volatile("ld.global.nc.u16 %0, [%1];" : "=r"(bias1) : "l"(p.b_sp + row0 + 8));
        }
      }
      TRACE(c.w, 32 + it);
      FT(c, 3);
      if (type == T_U) {
        const float add0 = 0.5f * bf_lo(bias0), add1 = 0.5f * bf_lo(bias1);
#pragma unroll
        for (int i = 0; i < 32; i++) {
          acc[4 * i] = fmaf(acc[4 * i], 0.5f, add0) * bf_lo(held[2 * i]); acc[4 * i + 1] = fmaf(acc[4 * i + 1], 0.5f, add0) * bf_hi(held[2 * i]);
          acc[4 * i + 2] = fmaf(acc[4 * i + 2], 0.5f, add1) * bf_lo(held[2 * i + 1]); acc[4 * i + 3] = fmaf(acc[4 * i + 3], 0.5f, add1) * bf_hi(held[2 * i + 1]);
        }
      }
      if (direct) {
        if (c.pend != 0) flush_pending(c);
#pragma unroll
        for (int h = 0; h < 2; h++) {
          uint32_t pk[32];
#pragma unroll
          for (int i = 0; i < 32; i++) pk[i] = pack_bf16(acc[64 * h + 2 * i], acc[64 * h + 2 * i + 1]);
          stage_wait<0>(c);
          store_pair(stg, pk, &p.tm[type == T_U ? TS_U : (sa ? TS_SA : TS_Q)], b * 256 + h * 128, (a * 2 + rank) * 128 + c.warp * 16);
        }
        c.pend = 1;
      } else {
        sh.row = (a * 2 + rank) * 128; sh.col = b * 256;
        if (type == T_Q) sh.store = TS_Q;
        else { sh.act = 2; sh.ca = GELU_A; sh.cb = GELU_B; }
      }
      it++;
    }
    if (c.pend != 0) flush_pending(c);
    FT(c, 63);
    if (elect_one()) { mbar_arrive(bars + B_DONE); bulk_wait<0>(); }
    FT(c, 0);
    TRACE(c.w, 31);
    __syncwarp();
    cluster_sync_all();
  }
}

typedef CUresult (*PFN_encodeTiled)(CUtensorMap*, CUtensorMapDataType, cuuint32_t, void*, const cuuint64_t*, const cuuint64_t*, const cuuint32_t*, const cuuint32_t*,
                                    CUtensorMapInterleave, CUtensorMapSwizzle, CUtensorMapL2promotion, CUtensorMapFloatOOBfill);
static PFN_encodeTiled s_encode = nullptr;
static void tm_2d(CUtensorMap* tm, const void* ptr, uint64_t rows, uint64_t cols, uint32_t box_rows) {
  cuuint64_t dims[2] = {cols, rows}; cuuint64_t strides[1] = {cols * 2}; cuuint32_t box[2] = {64, box_rows}; cuuint32_t es[2] = {1, 1};
  CUresult r = s_encode(tm, CU_TENSOR_MAP_DATA_TYPE_BFLOAT16, 2, (void*)ptr, dims, strides, box, es, CU_TENSOR_MAP_INTERLEAVE_NONE,
                        CU_TENSOR_MAP_SWIZZLE_128B, CU_TENSOR_MAP_L2_PROMOTION_L2_256B, CU_TENSOR_MAP_FLOAT_OOB_FILL_NONE);
  if (r != CUDA_SUCCESS) fprintf(stderr, "tensor map encode failed (%d)\n", (int)r);
}
static void tm_3d(CUtensorMap* tm, const void* ptr, uint64_t rows, uint64_t cols) {
  cuuint64_t dims[3] = {64, rows, cols / 64}; cuuint64_t strides[2] = {cols * 2, 128}; cuuint32_t box[3] = {64, 64, 2}; cuuint32_t es[3] = {1, 1, 1};
  CUresult r = s_encode(tm, CU_TENSOR_MAP_DATA_TYPE_BFLOAT16, 3, (void*)ptr, dims, strides, box, es, CU_TENSOR_MAP_INTERLEAVE_NONE,
                        CU_TENSOR_MAP_SWIZZLE_128B, CU_TENSOR_MAP_L2_PROMOTION_L2_256B, CU_TENSOR_MAP_FLOAT_OOB_FILL_NONE);
  if (r != CUDA_SUCCESS) fprintf(stderr, "tensor map encode failed (%d)\n", (int)r);
}
static inline uint16_t mk(int type, int a, int b) { return (uint16_t)(type << 12 | a << 5 | b); }

static void build_schedule(Params& P) {
  int cnt[NCLUSTER];
  for (int c = 0; c < NCLUSTER; c++) { cnt[c] = 0; for (int i = 0; i < MAXI; i++) P.items[c][i] = mk(T_END, 0, 0); }
  auto push = [&](int c, uint16_t v) { P.items[c][cnt[c]++] = v; };
  int natt[NCLUSTER], nq[NCLUSTER];
  for (int c = 0; c < NCLUSTER; c++) { natt[c] = c < 32 ? 3 : (c < 56 ? 5 : 4); nq[c] = c < 56 ? 1 : (c < 64 ? 7 : 8); }
  for (int c = 0; c < 56; c++) push(c, mk(T_Z2, c % 8, c / 8));
  int qi = 0;
  for (int slot = 0; slot < 8; slot++)
    for (int c = NCLUSTER - 1; c >= 0; c--) {
      const int first = c < 56 ? 1 : 0;
      if (slot >= first && slot < first + nq[c]) { push(c, mk(T_Q, qi % 8, qi / 8)); qi++; }
    }
  for (int c = 0; c < 56; c++) push(c, mk(T_U, c % 8, c / 8));
  int ai = 0;
  for (int slot = 0; slot < 5; slot++)
    for (int c = 0; c < NCLUSTER; c++) {
      const int first = c < 56 ? 0 : 1;
      if (slot >= first && slot < first + natt[c]) { push(c, mk(T_ATT, ai / 8, ai % 8)); ai++; }
    }
  for (int c = 0; c < 32; c++) push(c, mk(T_SA, c % 8, c / 8));
  for (int c = 0; c < 64; c++) push(c, mk(T_FIN, c % 16, c / 16));
  if (qi != 128 || ai != 256) fprintf(stderr, "bad schedule %d %d\n", qi, ai);
}

static Params s_params;
extern "C" void kernel_launch(void* const* d_in, const int* in_sizes, int n_in, void* d_out, int out_size) {
  (void)in_sizes; (void)n_in; (void)out_size;
  if (!s_encode) {
    void* fn = nullptr; cudaDriverEntryPointQueryResult qr;
    cudaGetDriverEntryPoint("cuTensorMapEncodeTiled", &fn, cudaEnableDefault, &qr);
    s_encode = (PFN_encodeTiled)fn;
    cudaFuncSetAttribute(fused_kernel, cudaFuncAttributeMaxDynamicSharedMemorySize, SMEM_BYTES);
    build_schedule(s_params);
  }
  Params& P = s_params;
  void *xn, *q, *o, *z2, *u, *gg, *sa;
  cudaGetSymbolAddress(&gg, g_g); cudaGetSymbolAddress(&sa, g_sa);
  cudaGetSymbolAddress(&xn, g_xn); cudaGetSymbolAddress(&q, g_q); cudaGetSymbolAddress(&o, g_o);
  cudaGetSymbolAddress(&z2, g_z2); cudaGetSymbolAddress(&u, g_u);
  tm_2d(&P.tm[TM_XN], xn, SEQ, DM, 128); tm_2d(&P.tm[TM_WSP], d_in[7], SEQ, SEQ, 128); tm_2d(&P.tm[TM_U], u, SEQ, FH, 128);
  tm_2d(&P.tm[TM_O], o, SEQ, HD, 128); tm_2d(&P.tm[TM_Q], q, SEQ, HD, 128); tm_2d(&P.tm[TM_X], d_in[0], SEQ, DM, 128);
  tm_2d(&P.tm[TM_K], d_in[1], NH * SEQ, 128, 128); tm_2d(&P.tm[TM_V], d_in[2], NH * SEQ, 128, 128);
  tm_2d(&P.tm[TM_SA], sa, SEQ, DM, 128); tm_2d(&P.tm[TM_G], gg, SEQ, DM, 128); tm_2d(&P.tm[TM_WO2], d_in[4], HD, DM, 128);
  tm_2d(&P.tm[TS_SA], sa, SEQ, DM, 16); tm_2d(&P.tm[TS_G], gg, SEQ, DM, 16);
  tm_3d(&P.tm[TM_WIN], d_in[6], DM, FF); tm_3d(&P.tm[TM_WQ], d_in[3], DM, HD); tm_3d(&P.tm[TM_Z2], z2, SEQ, FH);
  tm_3d(&P.tm[TM_WOUT], d_in[9], FH, DM); tm_3d(&P.tm[TM_WO], d_in[4], HD, DM);
  tm_2d(&P.tm[TS_Q], q, SEQ, HD, 16); tm_2d(&P.tm[TS_O], o, SEQ, HD, 16); tm_2d(&P.tm[TS_Z2], z2, SEQ, FH, 16);
  tm_2d(&P.tm[TS_U], u, SEQ, FH, 16); tm_2d(&P.tm[TS_OUT], d_out, SEQ, DM, 16);
  P.x = (const bf16*)d_in[0]; P.b_sp = (const bf16*)d_in[8];
  fused_kernel<<<2 * NCLUSTER, 384, SMEM_BYTES, cudaStreamPerThread>>>(P);
}
```

```cpp
#include <cuda_runtime.h>
#include <cuda_bf16.h>
#include <cuda.h>
#include <stdint.h>
#include <stdio.h>

typedef __nv_bfloat16 bf16;

constexpr int SEQ = 2048, DM = 1024, NH = 32, HD = 4096, FF = 3584, FH = 1792;

__device__ __align__(1024) bf16 g_xn[SEQ * DM];
__device__ __align__(1024) bf16 g_q[SEQ * HD];
__device__ __align__(1024) bf16 g_o[SEQ * HD];
__device__ __align__(1024) bf16 g_z2[SEQ * FH];
__device__ __align__(1024) bf16 g_u[SEQ * FH];
__device__ __align__(1024) float4 g_stats[SEQ * 8];
__device__ __align__(1024) bf16 g_g[SEQ * DM];
__device__ __align__(1024) bf16 g_sa[SEQ * DM];
constexpr int F_XN = 0;
constexpr int F_Z2 = 512;
constexpr int F_Q = 768;
constexpr int F_U = 1024;
constexpr int F_O = 1536;
constexpr int F_S = 2048;
constexpr int F_TOTAL = 2112;
__device__ __align__(1024) unsigned g_flags[F_TOTAL];
__device__ unsigned g_done;
__device__ unsigned g_epoch;

__device__ __forceinline__ uint32_t smem_u32(const void* p) { return (uint32_t)__cvta_generic_to_shared(p); }
__device__ __forceinline__ void mbar_init(uint32_t bar, uint32_t cnt) { asm volatile("mbarrier.init.shared::cta.b64 [%0], %1;" :: "r"(bar), "r"(cnt)); }
__device__ __forceinline__ void mbar_expect_tx(uint32_t bar, uint32_t bytes) { asm volatile("mbarrier.arrive.expect_tx.shared::cta.b64 _, [%0], %1;" :: "r"(bar), "r"(bytes) : "memory"); }
__device__ __forceinline__ void mbar_arrive(uint32_t bar) { asm volatile("mbarrier.arrive.shared::cta.b64 _, [%0];" :: "r"(bar) : "memory"); }
__device__ __forceinline__ void mbar_arrive_cta(uint32_t bar, uint32_t cta) {
  asm volatile("{\n.reg .b32 ra;\nmapa.shared::cluster.u32 ra, %0, %1;\nmbarrier.arrive.shared::cluster.b64 _, [ra];\n}" :: "r"(bar), "r"(cta) : "memory");
}
__device__ __forceinline__ void mbar_arrive_cta_release(uint32_t bar, uint32_t cta) {
  asm volatile("{\n.reg .b32 ra;\nmapa.shared::cluster.u32 ra, %0, %1;\nmbarrier.arrive.release.cluster.shared::cluster.b64 _, [ra];\n}" :: "r"(bar), "r"(cta) : "memory");
}
__device__ __forceinline__ bool mbar_test(uint32_t bar, uint32_t parity) {
  uint32_t ok;
  asm volatile("{\n.reg .pred P1;\nmbarrier.test_wait.parity.shared::cta.b64 P1, [%1], %2;\nselp.u32 %0, 1, 0, P1;\n}" : "=r"(ok) : "r"(bar), "r"(parity) : "memory");
  return ok;
}
__device__ __forceinline__ bool mbar_try(uint32_t bar, uint32_t parity) {
  uint32_t ok;
  asm volatile("{\n.reg .pred P1;\nmbarrier.try_wait.parity.shared::cta.b64 P1, [%1], %2;\nselp.u32 %0, 1, 0, P1;\n}" : "=r"(ok) : "r"(bar), "r"(parity) : "memory");
  return ok;
}
constexpr uint32_t SPIN_LIMIT = 1u << 22;
__device__ __forceinline__ void trap_if(bool c) { asm volatile("{\n.reg .pred P;\nsetp.ne.u32 P, %0, 0;\n@P trap;\n}" :: "r"((uint32_t)c)); }
__device__ __forceinline__ void mbar_wait(uint32_t bar, uint32_t parity) {
  asm volatile("{\n.reg .pred P1;\n.reg .u32 n;\nmbarrier.try_wait.parity.shared::cta.b64 P1, [%0], %1;\n@P1 bra DONE;\nmov.u32 n, 0;\n"
               "LOOP:\nmbarrier.try_wait.parity.shared::cta.b64 P1, [%0], %1;\n@P1 bra DONE;\nadd.u32 n, n, 1;\nsetp.gt.u32 P1, n, %2;\n@P1 trap;\nbra LOOP;\nDONE:\n}"
               :: "r"(bar), "r"(parity), "n"(SPIN_LIMIT) : "memory");
}
__device__ __forceinline__ void mbar_spin(uint32_t bar, uint32_t parity) {
  asm volatile("{\n.reg .pred P1;\nLOOP:\nmbarrier.try_wait.parity.shared::cta.b64 P1, [%0], %1;\n@!P1 bra LOOP;\n}" :: "r"(bar), "r"(parity) : "memory");
}
__device__ __forceinline__ bool mbar_try_long(uint32_t bar, uint32_t parity) {
  uint32_t ok;
  asm volatile("{\n.reg .pred P1;\nmbarrier.try_wait.parity.shared::cta.b64 P1, [%1], %2, %3;\nselp.u32 %0, 1, 0, P1;\n}" : "=r"(ok) : "r"(bar), "r"(parity), "r"(2000) : "memory");
  return ok;
}
__device__ __forceinline__ void mbar_wait_sleep(uint32_t bar, uint32_t parity, uint32_t ns) {
  uint32_t n = 0;
  while (!mbar_test(bar, parity)) { trap_if(++n > SPIN_LIMIT * 4); __nanosleep(ns); }
}
__device__ __forceinline__ void mbar_wait_long(uint32_t bar, uint32_t parity) {
  uint32_t n = 0;
  while (!mbar_try_long(bar, parity)) trap_if(++n > SPIN_LIMIT);
}
__device__ __forceinline__ void mbar_wait_cluster(uint32_t bar, uint32_t parity) {
  asm volatile("{\n.reg .pred P1;\n.reg .u32 n;\nmov.u32 n, 0;\n"
               "LOOP:\nmbarrier.try_wait.parity.acquire.cluster.shared::cta.b64 P1, [%0], %1;\n@P1 bra DONE;\nadd.u32 n, n, 1;\nsetp.gt.u32 P1, n, %2;\n@P1 trap;\nbra LOOP;\nDONE:\n}"
               :: "r"(bar), "r"(parity), "n"(SPIN_LIMIT) : "memory");
}
__device__ __forceinline__ void tma_load_2d(uint32_t dst, const CUtensorMap* tm, int c0, int c1, uint32_t bar) {
  asm volatile("cp.async.bulk.tensor.2d.shared::cluster.global.mbarrier::complete_tx::bytes [%0], [%1, {%3, %4}], [%2];"
    :: "r"(dst), "l"(tm), "r"(bar), "r"(c0), "r"(c1) : "memory");
}
__device__ __forceinline__ void tma_load_2d_mc(uint32_t dst, const CUtensorMap* tm, int c0, int c1, uint32_t bar) {
  asm volatile("cp.async.bulk.tensor.2d.shared::cluster.global.mbarrier::complete_tx::bytes.multicast::cluster [%0], [%1, {%3, %4}], [%2], %5;"
    :: "r"(dst), "l"(tm), "r"(bar), "r"(c0), "r"(c1), "h"((uint16_t)3) : "memory");
}
__device__ __forceinline__ uint64_t policy_evict_normal() { uint64_t p; asm volatile("createpolicy.fractional.L2::evict_normal.b64 %0, 1.0;" : "=l"(p)); return p; }
__device__ __forceinline__ uint64_t policy_evict_first() { uint64_t p; asm volatile("createpolicy.fractional.L2::evict_first.b64 %0, 1.0;" : "=l"(p)); return p; }
__device__ __forceinline__ void tma_load_2d_hint(uint32_t dst, const CUtensorMap* tm, int c0, int c1, uint32_t bar, uint64_t pol) {
  asm volatile("cp.async.bulk.tensor.2d.shared::cluster.global.mbarrier::complete_tx::bytes.L2::cache_hint [%0], [%1, {%3, %4}], [%2], %5;"
    :: "r"(dst), "l"(tm), "r"(bar), "r"(c0), "r"(c1), "l"(pol) : "memory");
}
__device__ __forceinline__ void tma_load_2d_mc_hint(uint32_t dst, const CUtensorMap* tm, int c0, int c1, uint32_t bar, uint64_t pol) {
  asm volatile("cp.async.bulk.tensor.2d.shared::cluster.global.mbarrier::complete_tx::bytes.multicast::cluster.L2::cache_hint [%0], [%1, {%3, %4}], [%2], %5, %6;"
    :: "r"(dst), "l"(tm), "r"(bar), "r"(c0), "r"(c1), "h"((uint16_t)3), "l"(pol) : "memory");
}
__device__ __forceinline__ void tma_prefetch_2d(const CUtensorMap* tm, int c0, int c1) {
  asm volatile("cp.async.bulk.prefetch.tensor.2d.L2.global [%0, {%1, %2}];" :: "l"(tm), "r"(c0), "r"(c1) : "memory");
}
__device__ __forceinline__ void tma_prefetch_3d(const CUtensorMap* tm, int c1, int c2) {
  asm volatile("cp.async.bulk.prefetch.tensor.3d.L2.global [%0, {%1, %2, %3}];" :: "l"(tm), "r"(0), "r"(c1), "r"(c2) : "memory");
}
__device__ __forceinline__ void l2_prefetch(const void* p, uint32_t bytes) { asm volatile("cp.async.bulk.prefetch.L2.global [%0], %1;" :: "l"(p), "r"(bytes) : "memory"); }
__device__ __forceinline__ void tma_load_3d(uint32_t dst, const CUtensorMap* tm, int c1, int c2, uint32_t bar) {
  asm volatile("cp.async.bulk.tensor.3d.shared::cluster.global.mbarrier::complete_tx::bytes [%0], [%1, {%3, %4, %5}], [%2];"
    :: "r"(dst), "l"(tm), "r"(bar), "r"(0), "r"(c1), "r"(c2) : "memory");
}
__device__ __forceinline__ void tma_load_3d_mc(uint32_t dst, const CUtensorMap* tm, int c1, int c2, uint32_t bar) {
  asm volatile("cp.async.bulk.tensor.3d.shared::cluster.global.mbarrier::complete_tx::bytes.multicast::cluster [%0], [%1, {%3, %4, %5}], [%2], %6;"
    :: "r"(dst), "l"(tm), "r"(bar), "r"(0), "r"(c1), "r"(c2), "h"((uint16_t)3) : "memory");
}
__device__ __forceinline__ void tma_store_2d(const CUtensorMap* tm, uint32_t src, int c0, int c1) {
  asm volatile("cp.async.bulk.tensor.2d.global.shared::cta.bulk_group [%0, {%2, %3}], [%1];" :: "l"(tm), "r"(src), "r"(c0), "r"(c1) : "memory");
}
__device__ __forceinline__ void bulk_commit() { asm volatile("cp.async.bulk.commit_group;" ::: "memory"); }
template <int N> __device__ __forceinline__ void bulk_wait_read() { asm volatile("cp.async.bulk.wait_group.read %0;" :: "n"(N) : "memory"); }
template <int N> __device__ __forceinline__ void bulk_wait() { asm volatile("cp.async.bulk.wait_group %0;" :: "n"(N) : "memory"); }
__device__ __forceinline__ void fence_async_smem() { asm volatile("fence.proxy.async.shared::cta;" ::: "memory"); }
__device__ __forceinline__ void fence_async_global() { asm volatile("fence.proxy.async.global;" ::: "memory"); }
__device__ __forceinline__ void wgmma_fence() { asm volatile("wgmma.fence.sync.aligned;" ::: "memory"); }
__device__ __forceinline__ void wgmma_commit() { asm volatile("wgmma.commit_group.sync.aligned;" ::: "memory"); }
template <int N> __device__ __forceinline__ void wgmma_wait() { asm volatile("wgmma.wait_group.sync.aligned %0;" :: "n"(N) : "memory"); }
__device__ __forceinline__ uint64_t make_desc(uint32_t addr, uint32_t lbo, uint32_t sbo) {
  return (uint64_t)((addr & 0x3FFFF) >> 4) | ((uint64_t)(lbo >> 4) << 16) | ((uint64_t)(sbo >> 4) << 32) | (1ull << 62);
}
template <int N> __device__ __forceinline__ void fence_regs(float (&d)[N]) {
#pragma unroll
  for (int i = 0; i < N; i++) asm volatile("" : "+f"(d[i]) :: "memory");
}
template <int N> __device__ __forceinline__ void fence_regs(uint32_t (&d)[N]) {
#pragma unroll
  for (int i = 0; i < N; i++) asm volatile("" : "+r"(d[i]) :: "memory");
}
__device__ __forceinline__ void named_sync(int id) { asm volatile("bar.sync %0, 256;" :: "r"(id) : "memory"); }
__device__ __forceinline__ void named_arrive(int id) { asm volatile("bar.arrive %0, 256;" :: "r"(id) : "memory"); }
__device__ __forceinline__ void pp_sync(bool w) { asm volatile("{\n.reg .pred p;\nsetp.ne.u32 p, %0, 0;\n@p bar.sync 2, 256;\n@!p bar.sync 1, 256;\n}" :: "r"((uint32_t)w) : "memory"); }
__device__ __forceinline__ void pp_arrive(bool w) { asm volatile("{\n.reg .pred p;\nsetp.ne.u32 p, %0, 0;\n@p bar.arrive 1, 256;\n@!p bar.arrive 2, 256;\n}" :: "r"((uint32_t)w) : "memory"); }
__device__ __forceinline__ bool wg_any(bool w, bool v) {
  uint32_t r;
  asm volatile("{\n.reg .pred p, q;\nsetp.ne.u32 p, %1, 0;\nbar.red.or.pred q, %2, 128, p;\nselp.u32 %0, 1, 0, q;\n}" : "=r"(r) : "r"((uint32_t)v), "r"(w ? 4 : 3) : "memory");
  return __any_sync(0xffffffffu, r);
}
__device__ __forceinline__ int fresh_warp() { uint32_t t; asm volatile("mov.u32 %0, %%tid.x;" : "=r"(t)); return __shfl_sync(0xffffffffu, (int)(t >> 5) - 4, 0); }
__device__ __forceinline__ void cluster_sync_all() { asm volatile("barrier.cluster.arrive.release.aligned;\nbarrier.cluster.wait.acquire.aligned;" ::: "memory"); }
__device__ __forceinline__ void cluster_sync_relaxed() { asm volatile("barrier.cluster.arrive.relaxed.aligned;\nbarrier.cluster.wait.aligned;" ::: "memory"); }
__device__ __forceinline__ uint32_t cluster_rank() { uint32_t r; asm volatile("mov.u32 %0, %%cluster_ctarank;" : "=r"(r)); return r; }
__device__ __forceinline__ unsigned ld_acquire(const unsigned* p) { unsigned v; asm volatile("ld.acquire.gpu.global.u32 %0, [%1];" : "=r"(v) : "l"(p) : "memory"); return v; }
__device__ __forceinline__ void red_release(unsigned* p, unsigned v) { asm volatile("red.release.gpu.global.add.u32 [%0], %1;" :: "l"(p), "r"(v) : "memory"); }
__device__ __forceinline__ void flag_wait(const unsigned* p, unsigned target) {
  uint32_t n = 0;
  while (ld_acquire(p) < target) { trap_if(++n > SPIN_LIMIT); __nanosleep(20); }
}
__device__ __forceinline__ void st_relaxed_v4(float4* p, float a, float b, float c) {
  asm volatile("st.relaxed.gpu.global.v4.f32 [%0], {%1, %2, %3, %3};" :: "l"(p), "f"(a), "f"(b), "f"(c) : "memory");
}
__device__ __forceinline__ float4 ld_relaxed_v4(const float4* p) {
  float4 v; asm volatile("ld.relaxed.gpu.global.v4.f32 {%0, %1, %2, %3}, [%4];" : "=f"(v.x), "=f"(v.y), "=f"(v.z), "=f"(v.w) : "l"(p) : "memory"); return v;
}
__device__ __forceinline__ uint32_t pack_bf16(float lo, float hi) { uint32_t r; asm("cvt.rn.bf16x2.f32 %0, %1, %2;" : "=r"(r) : "f"(hi), "f"(lo)); return r; }
__device__ __forceinline__ float bf_lo(uint32_t v) { return __uint_as_float(v << 16); }
__device__ __forceinline__ float bf_hi(uint32_t v) { return __uint_as_float(v & 0xffff0000u); }
__device__ __forceinline__ float ex2(float x) { float y; asm("ex2.approx.ftz.f32 %0, %1;" : "=f"(y) : "f"(x)); return y; }
__device__ __forceinline__ float tanh_fast(float x) { float y; asm("tanh.approx.f32 %0, %1;" : "=f"(y) : "f"(x)); return y; }
__device__ __forceinline__ void stmatrix_x4(uint32_t addr, uint32_t a, uint32_t b, uint32_t c, uint32_t d) {
  asm volatile("stmatrix.sync.aligned.m8n8.x4.shared.b16 [%0], {%1, %2, %3, %4};" :: "r"(addr), "r"(a), "r"(b), "r"(c), "r"(d) : "memory");
}
__device__ __forceinline__ void ldmatrix_x4(uint32_t addr, uint32_t& a, uint32_t& b, uint32_t& c, uint32_t& d) {
  asm volatile("ldmatrix.sync.aligned.m8n8.x4.shared.b16 {%0, %1, %2, %3}, [%4];" : "=r"(a), "=r"(b), "=r"(c), "=r"(d) : "r"(addr) : "memory");
}
__device__ __forceinline__ uint32_t lane_id() { uint32_t l; asm volatile("mov.u32 %0, %%laneid;" : "=r"(l)); return l; }
__device__ __forceinline__ bool elect_one() {
  uint32_t r;
  asm volatile("{\n.reg .pred P;\nelect.sync _|P, 0xffffffff;\nselp.u32 %0, 1, 0, P;\n}" : "=r"(r));
  return r;
}
__device__ __forceinline__ uint64_t gtime() { uint64_t t; asm volatile("mov.u64 %0, %%globaltimer;" : "=l"(t)); return t; }

__device__ __forceinline__ void wgmma_m64n128k16_ss_tb0(float (&d)[64], uint64_t da, uint64_t db, int scale_d) {
  asm volatile("{\n.reg .pred p;\nsetp.ne.b32 p, %66, 0;\n"
    "wgmma.mma_async.sync.aligned.m64n128k16.f32.bf16.bf16 "
    "{%0, %1, %2, %3, %4, %5, %6, %7, %8, %9, %10, %11, %12, %13, %14, %15, %16, %17, %18, %19, %20, %21, %22, %23, %24, %25, %26, %27, %28, %29, %30, %31, %32, %33, %34, %35, %36, %37, %38, %39, %40, %41, %42, %43, %44, %45, %46, %47, %48, %49, %50, %51, %52, %53, %54, %55, %56, %57, %58, %59, %60, %61, %62, %63}, "
    "%64, %65, p, 1, 1, 0, 0;\n}\n"
    : "+f"(d[0]), "+f"(d[1]), "+f"(d[2]), "+f"(d[3]), "+f"(d[4]), "+f"(d[5]), "+f"(d[6]), "+f"(d[7]), "+f"(d[8]), "+f"(d[9]), "+f"(d[10]), "+f"(d[11]), "+f"(d[12]), "+f"(d[13]), "+f"(d[14]), "+f"(d[15]), "+f"(d[16]), "+f"(d[17]), "+f"(d[18]), "+f"(d[19]), "+f"(d[20]), "+f"(d[21]), "+f"(d[22]), "+f"(d[23]), "+f"(d[24]), "+f"(d[25]), "+f"(d[26]), "+f"(d[27]), "+f"(d[28]), "+f"(d[29]), "+f"(d[30]), "+f"(d[31]), "+f"(d[32]), "+f"(d[33]), "+f"(d[34]), "+f"(d[35]), "+f"(d[36]), "+f"(d[37]), "+f"(d[38]), "+f"(d[39]), "+f"(d[40]), "+f"(d[41]), "+f"(d[42]), "+f"(d[43]), "+f"(d[44]), "+f"(d[45]), "+f"(d[46]), "+f"(d[47]), "+f"(d[48]), "+f"(d[49]), "+f"(d[50]), "+f"(d[51]), "+f"(d[52]), "+f"(d[53]), "+f"(d[54]), "+f"(d[55]), "+f"(d[56]), "+f"(d[57]), "+f"(d[58]), "+f"(d[59]), "+f"(d[60]), "+f"(d[61]), "+f"(d[62]), "+f"(d[63])
    : "l"(da), "l"(db), "r"(scale_d));
}
__device__ __forceinline__ void wgmma_m64n256k16_ss_tb1(float (&d)[128], uint64_t da, uint64_t db, int scale_d) {
  asm volatile("{\n.reg .pred p;\nsetp.ne.b32 p, %130, 0;\n"
    "wgmma.mma_async.sync.aligned.m64n256k16.f32.bf16.bf16 "
    "{%0, %1, %2, %3, %4, %5, %6, %7, %8, %9, %10, %11, %12, %13, %14, %15, %16, %17, %18, %19, %20, %21, %22, %23, %24, %25, %26, %27, %28, %29, %30, %31, %32, %33, %34, %35, %36, %37, %38, %39, %40, %41, %42, %43, %44, %45, %46, %47, %48, %49, %50, %51, %52, %53, %54, %55, %56, %57, %58, %59, %60, %61, %62, %63, %64, %65, %66, %67, %68, %69, %70, %71, %72, %73, %74, %75, %76, %77, %78, %79, %80, %81, %82, %83, %84, %85, %86, %87, %88, %89, %90, %91, %92, %93, %94, %95, %96, %97, %98, %99, %100, %101, %102, %103, %104, %105, %106, %107, %108, %109, %110, %111, %112, %113, %114, %115, %116, %117, %118, %119, %120, %121, %122, %123, %124, %125, %126, %127}, "
    "%128, %129, p, 1, 1, 0, 1;\n}\n"
    : "+f"(d[0]), "+f"(d[1]), "+f"(d[2]), "+f"(d[3]), "+f"(d[4]), "+f"(d[5]), "+f"(d[6]), "+f"(d[7]), "+f"(d[8]), "+f"(d[9]), "+f"(d[10]), "+f"(d[11]), "+f"(d[12]), "+f"(d[13]), "+f"(d[14]), "+f"(d[15]), "+f"(d[16]), "+f"(d[17]), "+f"(d[18]), "+f"(d[19]), "+f"(d[20]), "+f"(d[21]), "+f"(d[22]), "+f"(d[23]), "+f"(d[24]), "+f"(d[25]), "+f"(d[26]), "+f"(d[27]), "+f"(d[28]), "+f"(d[29]), "+f"(d[30]), "+f"(d[31]), "+f"(d[32]), "+f"(d[33]), "+f"(d[34]), "+f"(d[35]), "+f"(d[36]), "+f"(d[37]), "+f"(d[38]), "+f"(d[39]), "+f"(d[40]), "+f"(d[41]), "+f"(d[42]), "+f"(d[43]), "+f"(d[44]), "+f"(d[45]), "+f"(d[46]), "+f"(d[47]), "+f"(d[48]), "+f"(d[49]), "+f"(d[50]), "+f"(d[51]), "+f"(d[52]), "+f"(d[53]), "+f"(d[54]), "+f"(d[55]), "+f"(d[56]), "+f"(d[57]), "+f"(d[58]), "+f"(d[59]), "+f"(d[60]), "+f"(d[61]), "+f"(d[62]), "+f"(d[63]), "+f"(d[64]), "+f"(d[65]), "+f"(d[66]), "+f"(d[67]), "+f"(d[68]), "+f"(d[69]), "+f"(d[70]), "+f"(d[71]), "+f"(d[72]), "+f"(d[73]), "+f"(d[74]), "+f"(d[75]), "+f"(d[76]), "+f"(d[77]), "+f"(d[78]), "+f"(d[79]), "+f"(d[80]), "+f"(d[81]), "+f"(d[82]), "+f"(d[83]), "+f"(d[84]), "+f"(d[85]), "+f"(d[86]), "+f"(d[87]), "+f"(d[88]), "+f"(d[89]), "+f"(d[90]), "+f"(d[91]), "+f"(d[92]), "+f"(d[93]), "+f"(d[94]), "+f"(d[95]), "+f"(d[96]), "+f"(d[97]), "+f"(d[98]), "+f"(d[99]), "+f"(d[100]), "+f"(d[101]), "+f"(d[102]), "+f"(d[103]), "+f"(d[104]), "+f"(d[105]), "+f"(d[106]), "+f"(d[107]), "+f"(d[108]), "+f"(d[109]), "+f"(d[110]), "+f"(d[111]), "+f"(d[112]), "+f"(d[113]), "+f"(d[114]), "+f"(d[115]), "+f"(d[116]), "+f"(d[117]), "+f"(d[118]), "+f"(d[119]), "+f"(d[120]), "+f"(d[121]), "+f"(d[122]), "+f"(d[123]), "+f"(d[124]), "+f"(d[125]), "+f"(d[126]), "+f"(d[127])
    : "l"(da), "l"(db), "r"(scale_d));
}
__device__ __forceinline__ void wgmma_m64n128k16_rs_tb1(float (&d)[64], uint32_t a0, uint32_t a1, uint32_t a2, uint32_t a3, uint64_t db, int scale_d) {
  asm volatile("{\n.reg .pred p;\nsetp.ne.b32 p, %69, 0;\n"
    "wgmma.mma_async.sync.aligned.m64n128k16.f32.bf16.bf16 "
    "{%0, %1, %2, %3, %4, %5, %6, %7, %8, %9, %10, %11, %12, %13, %14, %15, %16, %17, %18, %19, %20, %21, %22, %23, %24, %25, %26, %27, %28, %29, %30, %31, %32, %33, %34, %35, %36, %37, %38, %39, %40, %41, %42, %43, %44, %45, %46, %47, %48, %49, %50, %51, %52, %53, %54, %55, %56, %57, %58, %59, %60, %61, %62, %63}, "
    "{%64, %65, %66, %67}, %68, p, 1, 1, 1;\n}\n"
    : "+f"(d[0]), "+f"(d[1]), "+f"(d[2]), "+f"(d[3]), "+f"(d[4]), "+f"(d[5]), "+f"(d[6]), "+f"(d[7]), "+f"(d[8]), "+f"(d[9]), "+f"(d[10]), "+f"(d[11]), "+f"(d[12]), "+f"(d[13]), "+f"(d[14]), "+f"(d[15]), "+f"(d[16]), "+f"(d[17]), "+f"(d[18]), "+f"(d[19]), "+f"(d[20]), "+f"(d[21]), "+f"(d[22]), "+f"(d[23]), "+f"(d[24]), "+f"(d[25]), "+f"(d[26]), "+f"(d[27]), "+f"(d[28]), "+f"(d[29]), "+f"(d[30]), "+f"(d[31]), "+f"(d[32]), "+f"(d[33]), "+f"(d[34]), "+f"(d[35]), "+f"(d[36]), "+f"(d[37]), "+f"(d[38]), "+f"(d[39]), "+f"(d[40]), "+f"(d[41]), "+f"(d[42]), "+f"(d[43]), "+f"(d[44]), "+f"(d[45]), "+f"(d[46]), "+f"(d[47]), "+f"(d[48]), "+f"(d[49]), "+f"(d[50]), "+f"(d[51]), "+f"(d[52]), "+f"(d[53]), "+f"(d[54]), "+f"(d[55]), "+f"(d[56]), "+f"(d[57]), "+f"(d[58]), "+f"(d[59]), "+f"(d[60]), "+f"(d[61]), "+f"(d[62]), "+f"(d[63])
    : "r"(a0), "r"(a1), "r"(a2), "r"(a3), "l"(db), "r"(scale_d));
}
__device__ __forceinline__ void wgmma_m64n128k16_ss_tb1(float (&d)[64], uint64_t da, uint64_t db, int scale_d) {
  asm volatile("{\n.reg .pred p;\nsetp.ne.b32 p, %66, 0;\n"
    "wgmma.mma_async.sync.aligned.m64n128k16.f32.bf16.bf16 "
    "{%0, %1, %2, %3, %4, %5, %6, %7, %8, %9, %10, %11, %12, %13, %14, %15, %16, %17, %18, %19, %20, %21, %22, %23, %24, %25, %26, %27, %28, %29, %30, %31, %32, %33, %34, %35, %36, %37, %38, %39, %40, %41, %42, %43, %44, %45, %46, %47, %48, %49, %50, %51, %52, %53, %54, %55, %56, %57, %58, %59, %60, %61, %62, %63}, "
    "%64, %65, p, 1, 1, 0, 1;\n}\n"
    : "+f"(d[0]), "+f"(d[1]), "+f"(d[2]), "+f"(d[3]), "+f"(d[4]), "+f"(d[5]), "+f"(d[6]), "+f"(d[7]), "+f"(d[8]), "+f"(d[9]), "+f"(d[10]), "+f"(d[11]), "+f"(d[12]), "+f"(d[13]), "+f"(d[14]), "+f"(d[15]), "+f"(d[16]), "+f"(d[17]), "+f"(d[18]), "+f"(d[19]), "+f"(d[20]), "+f"(d[21]), "+f"(d[22]), "+f"(d[23]), "+f"(d[24]), "+f"(d[25]), "+f"(d[26]), "+f"(d[27]), "+f"(d[28]), "+f"(d[29]), "+f"(d[30]), "+f"(d[31]), "+f"(d[32]), "+f"(d[33]), "+f"(d[34]), "+f"(d[35]), "+f"(d[36]), "+f"(d[37]), "+f"(d[38]), "+f"(d[39]), "+f"(d[40]), "+f"(d[41]), "+f"(d[42]), "+f"(d[43]), "+f"(d[44]), "+f"(d[45]), "+f"(d[46]), "+f"(d[47]), "+f"(d[48]), "+f"(d[49]), "+f"(d[50]), "+f"(d[51]), "+f"(d[52]), "+f"(d[53]), "+f"(d[54]), "+f"(d[55]), "+f"(d[56]), "+f"(d[57]), "+f"(d[58]), "+f"(d[59]), "+f"(d[60]), "+f"(d[61]), "+f"(d[62]), "+f"(d[63])
    : "l"(da), "l"(db), "r"(scale_d));
}

enum { TM_XN, TM_WSP, TM_U, TM_O, TM_Q, TM_X, TM_SA, TM_G, TM_K, TM_V, TM_O64,
       TM_WIN, TM_WQ, TM_Z2, TM_WOUT, TM_WO, TS_Q, TS_O, TS_Z2, TS_U, TS_SA, TS_G, TS_OUT, TM_COUNT };
enum { T_Z2 = 0, T_Q = 1, T_U = 2, T_ATT = 3, T_SA = 4, T_FIN = 5, T_END = 7 };
constexpr int NCLUSTER = 66, MAXI = 14;
struct alignas(64) Params {
  CUtensorMap tm[TM_COUNT];
  const bf16* x;
  const bf16* b_sp;
  uint16_t items[NCLUSTER][MAXI];
};

constexpr uint32_t G_STAGE = 49152, G_A = 16384, KV_SLOT = 32768;
constexpr uint32_t OFF_Q1 = 163840, OFF_Q0 = 196608, OFF_BAR = 229376, SMEM_BYTES = OFF_BAR + 256;
constexpr uint32_t B_GF = 0, B_GE = 32, B_KF = 64, B_KE = 104, B_QF = 144, B_QE = 160, B_XF = 176, B_XR = 184, B_STG = 192, B_FREE = 200, B_GO = 208, B_TAG = 216, B_RDY = 220;
#define SA_HEADS 20
#define SW_NS 100
#define ST_ROWS 16
#define ST_FLY 2
#define EF 0
#define KV_PF 0
#define KV_ALL 0
#define VMODE 0
#define OUT_PF 8
constexpr float SM_C = 0.08838834764831845f * 1.4426950408889634f;
constexpr float GELU_A = 0.7978845608028654f, GELU_B = 0.7978845608028654f * 0.044715f;
constexpr float SM_THR = 1024.f;

#define TRACE(w, i)
#define FT(c, tag)

extern __shared__ __align__(1024) uint8_t smem_raw[];
__device__ __forceinline__ uint32_t smem_base() { return smem_u32(smem_raw); }
__device__ __forceinline__ uint32_t smem_desc() { return (smem_base() & 0x3FFFF) >> 4; }

struct Ring { uint32_t s, ph; };
template <int N> __device__ __forceinline__ void ring_adv(Ring& r) { if (++r.s == N) { r.s = 0; r.ph ^= 1; } }

__device__ __forceinline__ int get_item(const Params& p, int i) {
  uint32_t b; asm volatile("mov.u32 %0, %%ctaid.x;" : "=r"(b));
  return p.items[b >> 1][i];
}
struct Cons {
  uint32_t sb;
  int warp;
  Ring g;
  uint32_t fph;
};

__device__ __forceinline__ void stage_acquire(const Cons& c) { mbar_spin(c.sb + OFF_BAR + B_FREE, c.fph); }
__device__ __forceinline__ void stage_commit(Cons& c) {
  __syncwarp();
  if (lane_id() == 0) mbar_arrive(c.sb + OFF_BAR + B_STG);
  c.fph ^= 1;
}

__device__ __forceinline__ void release_slot(const Cons& c, uint32_t bar, bool mc) {
  if (lane_id() == 0 && (c.warp & 3) < 2) mbar_arrive_cta(bar, mc ? (uint32_t)(c.warp & 1) : (blockIdx.x & 1));
}
constexpr uint64_t DESC_HI = (uint64_t)0x40000040u << 32;

template <bool FIRST> __device__ __forceinline__ void gemm_step(float (&acc)[128], Cons& c) {
  mbar_spin(c.sb + OFF_BAR + B_GF + 8 * c.g.s, c.g.ph);
  const uint32_t st = ((c.sb & 0x3FFFF) >> 4) + c.g.s * (G_STAGE >> 4);
  const uint32_t da = st + (c.warp >> 2) * 512 + (1u << 16), db = st + (G_A >> 4) + ((8192u >> 4) << 16);
  wgmma_fence();
#pragma unroll
  for (int kk = 0; kk < 4; kk++) wgmma_m64n256k16_ss_tb1(acc, DESC_HI | (da + kk * 2), DESC_HI | (db + kk * 128), !(FIRST && kk == 0));
  wgmma_commit();
}

template <int N> __device__ __forceinline__ void stage_chunks(uint32_t buf, uint32_t stride, const uint32_t* pk) {
  const uint32_t ln = lane_id();
  const uint32_t a = buf + ((ln & 15) << 7);
  const uint32_t x = ln & 7, hi = ln >> 4;
#pragma unroll
  for (int i = 0; i < 4 * N; i++) stmatrix_x4(a + (i >> 2) * stride + (((2 * (i & 3) + hi) ^ x) << 4), pk[4 * i], pk[4 * i + 1], pk[4 * i + 2], pk[4 * i + 3]);
}

__device__ __forceinline__ float act2_fn(float x, float a, float b) {
  return fmaf(x, tanh_fast(x * fmaf(x * x, b, a)), x);
}
__device__ __forceinline__ float quad_sum(float v) { v += __shfl_xor_sync(0xffffffffu, v, 1); v += __shfl_xor_sync(0xffffffffu, v, 2); return v; }
__device__ __forceinline__ float quad_max(float v) { v = fmaxf(v, __shfl_xor_sync(0xffffffffu, v, 1)); v = fmaxf(v, __shfl_xor_sync(0xffffffffu, v, 2)); return v; }

__device__ __forceinline__ float load_tag(const Cons& c) { float t; asm volatile("ld.volatile.shared.f32 %0, [%1];" : "=f"(t) : "r"(c.sb + OFF_BAR + B_TAG)); return t; }

struct Shadow {
  int act;
  int store;
};
__device__ __forceinline__ void rotate16(uint32_t (&h)[64]) {
#pragma unroll
  for (int i = 0; i < 16; i++)
    asm volatile("{\n.reg .b32 t;\nmov.b32 t, %0;\nmov.b32 %0, %1;\nmov.b32 %1, %2;\nmov.b32 %2, %3;\nmov.b32 %3, t;\n}" : "+r"(h[i]), "+r"(h[i + 16]), "+r"(h[i + 32]), "+r"(h[i + 48]));
}

template <int O>
__device__ __forceinline__ void act_block(uint32_t (&held)[64], float ca, float cb, bool first, float& u0, float& u1, float& s0, float& s1, float& q0, float& q1) {
#pragma unroll
  for (int i = O; i < O + 4; i += 2) {
    const float a0 = act2_fn(bf_lo(held[i]), ca, cb), a1 = act2_fn(bf_hi(held[i]), ca, cb);
    const float b0 = act2_fn(bf_lo(held[i + 1]), ca, cb), b1 = act2_fn(bf_hi(held[i + 1]), ca, cb);
    if (i == 0 && first) { u0 = a0; u1 = b0; }
    float d;
    d = a0 - u0; s0 += d; q0 = fmaf(d, d, q0); d = a1 - u0; s0 += d; q0 = fmaf(d, d, q0);
    d = b0 - u1; s1 += d; q1 = fmaf(d, d, q1); d = b1 - u1; s1 += d; q1 = fmaf(d, d, q1);
    held[i] = pack_bf16(a0, a1); held[i + 1] = pack_bf16(b0, b1);
  }
}

__device__ __forceinline__ void gemm_seg(float (&acc)[128], uint32_t (&held)[64], Cons& c, const Params& p, Shadow& sh, int nsteps) {
  const bool elected = lane_id() == 0 && (c.warp & 3) < 2;
  uint32_t rel;
  asm("mapa.shared::cluster.u32 %0, %1, %2;" : "=r"(rel) : "r"(c.sb + OFF_BAR + B_GE), "r"((uint32_t)(c.warp & 1)));
  gemm_step<true>(acc, c);
  ring_adv<4>(c.g);
  int k = 1;
#define G_STEP()                                                                                                   \
  { gemm_step<false>(acc, c);                                                                                    \
    FT(c, 70);                                                                                                          \
    wgmma_wait<1>();                                                                                                    \
    if (elected) asm volatile("mbarrier.arrive.shared::cluster.b64 _, [%0];" :: "r"(rel + 8 * ((c.g.s - 1) & 3)) : "memory"); \
    ring_adv<4>(c.g);                                                                                                             \
    k++; }
  if (sh.act != 0) {
    float u0 = 0.f, u1 = 0.f, s0 = 0.f, s1 = 0.f, q0 = 0.f, q1 = 0.f;
    const float ca = sh.act == 3 ? 0.5f : GELU_A, cb = sh.act == 3 ? 0.f : GELU_B;
#pragma unroll 1
    while (true) {
      act_block<0>(held, ca, cb, k == 1, u0, u1, s0, s1, q0, q1);
      G_STEP()
      act_block<4>(held, ca, cb, false, u0, u1, s0, s1, q0, q1);
      G_STEP()
      act_block<8>(held, ca, cb, false, u0, u1, s0, s1, q0, q1);
      G_STEP()
      act_block<12>(held, ca, cb, false, u0, u1, s0, s1, q0, q1);
      rotate16(held);
      if (k == 16) break;
      G_STEP()
    }
    if (sh.act == 2) {
      const int zi = get_item(p, 0);
      const int ln = lane_id(), row0 = (((zi >> 5) & 31) * 2 + (blockIdx.x & 1)) * 128 + c.warp * 16 + (ln >> 2), ql = ln & 3;
      const float m0 = fmaf(s0, 1.f / 64, u0), m1 = fmaf(s1, 1.f / 64, u1);
      q0 -= s0 * s0 * (1.f / 64); q1 -= s1 * s1 * (1.f / 64);
      const float mu0 = quad_sum(m0) * 0.25f, mu1 = quad_sum(m1) * 0.25f;
      q0 = quad_sum(fmaf(64.f * (m0 - mu0), m0 - mu0, q0)); q1 = quad_sum(fmaf(64.f * (m1 - mu1), m1 - mu1, q1));
      if (ql < 2) st_relaxed_v4(&g_stats[(row0 + 8 * ql) * 8 + (zi & 31)], ql ? mu1 : mu0, ql ? q1 : q0, load_tag(c));
    }
  }
  if (sh.store != 0) {
    float a0 = 0.f, a1 = 0.f, r0 = 1.f, r1 = 1.f;
    if (sh.store == 2) {
      const int zi = get_item(p, 0);
      const int ln = lane_id(), row0 = (((zi >> 5) & 31) * 2 + (blockIdx.x & 1)) * 128 + c.warp * 16 + (ln >> 2), ql = ln & 3;
      float4 t[4];
#pragma unroll
      for (int i = 0; i < 4; i++) t[i] = ld_relaxed_v4(&g_stats[(row0 + 8 * (i >> 1)) * 8 + min(ql + 4 * (i & 1), 6)]);
      G_STEP()
      const float tag = load_tag(c);
      while (true) {
        bool ok = true;
#pragma unroll
        for (int i = 0; i < 4; i++) ok = ok && __float_as_uint(t[i].z) == __float_as_uint(tag);
        if (__all_sync(0xffffffffu, ok)) break;
        __nanosleep(100);
#pragma unroll
        for (int i = 0; i < 4; i++) t[i] = ld_relaxed_v4(&g_stats[(row0 + 8 * (i >> 1)) * 8 + min(ql + 4 * (i & 1), 6)]);
      }
      const float wl = ql == 3 ? 0.f : 1.f;
      const float u0 = quad_sum(fmaf(wl, t[1].x, t[0].x)) * (1.f / 7), u1 = quad_sum(fmaf(wl, t[3].x, t[2].x)) * (1.f / 7);
      float d;
      d = t[0].x - u0; float v0 = fmaf(256.f * d, d, t[0].y);
      d = t[1].x - u0; v0 = fmaf(wl, fmaf(256.f * d, d, t[1].y), v0);
      d = t[2].x - u1; float v1 = fmaf(256.f * d, d, t[2].y);
      d = t[3].x - u1; v1 = fmaf(wl, fmaf(256.f * d, d, t[3].y), v1);
      r0 = rsqrtf(fmaxf(quad_sum(v0), 0.f) * (1.f / FH) + 4e-5f); r1 = rsqrtf(fmaxf(quad_sum(v1), 0.f) * (1.f / FH) + 4e-5f);
      a0 = -u0 * r0; a1 = -u1 * r1;
    }
#pragma unroll 1
    for (int x = 0; x < 6; x++) {
      G_STEP()
      if (x == 2 || x == 3) continue;
      if (sh.store == 2) {
#pragma unroll
        for (int i = 0; i < 8; i++) {
          held[2 * i] = pack_bf16(fmaf(bf_lo(held[2 * i]), r0, a0), fmaf(bf_hi(held[2 * i]), r0, a0));
          held[2 * i + 1] = pack_bf16(fmaf(bf_lo(held[2 * i + 1]), r1, a1), fmaf(bf_hi(held[2 * i + 1]), r1, a1));
        }
      }
      const bool second = x & 1;
      if (!second) stage_acquire(c);
      stage_chunks<1>(c.sb + OFF_Q0 + c.warp * 2048 + (second ? 16384 : 0), 0, held);
      if (second) stage_commit(c);
      rotate16(held);
    }
  }
#pragma unroll 1
  while (k < nsteps) G_STEP()
  wgmma_wait<0>();
  fence_regs(acc);
  if (elected) asm volatile("mbarrier.arrive.shared::cluster.b64 _, [%0];" :: "r"(rel + 8 * ((c.g.s - 1) & 3)) : "memory");
  sh.store = sh.act == 2 ? 2 : 0;
  sh.act = 0;
}

__device__ __forceinline__ void softmax_exp(const float (&S)[64], uint32_t (&P)[32], float m0, float m1, float& s0, float& s1) {
  float a0 = 0.f, a1 = 0.f, b0 = 0.f, b1 = 0.f;
#pragma unroll
  for (int j = 0; j < 16; j++) {
    const float p0 = ex2(fmaf(S[4 * j], SM_C, -m0)), p1 = ex2(fmaf(S[4 * j + 1], SM_C, -m0));
    const float p2 = ex2(fmaf(S[4 * j + 2], SM_C, -m1)), p3 = ex2(fmaf(S[4 * j + 3], SM_C, -m1));
    a0 += p0; b0 += p1; a1 += p2; b1 += p3;
    P[2 * j] = pack_bf16(p0, p1); P[2 * j + 1] = pack_bf16(p2, p3);
  }
  s0 = a0 + b0; s1 = a1 + b1;
}
__device__ __forceinline__ void row_max(const float (&S)[64], float& x0, float& x1) {
  float a0 = fmaxf(S[0], S[1]), a1 = fmaxf(S[2], S[3]);
#pragma unroll
  for (int j = 1; j < 16; j++) { a0 = fmaxf(a0, fmaxf(S[4 * j], S[4 * j + 1])); a1 = fmaxf(a1, fmaxf(S[4 * j + 2], S[4 * j + 3])); }
  x0 = fmaxf(quad_max(a0) * SM_C, -1e38f); x1 = fmaxf(quad_max(a1) * SM_C, -1e38f);
}

__device__ __forceinline__ void issue_qk(float (&S)[64], uint32_t da, uint32_t db) {
#pragma unroll
  for (int kk = 0; kk < 8; kk++) {
    const uint32_t o = (kk >> 2) * 1024 + (kk & 3) * 2;
    wgmma_m64n128k16_ss_tb0(S, DESC_HI | (da + o), DESC_HI | (db + o), kk > 0);
  }
}
template <int K0, int K1> __device__ __forceinline__ void issue_pv(float (&O)[64], const uint32_t (&P)[32], uint32_t db, int acc) {
#pragma unroll
  for (int kk = K0; kk < K1; kk++) wgmma_m64n128k16_rs_tb1(O, P[4 * kk], P[4 * kk + 1], P[4 * kk + 2], P[4 * kk + 3], DESC_HI | (db + kk * 128), (acc || kk > 0));
}

#define FA(k)
__device__ __forceinline__ void att_epilogue(Cons& c, float (&O)[64], uint32_t (&pk)[32], float l0, float l1, uint32_t qbuf) {
  const float i0 = __fdividef(1.f, quad_sum(l0)), i1 = __fdividef(1.f, quad_sum(l1));
  const uint32_t base = c.sb + (qbuf ? OFF_Q1 : OFF_Q0) + c.warp * 2048;
#pragma unroll
  for (int j = 0; j < 16; j++) {
    pk[2 * j] = pack_bf16(O[4 * j] * i0, O[4 * j + 1] * i0);
    pk[2 * j + 1] = pack_bf16(O[4 * j + 2] * i1, O[4 * j + 3] * i1);
  }
  stage_chunks<2>(base, 16384, pk);
  stage_commit(c);
}

#define ATT_ISSUE(PIN, ACC)                                                        \
  if (g < 20) FT(c, 15);                                                           \
  wgmma_fence();                                                                   \
  issue_qk(S, qd, kd); wgmma_commit();                                             \
  if (VMODE == 0) { if (g > 1) release_slot(c, vrel, true); mbar_spin(vbar, vph); wgmma_fence(); } \
  issue_pv<0, 8>(O, PIN, vd, ACC); wgmma_commit();                                 \
  if (VMODE != 0) { if (g > 1) release_slot(c, vrel, true); }                      \
  krel = kbar + (B_KE - B_KF); vrel = vbar + (B_KE - B_KF);                        \
  g++;                                                                             \
  if (g < total) { kd = kd0 + kv.s * (KV_SLOT >> 4); kbar = bars + B_KF + 8 * kv.s; kph = kv.ph; ring_adv<5>(kv); } \
  vd = vd0 + kv.s * (KV_SLOT >> 4); vbar = bars + B_KF + 8 * kv.s; vph = kv.ph; ring_adv<5>(kv); \
  wgmma_wait<1>();                                                                 \
  fence_regs(S);                                                                   \
  kready = mbar_test(kbar, kph);                                                   \
  if (VMODE == 1) kready = kready && mbar_test(vbar, vph);                         \
  release_slot(c, krel, true);

#define ATT_SOFTMAX(POUT, FIRST)                                                   \
  fresh = FIRST;                                                                   \
  _Pragma("unroll 1")                                                              \
  while (true) {                                                                   \
    if (__builtin_expect(fresh, 0)) {                                              \
      float x0, x1;                                                                \
      row_max(S, x0, x1);                                                          \
      x0 = fmaxf(x0, m0); x1 = fmaxf(x1, m1);                                      \
      f0 = ex2(m0 - x0); f1 = ex2(m1 - x1);                                        \
      m0 = x0; m1 = x1; l0 *= f0; l1 *= f1;                                        \
    }                                                                              \
    softmax_exp(S, POUT, m0, m1, s0, s1);                                          \
    if (VMODE == 2) kready = kready && mbar_test(vbar, vph);                       \
    bad = !(s0 <= SM_THR && s1 <= SM_THR);                                         \
    slow = fresh || __any_sync(0xffffffffu, bad || !kready);                       \
    if (__builtin_expect(!slow, 1)) break;                                         \
    if (fresh || !__any_sync(0xffffffffu, bad)) break;                             \
    fresh = true;                                                                  \
  }                                                                                \
  l0 += s0; l1 += s1;                                                              \
  wgmma_wait<0>(); fence_regs(O);

#define ATT_RESCALE()                                                              \
  { _Pragma("unroll")                                                              \
    for (int i = 0; i < 16; i++) { O[4 * i] *= f0; O[4 * i + 1] *= f0; O[4 * i + 2] *= f1; O[4 * i + 3] *= f1; } }

__device__ __forceinline__ void att_run(Cons& c, int n) {
  const uint32_t bars = c.sb + OFF_BAR;
  float S[64], O[64];
  uint32_t P0[32], P1[32];
#pragma unroll
  for (int i = 0; i < 64; i++) O[i] = 0.f;
#pragma unroll
  for (int i = 0; i < 32; i++) P0[i] = P1[i] = 0u;
  fence_regs(O); fence_regs(P0); fence_regs(P1);
  float m0 = 0.f, m1 = 0.f, l0 = 0.f, l1 = 0.f, f0 = 1.f, f1 = 1.f, s0, s1, pl0 = 0.f, pl1 = 0.f;
  const int total = 16 * n;
  int g = 0;
  Ring kv = {1, 0};
  uint32_t kbar = bars + B_KF, kph = 0, vbar = bars + B_KF, vph = 0, krel, vrel = 0;
  const uint32_t kd0 = (uint32_t)make_desc(c.sb, 16, 1024), vd0 = (uint32_t)make_desc(c.sb, 16384, 1024);
  uint32_t qd = kd0 + ((OFF_Q1 + (c.warp >> 2) * 8192) >> 4), kd = kd0, vd = vd0;
  bool fresh, kready, bad, slow;
  FT(c, 16);
  mbar_spin(bars + B_QF + 8, 0);
  FT(c, 17);
  mbar_spin(bars + B_KF, 0);
#pragma unroll 1
  while (true) {
    ATT_ISSUE(P1, 1)
    const bool first = ((g - 1) & 15) == 0;
    if (first) { pl0 = l0; pl1 = l1; m0 = m1 = -1e38f; l0 = l1 = 0.f; }
    ATT_SOFTMAX(P0, first)
    if (__builtin_expect(slow, 0)) {
      if (first) {
        if (g > 1) { att_epilogue(c, O, P1, pl0, pl1, (g >> 4) & 1); TRACE(c.warp >> 2, c.tr + (g >> 4)); FT(c, 24); }
      } else if (fresh) ATT_RESCALE();
      mbar_spin(kbar, kph);
      if (VMODE != 0) mbar_spin(vbar, vph);
    }
    ATT_ISSUE(P0, !first)
    ATT_SOFTMAX(P1, false)
    if (__builtin_expect(slow || (g & 15) == 0, 0)) {
      if (fresh) ATT_RESCALE();
      if (g == total) break;
      mbar_spin(kbar, kph);
      if (VMODE != 0) mbar_spin(vbar, vph);
      if ((g & 15) == 0) {
        const int t = g >> 4;
        const uint32_t qb = (t & 1) ^ 1;
        mbar_spin(bars + B_QF + 8 * qb, (t >> 1) & 1);
        qd = kd0 + (((qb ? OFF_Q1 : OFF_Q0) + (c.warp >> 2) * 8192) >> 4);
      }
    }
  }
  release_slot(c, vrel, true);
  mbar_spin(vbar, vph);
  wgmma_fence();
  issue_pv<0, 8>(O, P1, vd, 1); wgmma_commit();
  wgmma_wait<0>();
  fence_regs(O);
  release_slot(c, vbar + (B_KE - B_KF), true);
  att_epilogue(c, O, P0, l0, l1, n & 1);
  FT(c, 24);
}

__global__ void __cluster_dims__(2, 1, 1) __launch_bounds__(384, 1) fused_kernel(const __grid_constant__ Params p) {
  const uint32_t sb = smem_base();
  const uint32_t bars = sb + OFF_BAR;
  const int tid = threadIdx.x, lane = tid & 31;
  const int warp_id = __shfl_sync(0xffffffffu, tid >> 5, 0), wg = warp_id >> 2;
  const uint32_t rank = blockIdx.x & 1;
  const uint16_t* items = p.items[blockIdx.x >> 1];
  const int gw = blockIdx.x * 8 + warp_id - 4;
  uint4 xv[2][4];
  if (wg != 0 && gw < SEQ / 2) {
#pragma unroll
    for (int rr = 0; rr < 2; rr++)
#pragma unroll
      for (int i = 0; i < 4; i++) xv[rr][i] = __ldg(reinterpret_cast<const uint4*>(p.x + (size_t)(gw * 2 + rr) * DM) + i * 32 + lane);
  }
  if (warp_id == 1 && lane < TM_COUNT) asm volatile("prefetch.tensormap [%0];" :: "l"(&p.tm[lane]) : "memory");
  if (tid == 0) {
    for (int i = 0; i < 4; i++) { mbar_init(bars + B_GF + 8 * i, 1); mbar_init(bars + B_GE + 8 * i, 4); }
    for (int i = 0; i < 5; i++) { mbar_init(bars + B_KF + 8 * i, 1); mbar_init(bars + B_KE + 8 * i, 4); }
    for (int i = 0; i < 2; i++) { mbar_init(bars + B_QF + 8 * i, 1); mbar_init(bars + B_QE + 8 * i, 1); }
    mbar_init(bars + B_XF, 2); mbar_init(bars + B_XR, 2); mbar_init(bars + B_STG, 8); mbar_init(bars + B_FREE, 1); mbar_init(bars + B_GO, 1);
    asm volatile("fence.mbarrier_init.release.cluster;" ::: "memory");
  }
  asm volatile("barrier.cluster.arrive.relaxed.aligned;" ::: "memory");

  if (wg == 0) {
    asm volatile("setmaxnreg.dec.sync.aligned.u32 40;");
    asm volatile("barrier.cluster.wait.acquire.aligned;" ::: "memory");
    if (warp_id == 0) {
      trap_if(sb & 1023);
      Ring g = {0, 1};
      int it = 0;
      uint32_t xph = 0;
      if (elect_one()) {
#pragma unroll 1
        for (;; it++) {
          const int item = items[it], type = item >> 12, b = item & 31, row = (((item >> 5) & 31) * 2 + rank) * 128;
          if (type >= T_ATT) break;
#pragma unroll 1
          for (int seg = 0; seg < (type == T_U ? 2 : 1); seg++) {
            const CUtensorMap* tA = &p.tm[seg ? TM_WSP : TM_XN];
            const CUtensorMap* tB = &p.tm[seg ? TM_Z2 : (type == T_Q ? TM_WQ : TM_WIN)];
            const int bchunk = b * 4 + (type == T_Z2 ? 28 : 0) + rank * 2;
            const unsigned* fl = seg ? &g_flags[F_Z2 + b * 32] : &g_flags[F_XN + (row >> 2)];
            const unsigned tgt = seg ? 16 : 128;
            int k = 0;
            if (it == 0 && seg == 0) {
              for (; k < 4; k++) {
                mbar_expect_tx(bars + B_GF + 8 * k, G_STAGE);
                tma_load_3d_mc(sb + k * G_STAGE + G_A + rank * 16384, tB, k * 64, bchunk, bars + B_GF + 8 * k);
              }
              g.ph ^= 1;
              asm volatile("st.volatile.shared.v2.u32 [%0], {%1, %2};" :: "r"(bars + B_TAG), "r"(__ldcg(&g_epoch) + 1), "r"(0) : "memory");
            }
            flag_wait(fl, tgt);
            fence_async_global();
            for (int x = 0; x < k; x++) tma_load_2d(sb + x * G_STAGE, tA, x * 64, row, bars + B_GF + 8 * x);
#pragma unroll 1
            for (; k < (seg ? 32 : 16); k++) {
              if (k == 2 && type == T_U && seg == 0) { mbar_wait(bars + B_XF, xph); xph ^= 1; }
              mbar_wait(bars + B_GE + 8 * g.s, g.ph);
              const uint32_t st = sb + g.s * G_STAGE, fb = bars + B_GF + 8 * g.s;
              mbar_expect_tx(fb, G_STAGE);
              tma_load_2d(st, tA, k * 64, row, fb);
              tma_load_3d_mc(st + G_A + rank * 16384, tB, k * 64, bchunk, fb);
              ring_adv<4>(g);
            }
          }
        }
      }
      it = __shfl_sync(0xffffffffu, it, 0); g.ph = __shfl_sync(0xffffffffu, g.ph, 0);
      int n = 0;
      while ((items[it + n] >> 12) == T_ATT) n++;
      Ring kv = {0, 1};
      if (elect_one()) {
        const uint64_t pol = policy_evict_normal(), polq = pol;
        int prow = 0;
#pragma unroll 1
        for (int x = -1; x <= 32 * n; x++) {
          const int gb = x >> 1, t = x < 0 ? 0 : gb >> 4;
          const int hrow = ((items[it + t] >> 5) & 31) * SEQ;
          const bool isv = (x & 1) || x == 32 * n;
          if (x >= 0 && x != 1) {
            if (x == 4) { mbar_wait(bars + B_XF, xph); xph ^= 1; }
            mbar_wait(bars + B_KE + 8 * kv.s, kv.ph);
            mbar_expect_tx(bars + B_KF + 8 * kv.s, KV_SLOT);
            tma_load_2d_mc_hint(sb + kv.s * KV_SLOT + rank * 16384, &p.tm[isv ? TM_V : TM_K], rank * 64, isv ? prow : hrow + (gb & 15) * 128,
                                bars + B_KF + 8 * kv.s, pol);
            ring_adv<5>(kv);
          }
          if (KV_PF > 0 && x >= 0) {
            const int gp = gb + KV_PF, ip = items[it + (gp >> 4)];
            if (gp < 16 * n && (KV_ALL || ((gp ^ ip) & 7) == 0)) tma_prefetch_2d(&p.tm[(x & 1) ? TM_V : TM_K], rank * 64, ((ip >> 5) & 31) * SEQ + (gp & 15) * 128);
          }
          if (x == 32 * n - 8) mbar_arrive(bars + B_GO);
          if (x & 1) prow = hrow + (gb & 15) * 128;
          if (x < 0 || ((x & 31) == 11 && t + 1 < n)) {
            const int tq = x < 0 ? 0 : t + 1;
            const int im = items[it + tq], h = (im >> 5) & 31, m = (im & 31) * 2 + rank;
            const uint32_t qb = (tq & 1) ^ 1;
            flag_wait(&g_flags[F_Q + m * 16 + (h >> 1)], 1);
            fence_async_global();
            if (x < 0) {
              tma_prefetch_2d(&p.tm[TM_K], rank * 64, hrow); tma_prefetch_2d(&p.tm[TM_K], rank * 64, hrow + 128);
              tma_prefetch_2d(&p.tm[TM_V], rank * 64, hrow);
              tma_prefetch_2d(&p.tm[TM_Q], h * 128, m * 128); tma_prefetch_2d(&p.tm[TM_Q], h * 128 + 64, m * 128);
              for (int i = 0; i < 4; i++) mbar_wait(bars + B_GE + 8 * i, g.ph);
            }
            mbar_wait(bars + B_QE + 8 * qb, ((tq >> 1) & 1) ^ qb);
            const uint32_t dst = sb + (qb ? OFF_Q1 : OFF_Q0), fb = bars + B_QF + 8 * qb;
            mbar_expect_tx(fb, 32768);
            tma_load_2d_hint(dst, &p.tm[TM_Q], h * 128, m * 128, fb, polq);
            tma_load_2d_hint(dst + 16384, &p.tm[TM_Q], h * 128 + 64, m * 128, fb, polq);
          }
        }
      }
      __syncwarp();
      it += n;
      uint32_t ready = 0;
      auto wait_head = [&](int h) {
        if ((ready >> h) & 1) return;
        uint32_t cnt = 0;
        while (true) {
          asm volatile("ld.acquire.cta.shared.u32 %0, [%1];" : "=r"(ready) : "r"(bars + B_RDY) : "memory");
          if ((ready >> h) & 1) break;
          trap_if(++cnt > SPIN_LIMIT * 8);
          __nanosleep(20);
        }
        fence_async_global();
      };
      int item = items[it];
      if ((item >> 12) == T_SA) {
        const int m = ((item >> 5) & 31) * 2 + rank, b = item & 31;
        if (lane == 0) flag_wait(&g_flags[F_U + m * 32], 7);
        __syncwarp();
        fence_async_global();
#pragma unroll 1
        for (int i = -OUT_PF; i < 28 + 2 * SA_HEADS; i++) {
          if (i >= 0) {
            const bool so = i >= 28;
            const int k = so ? i - 28 : i;
            if (so) wait_head(k >> 1);
            if (elect_one()) {
              if (i == 0) { Ring h = kv; for (int x = 0; x < 5; x++) { mbar_wait(bars + B_KE + 8 * h.s, h.ph); ring_adv<5>(h); } }
              if (i == 3) { mbar_wait(bars + B_XF, xph); xph ^= 1; }
              mbar_wait(bars + B_GE + 8 * g.s, g.ph);
              const uint32_t st = sb + g.s * G_STAGE, fb = bars + B_GF + 8 * g.s;
              mbar_expect_tx(fb, G_STAGE);
              tma_load_2d(st, &p.tm[so ? TM_O : TM_U], k * 64, m * 128, fb);
              tma_load_3d_mc(st + G_A + rank * 16384, &p.tm[so ? TM_WO : TM_WOUT], k * 64, b * 4 + rank * 2, fb);
            }
            ring_adv<4>(g);
          }
          const int ip = i + OUT_PF;
          if (ip < 28 + 2 * SA_HEADS && elect_one()) {
            const bool so = ip >= 28;
            const int k = so ? ip - 28 : ip;
            if ((ip & 3) == b && (!so || ((ready >> (k >> 1)) & 1))) tma_prefetch_2d(&p.tm[so ? TM_O : TM_U], k * 64, m * 128);
            if ((ip & 7) == (m >> 1)) tma_prefetch_3d(&p.tm[so ? TM_WO : TM_WOUT], k * 64, b * 4 + rank * 2);
          }
          __syncwarp();
        }
        item = items[++it];
      }
      if ((item >> 12) == T_FIN) {
        const int m = (item >> 5) & 31, col = (item & 31) * 256 + rank * 128;
        const bool lent = (items[it - 1] >> 12) == T_SA;
        uint32_t ps = lent ? 0 : kv.s;
#pragma unroll 1
        for (int k = 2 * SA_HEADS; k <= 2 * NH; k++) {
          if (k < 2 * NH) wait_head(k >> 1);
          if (elect_one()) {
            if (k == 2 * SA_HEADS) {
              for (int y = k; y < k + 6; y++) if ((ready >> (y >> 1)) & 1) tma_prefetch_2d(&p.tm[TM_O64], y * 64, m * 128 + rank * 64);
              for (int x = 0; x < 4; x++) { mbar_wait(bars + B_GE + 8 * g.s, g.ph); ring_adv<4>(g); }
            }
            if (lent && k == 2 * SA_HEADS + 3) mbar_wait(bars + B_XF, xph);
            if (k == 2 * NH) { flag_wait(&g_flags[F_S + m * 4 + (item & 31)], 2); fence_async_global(); }
            mbar_wait(bars + B_KE + 8 * kv.s, kv.ph);
            const uint32_t dst = sb + ps * KV_SLOT, fb = bars + B_KF + 8 * kv.s;
            if (++ps == 5) ps = 0;
            mbar_expect_tx(fb, KV_SLOT);
            if (k < 2 * NH) {
              tma_load_2d_mc(dst + rank * 8192, &p.tm[TM_O64], k * 64, m * 128 + rank * 64, fb);
              tma_load_3d(dst + 16384, &p.tm[TM_WO], k * 64, col >> 6, fb);
            } else {
              tma_load_2d(dst, &p.tm[TM_SA], col, m * 128, fb);
              tma_load_2d(dst + 16384, &p.tm[TM_SA], col + 64, m * 128, fb);
            }
            ring_adv<5>(kv);
          }
          __syncwarp();
        }
      }
      unsigned last = 0;
      if (lane == 0 && (item >> 12) == T_FIN) mbar_wait_long(bars + B_XR, 0);
      if (lane == 0) { __threadfence(); last = atomicInc(&g_done, gridDim.x - 1) == gridDim.x - 1; }
      last = __shfl_sync(0xffffffffu, last, 0);
      if (last) {
        for (int i = lane; i < F_TOTAL / 4; i += 32) reinterpret_cast<uint4*>(g_flags)[i] = make_uint4(0, 0, 0, 0);
        if (lane == 0) g_epoch = g_epoch + 1;
      }
    } else if (warp_id == 1) {
      if (elect_one()) {
        uint32_t ph = 0;
        int t = 0;
        const bool z = (items[0] >> 12) == T_Z2;
#pragma unroll 1
        for (int it = 0;; it++) {
          const int ii = (z && it < 2) ? it ^ 1 : it;
          const int item = items[ii], type = item >> 12, a = (item >> 5) & 31, b = item & 31;
          if (type == T_END) break;
          const int nt = items[ii + 1] >> 12;
          int row = (a * 2 + rank) * 128, col = b * 256;
          unsigned* f = &g_flags[F_S + (a * 2 + rank) * 4 + b];
          int tm = TS_G, npair = 2;
          bool quad = false;
          uint32_t src = sb + OFF_Q0;
          if (type == T_Z2) { tm = TS_Z2; f = &g_flags[F_Z2 + b * 32]; }
          else if (type == T_Q) { tm = TS_Q; f = &g_flags[F_Q + (a * 2 + rank) * 16 + b]; if (z || nt >= T_ATT) { npair = 0; quad = true; } }
          else if (type == T_U) { tm = TS_U; f = &g_flags[F_U + (a * 2 + rank) * 32]; npair = 0; quad = true; }
          else if (type == T_ATT) { tm = TS_O; f = &g_flags[F_O + (b * 2 + rank) * 32 + a]; npair = 1; row = (b * 2 + rank) * 128; col = a * 128; if (!(t & 1)) src = sb + OFF_Q1; }
          else if (type == T_SA) quad = true;
          else {
            tm = TS_OUT; npair = 1; row = a * 128; col = b * 256 + rank * 128;
            for (int y = 0; y < 2; y++) {
              if (y) { flag_wait(&g_flags[F_S + a * 4 + b], 1); fence_async_global(); }
              mbar_expect_tx(bars + B_QF + 8 * y, 32768);
              tma_load_2d(sb + (y ? OFF_Q1 : OFF_Q0), &p.tm[y ? TM_G : TM_X], col, row, bars + B_QF + 8 * y);
              tma_load_2d(sb + (y ? OFF_Q1 : OFF_Q0) + 16384, &p.tm[y ? TM_G : TM_X], col + 64, row, bars + B_QF + 8 * y);
            }
            mbar_arrive(bars + B_XR);
          }
#pragma unroll 1
          for (int op = 0; op < npair + quad; op++) {
            const bool q = op == npair;
            if (q && type == T_SA) tm = TS_SA;
            const int c0 = q ? col : col + op * 128;
            mbar_wait_sleep(bars + B_STG, ph, SW_NS);
            ph ^= 1;
            fence_async_smem();
#pragma unroll 1
            for (int bx = q ? 0 : 2; bx < 4; bx++) {
              const uint32_t from = bx < 2 ? sb + (2 + bx) * G_STAGE : src + (bx - 2) * 16384;
              const int cc = c0 + (bx ^ 2) * 64;
#pragma unroll 1
              for (int r = 0; r < 128; r += ST_ROWS) {
                tma_store_2d(&p.tm[tm], from + r * 128, cc, row + r);
                bulk_commit();
                if (type != T_FIN) bulk_wait_read<ST_FLY>();
              }
              if (bx == 1) { bulk_wait_read<0>(); mbar_arrive_cta(bars + B_XF, 0); mbar_arrive_cta(bars + B_XF, 1); }
            }
            bulk_wait_read<0>();
            if (type == T_FIN) break;
            mbar_arrive(bars + B_FREE);
            if (type == T_ATT && nt == T_SA) { mbar_arrive_cta(bars + B_XF, 0); mbar_arrive_cta(bars + B_XF, 1); }
            if (type == T_ATT) mbar_arrive(bars + B_QE + ((t & 1) ? 0 : 8));
            else if (nt == T_ATT) mbar_arrive(bars + B_QE);
            if (op + 1 >= npair) { bulk_wait<0>(); red_release(f, 1); }
          }
          if (type == T_ATT) t++;
        }
      }
      __syncwarp();
    } else if (warp_id == 2) {
      int it = 0;
      while ((items[it] >> 12) <= T_ATT) it++;
      if ((items[it] >> 12) != T_END) {
        const bool sa = (items[it] >> 12) == T_SA;
        const int m0 = ((items[it] >> 5) & 31) * 2 + rank, m1 = (items[it + sa] >> 5) & 31;
        if (lane == 0) {
          mbar_wait_long(bars + B_GO, 0);
          if (!sa) for (int y = (blockIdx.x & 63); y < 16 * (NH - SA_HEADS); y += 64) tma_prefetch_3d(&p.tm[TM_WO], (2 * SA_HEADS + (y >> 3)) * 64, (y & 7) * 2);
        }
        __syncwarp();
        uint32_t cnt = 0;
        while (true) {
          const uint32_t r0 = sa ? __ballot_sync(0xffffffffu, ld_acquire(&g_flags[F_O + m0 * 32 + lane]) != 0) : ~0u;
          const uint32_t r1 = __ballot_sync(0xffffffffu, ld_acquire(&g_flags[F_O + m1 * 32 + lane]) != 0);
          const uint32_t r = (r0 & ((1u << SA_HEADS) - 1)) | (r1 & ~((1u << SA_HEADS) - 1));
          if (lane == 0) asm volatile("st.release.cta.shared.u32 [%0], %1;" :: "r"(bars + B_RDY), "r"(r) : "memory");
          if (r == ~0u) break;
          trap_if(++cnt > SPIN_LIMIT);
          __nanosleep(200);
        }
        if (lane == 0) mbar_arrive(bars + B_XR);
      }
      __syncwarp();
    }
    cluster_sync_relaxed();
  } else {
    Cons c;
    c.sb = sb; c.warp = warp_id - 4; c.g = {0, 0}; c.fph = 1;
    TRACE(c.warp >> 2, 0);
    FT(c, 1);
    if (gw < SEQ / 2) {
#pragma unroll
      for (int rr = 0; rr < 2; rr++) {
        float f[32];
#pragma unroll
        for (int i = 0; i < 4; i++) {
          const uint4 v = rr ? xv[1][i] : xv[0][i];
          f[8 * i + 0] = bf_lo(v.x); f[8 * i + 1] = bf_hi(v.x); f[8 * i + 2] = bf_lo(v.y); f[8 * i + 3] = bf_hi(v.y);
          f[8 * i + 4] = bf_lo(v.z); f[8 * i + 5] = bf_hi(v.z); f[8 * i + 6] = bf_lo(v.w); f[8 * i + 7] = bf_hi(v.w);
        }
        float s = 0.f;
#pragma unroll
        for (int i = 0; i < 32; i++) s += f[i];
#pragma unroll
        for (int o = 16; o; o >>= 1) s += __shfl_xor_sync(0xffffffffu, s, o);
        const float mean = s * (1.f / DM);
        float q = 0.f;
#pragma unroll
        for (int i = 0; i < 32; i++) { f[i] -= mean; q = fmaf(f[i], f[i], q); }
#pragma unroll
        for (int o = 16; o; o >>= 1) q += __shfl_xor_sync(0xffffffffu, q, o);
        const float rs = rsqrtf(q * (1.f / DM) + 1e-5f);
#pragma unroll
        for (int i = 0; i < 4; i++) {
          uint4 o;
          o.x = pack_bf16(f[8 * i] * rs, f[8 * i + 1] * rs); o.y = pack_bf16(f[8 * i + 2] * rs, f[8 * i + 3] * rs);
          o.z = pack_bf16(f[8 * i + 4] * rs, f[8 * i + 5] * rs); o.w = pack_bf16(f[8 * i + 6] * rs, f[8 * i + 7] * rs);
          reinterpret_cast<uint4*>(g_xn + (size_t)(gw * 2 + rr) * DM)[i * 32 + lane] = o;
        }
      }
      __syncwarp();
      if (lane == 0) red_release(&g_flags[F_XN + (gw >> 6) * 32], 2);
    }
    asm volatile("setmaxnreg.inc.sync.aligned.u32 232;");
    asm volatile("barrier.cluster.wait.acquire.aligned;" ::: "memory");
#define stg (c.sb + OFF_Q0 + c.warp * 2048)
    int natt = 0;
    int it = 0;
    uint32_t held[64];
#pragma unroll
    for (int i = 0; i < 64; i++) held[i] = 0u;
    Shadow sh = {0, 0};
#pragma unroll 1
    while (true) {
      const int item = get_item(p, it), type = item >> 12, a = (item >> 5) & 31, b = item & 31;
      if (type == T_END) break;
      c.warp = fresh_warp();
      TRACE(c.warp >> 2, 1 + it);
      FT(c, 2);
      if (type == T_ATT) {
        int n = 1;
        while ((get_item(p, it + n) >> 12) == T_ATT) n++;
        att_run(c, n);
#pragma unroll
        for (int i = 0; i < 64; i++) held[i] = 0u;
        natt = n;
        it += n;
        continue;
      }
      if (type == T_FIN) {
        float acc[64];
        Ring kv = {(uint32_t)(32 * natt) % 5, ((uint32_t)(32 * natt) / 5) & 1};
        uint32_t ps = (get_item(p, it - 1) >> 12) == T_SA ? 0 : kv.s;
        uint32_t prev = 0;
#pragma unroll 1
        for (int k = 2 * SA_HEADS; k < 2 * NH; k++) {
          mbar_spin(bars + B_KF + 8 * kv.s, kv.ph);
          const uint32_t st = ((c.sb & 0x3FFFF) >> 4) + ps * (KV_SLOT >> 4);
          const uint32_t da = st + (c.warp >> 2) * 512 + (1u << 16), db = st + 1024 + ((8192u >> 4) << 16);
          wgmma_fence();
          if (k == 2 * SA_HEADS) wgmma_m64n128k16_ss_tb1(acc, DESC_HI | da, DESC_HI | db, 0);
          else wgmma_m64n128k16_ss_tb1(acc, DESC_HI | da, DESC_HI | db, 1);
#pragma unroll
          for (int kk = 1; kk < 4; kk++) wgmma_m64n128k16_ss_tb1(acc, DESC_HI | (da + kk * 2), DESC_HI | (db + kk * 128), 1);
          wgmma_commit();
          FT(c, 70);
          wgmma_wait<1>();
          if (k > 2 * SA_HEADS) release_slot(c, prev, true);
          prev = bars + B_KE + 8 * kv.s;
          ring_adv<5>(kv);
          if (++ps == 5) ps = 0;
        }
        const uint32_t ln = lane_id();
        uint32_t in[3][32];
#pragma unroll
        for (int t = 0; t < 3; t++) {
          if (t < 2) mbar_spin(bars + B_QF + 8 * t, ((natt + t) >> 1) & 1); else mbar_spin(bars + B_KF + 8 * kv.s, kv.ph);
          const uint32_t xa = sb + (t == 0 ? OFF_Q0 : (t == 1 ? OFF_Q1 : ps * KV_SLOT)) + c.warp * 2048 + ((ln & 15) << 7);
#pragma unroll
          for (int i = 0; i < 8; i++)
            ldmatrix_x4(xa + (i >> 2) * 16384 + (((2 * (i & 3) + (ln >> 4)) ^ (ln & 7)) << 4), in[t][4 * i], in[t][4 * i + 1], in[t][4 * i + 2], in[t][4 * i + 3]);
        }
        wgmma_wait<0>();
        fence_regs(acc);
        TRACE(c.warp >> 2, 32 + it);
        FT(c, 3);
#pragma unroll
        for (int i = 0; i < 32; i++)
          in[0][i] = pack_bf16(fmaf(0.5f * (acc[2 * i] + bf_lo(in[2][i])), bf_lo(in[1][i]), bf_lo(in[0][i])),
                               fmaf(0.5f * (acc[2 * i + 1] + bf_hi(in[2][i])), bf_hi(in[1][i]), bf_hi(in[0][i])));
        __syncwarp();
        stage_chunks<2>(stg, 16384, in[0]);
        stage_commit(c);
        break;
      }
      float acc[128];
      const bool sa = type == T_SA;
      bool more = type >= T_U;
      int nsteps = sa ? 28 : 16;
      const bool direct = sh.act == 2 || (get_item(p, it + 1) >> 12) >= T_ATT;
      uint32_t bias0 = 0, bias1 = 0;
#pragma unroll 1
      while (true) {
        gemm_seg(acc, held, c, p, sh, nsteps);
        if (!more && direct) break;
#pragma unroll
        for (int i = 0; i < 64; i++) held[i] = pack_bf16(acc[2 * i], acc[2 * i + 1]);
        if (!more) break;
        more = false;
        nsteps = sa ? 2 * SA_HEADS : 32;
        sh.act = sa ? 3 : 1;
        if (sa) {
          sh.store = 1;
        } else {
          const int row0 = (a * 2 + rank) * 128 + c.warp * 16 + (lane_id() >> 2);
          asm volatile("ld.global.nc.u16 %0, [%1];" : "=r"(bias0) : "l"(p.b_sp + row0));
          asm volatile("ld.global.nc.u16 %0, [%1];" : "=r"(bias1) : "l"(p.b_sp + row0 + 8));
        }
      }
      TRACE(c.warp >> 2, 32 + it);
      FT(c, 3);
      if (type == T_U) {
        const float add0 = 0.5f * bf_lo(bias0), add1 = 0.5f * bf_lo(bias1);
#pragma unroll
        for (int i = 0; i < 32; i++) {
          acc[4 * i] = fmaf(acc[4 * i], 0.5f, add0) * bf_lo(held[2 * i]); acc[4 * i + 1] = fmaf(acc[4 * i + 1], 0.5f, add0) * bf_hi(held[2 * i]);
          acc[4 * i + 2] = fmaf(acc[4 * i + 2], 0.5f, add1) * bf_lo(held[2 * i + 1]); acc[4 * i + 3] = fmaf(acc[4 * i + 3], 0.5f, add1) * bf_hi(held[2 * i + 1]);
        }
      }
      c.warp = fresh_warp();
      if (direct) {
        stage_acquire(c);
#pragma unroll
        for (int h = 0; h < 2; h++) {
          uint32_t pk[32];
#pragma unroll
          for (int i = 0; i < 32; i++) pk[i] = pack_bf16(acc[64 * h + 2 * i], acc[64 * h + 2 * i + 1]);
          stage_chunks<2>(h ? sb + 2 * G_STAGE + c.warp * 2048 : stg, h ? G_STAGE : 16384, pk);
        }
        stage_commit(c);
      } else if (type == T_Q) {
        sh.store = 1;
      } else {
        sh.act = 2;
      }
      it++;
    }
    FT(c, 63);
    FT(c, 0);
    TRACE(c.warp >> 2, 31);
    __syncwarp();
    cluster_sync_relaxed();
  }
}

typedef CUresult (*PFN_encodeTiled)(CUtensorMap*, CUtensorMapDataType, cuuint32_t, void*, const cuuint64_t*, const cuuint64_t*, const cuuint32_t*, const cuuint32_t*,
                                    CUtensorMapInterleave, CUtensorMapSwizzle, CUtensorMapL2promotion, CUtensorMapFloatOOBfill);
static PFN_encodeTiled s_encode = nullptr;
static void tm_2d(CUtensorMap* tm, const void* ptr, uint64_t rows, uint64_t cols, uint32_t box_rows) {
  cuuint64_t dims[2] = {cols, rows}; cuuint64_t strides[1] = {cols * 2}; cuuint32_t box[2] = {64, box_rows}; cuuint32_t es[2] = {1, 1};
  CUresult r = s_encode(tm, CU_TENSOR_MAP_DATA_TYPE_BFLOAT16, 2, (void*)ptr, dims, strides, box, es, CU_TENSOR_MAP_INTERLEAVE_NONE,
                        CU_TENSOR_MAP_SWIZZLE_128B, CU_TENSOR_MAP_L2_PROMOTION_L2_256B, CU_TENSOR_MAP_FLOAT_OOB_FILL_NONE);
  if (r != CUDA_SUCCESS) fprintf(stderr, "tensor map encode failed (%d)\n", (int)r);
}
static void tm_3d(CUtensorMap* tm, const void* ptr, uint64_t rows, uint64_t cols) {
  cuuint64_t dims[3] = {64, rows, cols / 64}; cuuint64_t strides[2] = {cols * 2, 128}; cuuint32_t box[3] = {64, 64, 2}; cuuint32_t es[3] = {1, 1, 1};
  CUresult r = s_encode(tm, CU_TENSOR_MAP_DATA_TYPE_BFLOAT16, 3, (void*)ptr, dims, strides, box, es, CU_TENSOR_MAP_INTERLEAVE_NONE,
                        CU_TENSOR_MAP_SWIZZLE_128B, CU_TENSOR_MAP_L2_PROMOTION_L2_256B, CU_TENSOR_MAP_FLOAT_OOB_FILL_NONE);
  if (r != CUDA_SUCCESS) fprintf(stderr, "tensor map encode failed (%d)\n", (int)r);
}
static inline uint16_t mk(int type, int a, int b) { return (uint16_t)(type << 12 | a << 5 | b); }

static void build_schedule(Params& P) {
  int cnt[NCLUSTER];
  for (int c = 0; c < NCLUSTER; c++) { cnt[c] = 0; for (int i = 0; i < MAXI; i++) P.items[c][i] = mk(T_END, 0, 0); }
  auto push = [&](int c, uint16_t v) { P.items[c][cnt[c]++] = v; };
  int natt[NCLUSTER], nq[NCLUSTER];
  for (int c = 0; c < NCLUSTER; c++) { natt[c] = c < 32 ? 3 : (c < 56 ? 5 : (c < 62 ? 4 : (c < 64 ? 3 : 5))); nq[c] = c < 56 ? 1 : (c < 62 ? 7 : (c < 64 ? 9 : 6)); }
  for (int c = 0; c < 56; c++) push(c, mk(T_Z2, c % 8, c / 8));
  int qi = 0;
  for (int slot = 0; slot < 9; slot++)
    for (int c = NCLUSTER - 1; c >= 0; c--) {
      const int first = c < 56 ? 1 : 0;
      if (slot >= first && slot < first + nq[c]) { push(c, mk(T_Q, qi % 8, qi / 8)); qi++; }
    }
  for (int c = 0; c < 56; c++) push(c, mk(T_U, c % 8, c / 8));
  int ai = 0;
  for (int slot = 0; slot < 5; slot++)
    for (int c = 0; c < NCLUSTER; c++) {
      const int first = c < 32 ? 0 : 5 - natt[c];
      if (slot >= first && slot < first + natt[c]) { push(c, mk(T_ATT, ai / 8, ai % 8)); ai++; }
    }
  for (int c = 0; c < 32; c++) push(c, mk(T_SA, c % 8, c / 8));
  for (int c = 0; c < 64; c++) push(c, mk(T_FIN, c % 16, c / 16));
  if (qi != 128 || ai != 256) fprintf(stderr, "bad schedule %d %d\n", qi, ai);
}

static Params s_params;
extern "C" void kernel_launch(void* const* d_in, const int* in_sizes, int n_in, void* d_out, int out_size) {
  (void)in_sizes; (void)n_in; (void)out_size;
  if (!s_encode) {
    void* fn = nullptr; cudaDriverEntryPointQueryResult qr;
    cudaGetDriverEntryPoint("cuTensorMapEncodeTiled", &fn, cudaEnableDefault, &qr);
    s_encode = (PFN_encodeTiled)fn;
    cudaFuncSetAttribute(fused_kernel, cudaFuncAttributeMaxDynamicSharedMemorySize, SMEM_BYTES);
    build_schedule(s_params);
  }
  Params& P = s_params;
  void *xn, *q, *o, *z2, *u, *gg, *sa;
  cudaGetSymbolAddress(&gg, g_g); cudaGetSymbolAddress(&sa, g_sa);
  cudaGetSymbolAddress(&xn, g_xn); cudaGetSymbolAddress(&q, g_q); cudaGetSymbolAddress(&o, g_o);
  cudaGetSymbolAddress(&z2, g_z2); cudaGetSymbolAddress(&u, g_u);
  tm_2d(&P.tm[TM_XN], xn, SEQ, DM, 128); tm_2d(&P.tm[TM_WSP], d_in[7], SEQ, SEQ, 128); tm_2d(&P.tm[TM_U], u, SEQ, FH, 128);
  tm_2d(&P.tm[TM_O], o, SEQ, HD, 128); tm_2d(&P.tm[TM_Q], q, SEQ, HD, 128); tm_2d(&P.tm[TM_X], d_in[0], SEQ, DM, 128);
  tm_2d(&P.tm[TM_K], d_in[1], NH * SEQ, 128, 128); tm_2d(&P.tm[TM_V], d_in[2], NH * SEQ, 128, 128);
  tm_2d(&P.tm[TM_SA], sa, SEQ, DM, 128); tm_2d(&P.tm[TM_G], gg, SEQ, DM, 128); tm_2d(&P.tm[TM_O64], o, SEQ, HD, 64);
  tm_3d(&P.tm[TM_WIN], d_in[6], DM, FF); tm_3d(&P.tm[TM_WQ], d_in[3], DM, HD); tm_3d(&P.tm[TM_Z2], z2, SEQ, FH);
  tm_3d(&P.tm[TM_WOUT], d_in[9], FH, DM); tm_3d(&P.tm[TM_WO], d_in[4], HD, DM);
  tm_2d(&P.tm[TS_Q], q, SEQ, HD, ST_ROWS); tm_2d(&P.tm[TS_O], o, SEQ, HD, ST_ROWS); tm_2d(&P.tm[TS_Z2], z2, SEQ, FH, ST_ROWS); tm_2d(&P.tm[TS_U], u, SEQ, FH, ST_ROWS);
  tm_2d(&P.tm[TS_SA], sa, SEQ, DM, ST_ROWS); tm_2d(&P.tm[TS_G], gg, SEQ, DM, ST_ROWS); tm_2d(&P.tm[TS_OUT], d_out, SEQ, DM, ST_ROWS);
  P.x = (const bf16*)d_in[0]; P.b_sp = (const bf16*)d_in[8];
  fused_kernel<<<2 * NCLUSTER, 384, SMEM_BYTES, cudaStreamPerThread>>>(P);
}
```

```cpp
#include <cuda_runtime.h>
#include <cuda_bf16.h>
#include <cuda.h>
#include <stdint.h>
#include <stdio.h>

typedef __nv_bfloat16 bf16;

constexpr int SEQ = 2048, DM = 1024, NH = 32, HD = 4096, FF = 3584, FH = 1792;

__device__ __align__(1024) bf16 g_xn[SEQ * DM];
__device__ __align__(1024) bf16 g_q[SEQ * HD];
__device__ __align__(1024) bf16 g_o[SEQ * HD];
__device__ __align__(1024) bf16 g_z2[SEQ * FH];
__device__ __align__(1024) bf16 g_u[SEQ * FH];
__device__ __align__(1024) uint4 g_stats[SEQ * 8];
__device__ __align__(1024) bf16 g_g[SEQ * DM];
__device__ __align__(1024) bf16 g_sa[SEQ * DM];
constexpr int F_XN = 0;
constexpr int F_Z2 = 512;
constexpr int F_Q = 768;
constexpr int F_U = 1024;
constexpr int F_O = 1536;
constexpr int F_S = 2048;
constexpr int F_TOTAL = 2112;
__device__ __align__(1024) unsigned g_flags[F_TOTAL];
__device__ unsigned g_done;
__device__ unsigned g_epoch;

__device__ __forceinline__ uint32_t smem_u32(const void* p) { return (uint32_t)__cvta_generic_to_shared(p); }
__device__ __forceinline__ void mbar_init(uint32_t bar, uint32_t cnt) { asm volatile("mbarrier.init.shared::cta.b64 [%0], %1;" :: "r"(bar), "r"(cnt)); }
__device__ __forceinline__ void mbar_expect_tx(uint32_t bar, uint32_t bytes) { asm volatile("mbarrier.arrive.expect_tx.shared::cta.b64 _, [%0], %1;" :: "r"(bar), "r"(bytes) : "memory"); }
__device__ __forceinline__ void mbar_arrive(uint32_t bar) { asm volatile("mbarrier.arrive.shared::cta.b64 _, [%0];" :: "r"(bar) : "memory"); }
__device__ __forceinline__ void mbar_arrive_cta(uint32_t bar, uint32_t cta) {
  asm volatile("{\n.reg .b32 ra;\nmapa.shared::cluster.u32 ra, %0, %1;\nmbarrier.arrive.shared::cluster.b64 _, [ra];\n}" :: "r"(bar), "r"(cta) : "memory");
}
__device__ __forceinline__ void mbar_arrive_cta_release(uint32_t bar, uint32_t cta) {
  asm volatile("{\n.reg .b32 ra;\nmapa.shared::cluster.u32 ra, %0, %1;\nmbarrier.arrive.release.cluster.shared::cluster.b64 _, [ra];\n}" :: "r"(bar), "r"(cta) : "memory");
}
__device__ __forceinline__ bool mbar_test(uint32_t bar, uint32_t parity) {
  uint32_t ok;
  asm volatile("{\n.reg .pred P1;\nmbarrier.test_wait.parity.shared::cta.b64 P1, [%1], %2;\nselp.u32 %0, 1, 0, P1;\n}" : "=r"(ok) : "r"(bar), "r"(parity) : "memory");
  return ok;
}
__device__ __forceinline__ bool mbar_try(uint32_t bar, uint32_t parity) {
  uint32_t ok;
  asm volatile("{\n.reg .pred P1;\nmbarrier.try_wait.parity.shared::cta.b64 P1, [%1], %2;\nselp.u32 %0, 1, 0, P1;\n}" : "=r"(ok) : "r"(bar), "r"(parity) : "memory");
  return ok;
}
constexpr uint32_t SPIN_LIMIT = 1u << 22;
__device__ __forceinline__ void trap_if(bool c) { asm volatile("{\n.reg .pred P;\nsetp.ne.u32 P, %0, 0;\n@P trap;\n}" :: "r"((uint32_t)c)); }
__device__ __forceinline__ void mbar_wait(uint32_t bar, uint32_t parity) {
  asm volatile("{\n.reg .pred P1;\n.reg .u32 n;\nmbarrier.try_wait.parity.shared::cta.b64 P1, [%0], %1;\n@P1 bra DONE;\nmov.u32 n, 0;\n"
               "LOOP:\nmbarrier.try_wait.parity.shared::cta.b64 P1, [%0], %1;\n@P1 bra DONE;\nadd.u32 n, n, 1;\nsetp.gt.u32 P1, n, %2;\n@P1 trap;\nbra LOOP;\nDONE:\n}"
               :: "r"(bar), "r"(parity), "n"(SPIN_LIMIT) : "memory");
}
__device__ __forceinline__ void mbar_spin(uint32_t bar, uint32_t parity) {
  asm volatile("{\n.reg .pred P1;\nLOOP:\nmbarrier.try_wait.parity.shared::cta.b64 P1, [%0], %1;\n@!P1 bra LOOP;\n}" :: "r"(bar), "r"(parity) : "memory");
}
__device__ __forceinline__ bool mbar_try_long(uint32_t bar, uint32_t parity) {
  uint32_t ok;
  asm volatile("{\n.reg .pred P1;\nmbarrier.try_wait.parity.shared::cta.b64 P1, [%1], %2, %3;\nselp.u32 %0, 1, 0, P1;\n}" : "=r"(ok) : "r"(bar), "r"(parity), "r"(2000) : "memory");
  return ok;
}
__device__ __forceinline__ void mbar_wait_sleep(uint32_t bar, uint32_t parity, uint32_t ns) {
  uint32_t n = 0;
  while (!mbar_test(bar, parity)) { trap_if(++n > SPIN_LIMIT * 4); __nanosleep(ns); }
}
__device__ __forceinline__ void mbar_wait_long(uint32_t bar, uint32_t parity) {
  uint32_t n = 0;
  while (!mbar_try_long(bar, parity)) trap_if(++n > SPIN_LIMIT);
}
__device__ __forceinline__ void mbar_wait_cluster(uint32_t bar, uint32_t parity) {
  asm volatile("{\n.reg .pred P1;\n.reg .u32 n;\nmov.u32 n, 0;\n"
               "LOOP:\nmbarrier.try_wait.parity.acquire.cluster.shared::cta.b64 P1, [%0], %1;\n@P1 bra DONE;\nadd.u32 n, n, 1;\nsetp.gt.u32 P1, n, %2;\n@P1 trap;\nbra LOOP;\nDONE:\n}"
               :: "r"(bar), "r"(parity), "n"(SPIN_LIMIT) : "memory");
}
__device__ __forceinline__ void tma_load_2d(uint32_t dst, const CUtensorMap* tm, int c0, int c1, uint32_t bar) {
  asm volatile("cp.async.bulk.tensor.2d.shared::cluster.global.mbarrier::complete_tx::bytes [%0], [%1, {%3, %4}], [%2];"
    :: "r"(dst), "l"(tm), "r"(bar), "r"(c0), "r"(c1) : "memory");
}
__device__ __forceinline__ void tma_load_2d_mc(uint32_t dst, const CUtensorMap* tm, int c0, int c1, uint32_t bar) {
  asm volatile("cp.async.bulk.tensor.2d.shared::cluster.global.mbarrier::complete_tx::bytes.multicast::cluster [%0], [%1, {%3, %4}], [%2], %5;"
    :: "r"(dst), "l"(tm), "r"(bar), "r"(c0), "r"(c1), "h"((uint16_t)3) : "memory");
}
__device__ __forceinline__ uint64_t policy_evict_normal() { uint64_t p; asm volatile("createpolicy.fractional.L2::evict_normal.b64 %0, 1.0;" : "=l"(p)); return p; }
__device__ __forceinline__ uint64_t policy_evict_first() { uint64_t p; asm volatile("createpolicy.fractional.L2::evict_first.b64 %0, 1.0;" : "=l"(p)); return p; }
__device__ __forceinline__ void tma_load_2d_hint(uint32_t dst, const CUtensorMap* tm, int c0, int c1, uint32_t bar, uint64_t pol) {
  asm volatile("cp.async.bulk.tensor.2d.shared::cluster.global.mbarrier::complete_tx::bytes.L2::cache_hint [%0], [%1, {%3, %4}], [%2], %5;"
    :: "r"(dst), "l"(tm), "r"(bar), "r"(c0), "r"(c1), "l"(pol) : "memory");
}
__device__ __forceinline__ void tma_load_2d_mc_hint(uint32_t dst, const CUtensorMap* tm, int c0, int c1, uint32_t bar, uint64_t pol) {
  asm volatile("cp.async.bulk.tensor.2d.shared::cluster.global.mbarrier::complete_tx::bytes.multicast::cluster.L2::cache_hint [%0], [%1, {%3, %4}], [%2], %5, %6;"
    :: "r"(dst), "l"(tm), "r"(bar), "r"(c0), "r"(c1), "h"((uint16_t)3), "l"(pol) : "memory");
}
__device__ __forceinline__ void tma_prefetch_2d(const CUtensorMap* tm, int c0, int c1) {
  asm volatile("cp.async.bulk.prefetch.tensor.2d.L2.global [%0, {%1, %2}];" :: "l"(tm), "r"(c0), "r"(c1) : "memory");
}
__device__ __forceinline__ void tma_prefetch_3d(const CUtensorMap* tm, int c1, int c2) {
  asm volatile("cp.async.bulk.prefetch.tensor.3d.L2.global [%0, {%1, %2, %3}];" :: "l"(tm), "r"(0), "r"(c1), "r"(c2) : "memory");
}
__device__ __forceinline__ void l2_prefetch(const void* p, uint32_t bytes) { asm volatile("cp.async.bulk.prefetch.L2.global [%0], %1;" :: "l"(p), "r"(bytes) : "memory"); }
__device__ __forceinline__ void tma_load_3d(uint32_t dst, const CUtensorMap* tm, int c1, int c2, uint32_t bar) {
  asm volatile("cp.async.bulk.tensor.3d.shared::cluster.global.mbarrier::complete_tx::bytes [%0], [%1, {%3, %4, %5}], [%2];"
    :: "r"(dst), "l"(tm), "r"(bar), "r"(0), "r"(c1), "r"(c2) : "memory");
}
__device__ __forceinline__ void tma_load_3d_mc(uint32_t dst, const CUtensorMap* tm, int c1, int c2, uint32_t bar) {
  asm volatile("cp.async.bulk.tensor.3d.shared::cluster.global.mbarrier::complete_tx::bytes.multicast::cluster [%0], [%1, {%3, %4, %5}], [%2], %6;"
    :: "r"(dst), "l"(tm), "r"(bar), "r"(0), "r"(c1), "r"(c2), "h"((uint16_t)3) : "memory");
}
__device__ __forceinline__ void tma_store_2d(const CUtensorMap* tm, uint32_t src, int c0, int c1) {
  asm volatile("cp.async.bulk.tensor.2d.global.shared::cta.bulk_group [%0, {%2, %3}], [%1];" :: "l"(tm), "r"(src), "r"(c0), "r"(c1) : "memory");
}
__device__ __forceinline__ void bulk_commit() { asm volatile("cp.async.bulk.commit_group;" ::: "memory"); }
template <int N> __device__ __forceinline__ void bulk_wait_read() { asm volatile("cp.async.bulk.wait_group.read %0;" :: "n"(N) : "memory"); }
template <int N> __device__ __forceinline__ void bulk_wait() { asm volatile("cp.async.bulk.wait_group %0;" :: "n"(N) : "memory"); }
__device__ __forceinline__ void fence_async_smem() { asm volatile("fence.proxy.async.shared::cta;" ::: "memory"); }
__device__ __forceinline__ void fence_async_global() { asm volatile("fence.proxy.async.global;" ::: "memory"); }
__device__ __forceinline__ void wgmma_fence() { asm volatile("wgmma.fence.sync.aligned;" ::: "memory"); }
__device__ __forceinline__ void wgmma_commit() { asm volatile("wgmma.commit_group.sync.aligned;" ::: "memory"); }
template <int N> __device__ __forceinline__ void wgmma_wait() { asm volatile("wgmma.wait_group.sync.aligned %0;" :: "n"(N) : "memory"); }
__device__ __forceinline__ uint64_t make_desc(uint32_t addr, uint32_t lbo, uint32_t sbo) {
  return (uint64_t)((addr & 0x3FFFF) >> 4) | ((uint64_t)(lbo >> 4) << 16) | ((uint64_t)(sbo >> 4) << 32) | (1ull << 62);
}
template <int N> __device__ __forceinline__ void fence_regs(float (&d)[N]) {
#pragma unroll
  for (int i = 0; i < N; i++) asm volatile("" : "+f"(d[i]) :: "memory");
}
template <int N> __device__ __forceinline__ void fence_regs(uint32_t (&d)[N]) {
#pragma unroll
  for (int i = 0; i < N; i++) asm volatile("" : "+r"(d[i]) :: "memory");
}
__device__ __forceinline__ void named_sync(int id) { asm volatile("bar.sync %0, 256;" :: "r"(id) : "memory"); }
__device__ __forceinline__ void named_arrive(int id) { asm volatile("bar.arrive %0, 256;" :: "r"(id) : "memory"); }
__device__ __forceinline__ void pp_sync(bool w) { asm volatile("{\n.reg .pred p;\nsetp.ne.u32 p, %0, 0;\n@p bar.sync 2, 256;\n@!p bar.sync 1, 256;\n}" :: "r"((uint32_t)w) : "memory"); }
__device__ __forceinline__ void pp_arrive(bool w) { asm volatile("{\n.reg .pred p;\nsetp.ne.u32 p, %0, 0;\n@p bar.arrive 1, 256;\n@!p bar.arrive 2, 256;\n}" :: "r"((uint32_t)w) : "memory"); }
__device__ __forceinline__ bool wg_any(bool w, bool v) {
  uint32_t r;
  asm volatile("{\n.reg .pred p, q;\nsetp.ne.u32 p, %1, 0;\nbar.red.or.pred q, %2, 128, p;\nselp.u32 %0, 1, 0, q;\n}" : "=r"(r) : "r"((uint32_t)v), "r"(w ? 4 : 3) : "memory");
  return __any_sync(0xffffffffu, r);
}
__device__ __forceinline__ int fresh_warp() { uint32_t t; asm volatile("mov.u32 %0, %%tid.x;" : "=r"(t)); return __shfl_sync(0xffffffffu, (int)(t >> 5) - 4, 0); }
__device__ __forceinline__ void cluster_sync_all() { asm volatile("barrier.cluster.arrive.release.aligned;\nbarrier.cluster.wait.acquire.aligned;" ::: "memory"); }
__device__ __forceinline__ void cluster_sync_relaxed() { asm volatile("barrier.cluster.arrive.relaxed.aligned;\nbarrier.cluster.wait.aligned;" ::: "memory"); }
__device__ __forceinline__ uint32_t cluster_rank() { uint32_t r; asm volatile("mov.u32 %0, %%cluster_ctarank;" : "=r"(r)); return r; }
__device__ __forceinline__ unsigned ld_acquire(const unsigned* p) { unsigned v; asm volatile("ld.acquire.gpu.global.u32 %0, [%1];" : "=r"(v) : "l"(p) : "memory"); return v; }
__device__ __forceinline__ void red_release(unsigned* p, unsigned v) { asm volatile("red.release.gpu.global.add.u32 [%0], %1;" :: "l"(p), "r"(v) : "memory"); }
__device__ __forceinline__ void flag_wait(const unsigned* p, unsigned target) {
  uint32_t n = 0;
  while (ld_acquire(p) < target) { trap_if(++n > SPIN_LIMIT); __nanosleep(20); }
}
__device__ __forceinline__ void st_tagged(uint4* p, float a, float b, uint32_t tag) {
  asm volatile("{\n.reg .b64 x, y;\nmov.b64 x, {%1, %3};\nmov.b64 y, {%2, %3};\nst.relaxed.gpu.global.v2.b64 [%0], {x, y};\n}" :: "l"(p), "r"(__float_as_uint(a)), "r"(__float_as_uint(b)), "r"(tag) : "memory");
}
__device__ __forceinline__ bool ld_tagged(const uint4* p, float& a, float& b, uint32_t tag) {
  uint32_t u, v, t0, t1;
  asm volatile("{\n.reg .b64 x, y;\nld.relaxed.gpu.global.v2.b64 {x, y}, [%4];\nmov.b64 {%0, %2}, x;\nmov.b64 {%1, %3}, y;\n}" : "=r"(u), "=r"(v), "=r"(t0), "=r"(t1) : "l"(p) : "memory");
  a = __uint_as_float(u); b = __uint_as_float(v);
  return t0 == tag && t1 == tag;
}
__device__ __forceinline__ uint32_t pack_bf16(float lo, float hi) { uint32_t r; asm("cvt.rn.bf16x2.f32 %0, %1, %2;" : "=r"(r) : "f"(hi), "f"(lo)); return r; }
__device__ __forceinline__ uint32_t bf2_fma(uint32_t a, uint32_t b, uint32_t c) { uint32_t r; asm("fma.rn.bf16x2 %0, %1, %2, %3;" : "=r"(r) : "r"(a), "r"(b), "r"(c)); return r; }
__device__ __forceinline__ uint32_t bf2_mul(uint32_t a, uint32_t b) { uint32_t r; asm("mul.rn.bf16x2 %0, %1, %2;" : "=r"(r) : "r"(a), "r"(b)); return r; }
__device__ __forceinline__ uint32_t bf2_add(uint32_t a, uint32_t b) { uint32_t r; asm("add.rn.bf16x2 %0, %1, %2;" : "=r"(r) : "r"(a), "r"(b)); return r; }
constexpr uint32_t BF2_HALF = 0x3f003f00u;
__device__ __forceinline__ float bf_lo(uint32_t v) { return __uint_as_float(v << 16); }
__device__ __forceinline__ float bf_hi(uint32_t v) { return __uint_as_float(v & 0xffff0000u); }
__device__ __forceinline__ float ex2(float x) { float y; asm("ex2.approx.ftz.f32 %0, %1;" : "=f"(y) : "f"(x)); return y; }
__device__ __forceinline__ float tanh_fast(float x) { float y; asm("tanh.approx.f32 %0, %1;" : "=f"(y) : "f"(x)); return y; }
__device__ __forceinline__ void stmatrix_x4(uint32_t addr, uint32_t a, uint32_t b, uint32_t c, uint32_t d) {
  asm volatile("stmatrix.sync.aligned.m8n8.x4.shared.b16 [%0], {%1, %2, %3, %4};" :: "r"(addr), "r"(a), "r"(b), "r"(c), "r"(d) : "memory");
}
__device__ __forceinline__ void ldmatrix_x4(uint32_t addr, uint32_t& a, uint32_t& b, uint32_t& c, uint32_t& d) {
  asm volatile("ldmatrix.sync.aligned.m8n8.x4.shared.b16 {%0, %1, %2, %3}, [%4];" : "=r"(a), "=r"(b), "=r"(c), "=r"(d) : "r"(addr) : "memory");
}
__device__ __forceinline__ uint32_t lane_id() { uint32_t l; asm volatile("mov.u32 %0, %%laneid;" : "=r"(l)); return l; }
__device__ __forceinline__ bool elect_one() {
  uint32_t r;
  asm volatile("{\n.reg .pred P;\nelect.sync _|P, 0xffffffff;\nselp.u32 %0, 1, 0, P;\n}" : "=r"(r));
  return r;
}
__device__ __forceinline__ uint64_t gtime() { uint64_t t; asm volatile("mov.u64 %0, %%globaltimer;" : "=l"(t)); return t; }

__device__ __forceinline__ void wgmma_m64n128k16_ss_tb0(float (&d)[64], uint64_t da, uint64_t db, int scale_d) {
  asm volatile("{\n.reg .pred p;\nsetp.ne.b32 p, %66, 0;\n"
    "wgmma.mma_async.sync.aligned.m64n128k16.f32.bf16.bf16 "
    "{%0, %1, %2, %3, %4, %5, %6, %7, %8, %9, %10, %11, %12, %13, %14, %15, %16, %17, %18, %19, %20, %21, %22, %23, %24, %25, %26, %27, %28, %29, %30, %31, %32, %33, %34, %35, %36, %37, %38, %39, %40, %41, %42, %43, %44, %45, %46, %47, %48, %49, %50, %51, %52, %53, %54, %55, %56, %57, %58, %59, %60, %61, %62, %63}, "
    "%64, %65, p, 1, 1, 0, 0;\n}\n"
    : "+f"(d[0]), "+f"(d[1]), "+f"(d[2]), "+f"(d[3]), "+f"(d[4]), "+f"(d[5]), "+f"(d[6]), "+f"(d[7]), "+f"(d[8]), "+f"(d[9]), "+f"(d[10]), "+f"(d[11]), "+f"(d[12]), "+f"(d[13]), "+f"(d[14]), "+f"(d[15]), "+f"(d[16]), "+f"(d[17]), "+f"(d[18]), "+f"(d[19]), "+f"(d[20]), "+f"(d[21]), "+f"(d[22]), "+f"(d[23]), "+f"(d[24]), "+f"(d[25]), "+f"(d[26]), "+f"(d[27]), "+f"(d[28]), "+f"(d[29]), "+f"(d[30]), "+f"(d[31]), "+f"(d[32]), "+f"(d[33]), "+f"(d[34]), "+f"(d[35]), "+f"(d[36]), "+f"(d[37]), "+f"(d[38]), "+f"(d[39]), "+f"(d[40]), "+f"(d[41]), "+f"(d[42]), "+f"(d[43]), "+f"(d[44]), "+f"(d[45]), "+f"(d[46]), "+f"(d[47]), "+f"(d[48]), "+f"(d[49]), "+f"(d[50]), "+f"(d[51]), "+f"(d[52]), "+f"(d[53]), "+f"(d[54]), "+f"(d[55]), "+f"(d[56]), "+f"(d[57]), "+f"(d[58]), "+f"(d[59]), "+f"(d[60]), "+f"(d[61]), "+f"(d[62]), "+f"(d[63])
    : "l"(da), "l"(db), "r"(scale_d));
}
__device__ __forceinline__ void wgmma_m64n256k16_ss_tb1(float (&d)[128], uint64_t da, uint64_t db, int scale_d) {
  asm volatile("{\n.reg .pred p;\nsetp.ne.b32 p, %130, 0;\n"
    "wgmma.mma_async.sync.aligned.m64n256k16.f32.bf16.bf16 "
    "{%0, %1, %2, %3, %4, %5, %6, %7, %8, %9, %10, %11, %12, %13, %14, %15, %16, %17, %18, %19, %20, %21, %22, %23, %24, %25, %26, %27, %28, %29, %30, %31, %32, %33, %34, %35, %36, %37, %38, %39, %40, %41, %42, %43, %44, %45, %46, %47, %48, %49, %50, %51, %52, %53, %54, %55, %56, %57, %58, %59, %60, %61, %62, %63, %64, %65, %66, %67, %68, %69, %70, %71, %72, %73, %74, %75, %76, %77, %78, %79, %80, %81, %82, %83, %84, %85, %86, %87, %88, %89, %90, %91, %92, %93, %94, %95, %96, %97, %98, %99, %100, %101, %102, %103, %104, %105, %106, %107, %108, %109, %110, %111, %112, %113, %114, %115, %116, %117, %118, %119, %120, %121, %122, %123, %124, %125, %126, %127}, "
    "%128, %129, p, 1, 1, 0, 1;\n}\n"
    : "+f"(d[0]), "+f"(d[1]), "+f"(d[2]), "+f"(d[3]), "+f"(d[4]), "+f"(d[5]), "+f"(d[6]), "+f"(d[7]), "+f"(d[8]), "+f"(d[9]), "+f"(d[10]), "+f"(d[11]), "+f"(d[12]), "+f"(d[13]), "+f"(d[14]), "+f"(d[15]), "+f"(d[16]), "+f"(d[17]), "+f"(d[18]), "+f"(d[19]), "+f"(d[20]), "+f"(d[21]), "+f"(d[22]), "+f"(d[23]), "+f"(d[24]), "+f"(d[25]), "+f"(d[26]), "+f"(d[27]), "+f"(d[28]), "+f"(d[29]), "+f"(d[30]), "+f"(d[31]), "+f"(d[32]), "+f"(d[33]), "+f"(d[34]), "+f"(d[35]), "+f"(d[36]), "+f"(d[37]), "+f"(d[38]), "+f"(d[39]), "+f"(d[40]), "+f"(d[41]), "+f"(d[42]), "+f"(d[43]), "+f"(d[44]), "+f"(d[45]), "+f"(d[46]), "+f"(d[47]), "+f"(d[48]), "+f"(d[49]), "+f"(d[50]), "+f"(d[51]), "+f"(d[52]), "+f"(d[53]), "+f"(d[54]), "+f"(d[55]), "+f"(d[56]), "+f"(d[57]), "+f"(d[58]), "+f"(d[59]), "+f"(d[60]), "+f"(d[61]), "+f"(d[62]), "+f"(d[63]), "+f"(d[64]), "+f"(d[65]), "+f"(d[66]), "+f"(d[67]), "+f"(d[68]), "+f"(d[69]), "+f"(d[70]), "+f"(d[71]), "+f"(d[72]), "+f"(d[73]), "+f"(d[74]), "+f"(d[75]), "+f"(d[76]), "+f"(d[77]), "+f"(d[78]), "+f"(d[79]), "+f"(d[80]), "+f"(d[81]), "+f"(d[82]), "+f"(d[83]), "+f"(d[84]), "+f"(d[85]), "+f"(d[86]), "+f"(d[87]), "+f"(d[88]), "+f"(d[89]), "+f"(d[90]), "+f"(d[91]), "+f"(d[92]), "+f"(d[93]), "+f"(d[94]), "+f"(d[95]), "+f"(d[96]), "+f"(d[97]), "+f"(d[98]), "+f"(d[99]), "+f"(d[100]), "+f"(d[101]), "+f"(d[102]), "+f"(d[103]), "+f"(d[104]), "+f"(d[105]), "+f"(d[106]), "+f"(d[107]), "+f"(d[108]), "+f"(d[109]), "+f"(d[110]), "+f"(d[111]), "+f"(d[112]), "+f"(d[113]), "+f"(d[114]), "+f"(d[115]), "+f"(d[116]), "+f"(d[117]), "+f"(d[118]), "+f"(d[119]), "+f"(d[120]), "+f"(d[121]), "+f"(d[122]), "+f"(d[123]), "+f"(d[124]), "+f"(d[125]), "+f"(d[126]), "+f"(d[127])
    : "l"(da), "l"(db), "r"(scale_d));
}
__device__ __forceinline__ void wgmma_m64n128k16_rs_tb1(float (&d)[64], uint32_t a0, uint32_t a1, uint32_t a2, uint32_t a3, uint64_t db, int scale_d) {
  asm volatile("{\n.reg .pred p;\nsetp.ne.b32 p, %69, 0;\n"
    "wgmma.mma_async.sync.aligned.m64n128k16.f32.bf16.bf16 "
    "{%0, %1, %2, %3, %4, %5, %6, %7, %8, %9, %10, %11, %12, %13, %14, %15, %16, %17, %18, %19, %20, %21, %22, %23, %24, %25, %26, %27, %28, %29, %30, %31, %32, %33, %34, %35, %36, %37, %38, %39, %40, %41, %42, %43, %44, %45, %46, %47, %48, %49, %50, %51, %52, %53, %54, %55, %56, %57, %58, %59, %60, %61, %62, %63}, "
    "{%64, %65, %66, %67}, %68, p, 1, 1, 1;\n}\n"
    : "+f"(d[0]), "+f"(d[1]), "+f"(d[2]), "+f"(d[3]), "+f"(d[4]), "+f"(d[5]), "+f"(d[6]), "+f"(d[7]), "+f"(d[8]), "+f"(d[9]), "+f"(d[10]), "+f"(d[11]), "+f"(d[12]), "+f"(d[13]), "+f"(d[14]), "+f"(d[15]), "+f"(d[16]), "+f"(d[17]), "+f"(d[18]), "+f"(d[19]), "+f"(d[20]), "+f"(d[21]), "+f"(d[22]), "+f"(d[23]), "+f"(d[24]), "+f"(d[25]), "+f"(d[26]), "+f"(d[27]), "+f"(d[28]), "+f"(d[29]), "+f"(d[30]), "+f"(d[31]), "+f"(d[32]), "+f"(d[33]), "+f"(d[34]), "+f"(d[35]), "+f"(d[36]), "+f"(d[37]), "+f"(d[38]), "+f"(d[39]), "+f"(d[40]), "+f"(d[41]), "+f"(d[42]), "+f"(d[43]), "+f"(d[44]), "+f"(d[45]), "+f"(d[46]), "+f"(d[47]), "+f"(d[48]), "+f"(d[49]), "+f"(d[50]), "+f"(d[51]), "+f"(d[52]), "+f"(d[53]), "+f"(d[54]), "+f"(d[55]), "+f"(d[56]), "+f"(d[57]), "+f"(d[58]), "+f"(d[59]), "+f"(d[60]), "+f"(d[61]), "+f"(d[62]), "+f"(d[63])
    : "r"(a0), "r"(a1), "r"(a2), "r"(a3), "l"(db), "r"(scale_d));
}
__device__ __forceinline__ void wgmma_m64n128k16_ss_tb1(float (&d)[64], uint64_t da, uint64_t db, int scale_d) {
  asm volatile("{\n.reg .pred p;\nsetp.ne.b32 p, %66, 0;\n"
    "wgmma.mma_async.sync.aligned.m64n128k16.f32.bf16.bf16 "
    "{%0, %1, %2, %3, %4, %5, %6, %7, %8, %9, %10, %11, %12, %13, %14, %15, %16, %17, %18, %19, %20, %21, %22, %23, %24, %25, %26, %27, %28, %29, %30, %31, %32, %33, %34, %35, %36, %37, %38, %39, %40, %41, %42, %43, %44, %45, %46, %47, %48, %49, %50, %51, %52, %53, %54, %55, %56, %57, %58, %59, %60, %61, %62, %63}, "
    "%64, %65, p, 1, 1, 0, 1;\n}\n"
    : "+f"(d[0]), "+f"(d[1]), "+f"(d[2]), "+f"(d[3]), "+f"(d[4]), "+f"(d[5]), "+f"(d[6]), "+f"(d[7]), "+f"(d[8]), "+f"(d[9]), "+f"(d[10]), "+f"(d[11]), "+f"(d[12]), "+f"(d[13]), "+f"(d[14]), "+f"(d[15]), "+f"(d[16]), "+f"(d[17]), "+f"(d[18]), "+f"(d[19]), "+f"(d[20]), "+f"(d[21]), "+f"(d[22]), "+f"(d[23]), "+f"(d[24]), "+f"(d[25]), "+f"(d[26]), "+f"(d[27]), "+f"(d[28]), "+f"(d[29]), "+f"(d[30]), "+f"(d[31]), "+f"(d[32]), "+f"(d[33]), "+f"(d[34]), "+f"(d[35]), "+f"(d[36]), "+f"(d[37]), "+f"(d[38]), "+f"(d[39]), "+f"(d[40]), "+f"(d[41]), "+f"(d[42]), "+f"(d[43]), "+f"(d[44]), "+f"(d[45]), "+f"(d[46]), "+f"(d[47]), "+f"(d[48]), "+f"(d[49]), "+f"(d[50]), "+f"(d[51]), "+f"(d[52]), "+f"(d[53]), "+f"(d[54]), "+f"(d[55]), "+f"(d[56]), "+f"(d[57]), "+f"(d[58]), "+f"(d[59]), "+f"(d[60]), "+f"(d[61]), "+f"(d[62]), "+f"(d[63])
    : "l"(da), "l"(db), "r"(scale_d));
}

enum { TM_XN, TM_WSP, TM_U, TM_O, TM_Q, TM_X, TM_SA, TM_G, TM_K, TM_V, TM_WO64,
       TM_WIN, TM_WQ, TM_Z2, TM_WOUT, TM_WO, TS_Q, TS_O, TS_Z2, TS_U, TS_SA, TS_G, TS_OUT, TM_COUNT };
enum { T_Z2 = 0, T_Q = 1, T_U = 2, T_ATT = 3, T_SA = 4, T_FIN = 5, T_END = 7 };
constexpr int NCLUSTER = 66, MAXI = 14;
struct alignas(64) Params {
  const bf16* x;
  const bf16* b_sp;
  CUtensorMap tm[TM_COUNT];
  uint16_t items[NCLUSTER][MAXI];
};

constexpr uint32_t G_STAGE = 49152, G_A = 16384, KV_SLOT = 32768;
constexpr uint32_t OFF_Q1 = 163840, OFF_Q0 = 196608, OFF_BAR = 229376, OFF_LN = OFF_BAR + 256, SMEM_BYTES = OFF_LN + 1024;
constexpr uint32_t B_GF = 0, B_GE = 32, B_KF = 64, B_KE = 104, B_QF = 144, B_QE = 160, B_XF = 176, B_XR = 184, B_STG = 192, B_FREE = 200, B_GO = 208, B_LN = 216, B_TAG = 224, B_RDY = 228, B_PROG = 232, B_PUB = 248;
#define SA_HEADS 17
#define SW_NS 40
#define ST_ROWS 16
#define ST_FLY 2
#define EF 0
#define KV_PF 4
#define KV_ALL 0
#define KV_PF0 -1
#define SMX 0
#define Z_DELAY 3
#define MZERO 1
#define SW_ATT 800
#define RESTAG 2
#define OUT_PF 8
constexpr float SM_C = 0.08838834764831845f * 1.4426950408889634f;
constexpr float GELU_A = 0.7978845608028654f, GELU_B = 0.7978845608028654f * 0.044715f;
constexpr float SM_ZERO = 24.f, SM_THR_Z = 1e12f;
constexpr float SM_THR = 1024.f;

#define TRACE(w, i)
#define FT(c, tag)

extern __shared__ __align__(1024) uint8_t smem_raw[];
__device__ __forceinline__ uint32_t smem_base() { return smem_u32(smem_raw); }
__device__ __forceinline__ uint32_t smem_desc() { return (smem_base() & 0x3FFFF) >> 4; }

struct Ring { uint32_t s, ph; };
template <int N> __device__ __forceinline__ void ring_adv(Ring& r) { if (++r.s == N) { r.s = 0; r.ph ^= 1; } }

__device__ __forceinline__ int get_item(const Params& p, int i) {
  uint32_t b; asm volatile("mov.u32 %0, %%ctaid.x;" : "=r"(b));
  return p.items[b >> 1][i];
}
struct Cons {
  uint32_t sb;
  int warp;
  Ring g;
  uint32_t fph;
};

__device__ __forceinline__ void stage_acquire(const Cons& c) { mbar_spin(c.sb + OFF_BAR + B_FREE, c.fph); }
__device__ __forceinline__ void stage_commit(Cons& c) {
  __syncwarp();
  if (lane_id() == 0) mbar_arrive(c.sb + OFF_BAR + B_STG);
  c.fph ^= 1;
}

__device__ __forceinline__ void release_slot(const Cons& c, uint32_t bar, bool mc) {
  if (lane_id() == 0 && (c.warp & 3) < 2) mbar_arrive_cta(bar, mc ? (uint32_t)(c.warp & 1) : (blockIdx.x & 1));
}
constexpr uint64_t DESC_HI = (uint64_t)0x40000040u << 32;

template <bool FIRST> __device__ __forceinline__ void gemm_step(float (&acc)[128], Cons& c) {
  mbar_spin(c.sb + OFF_BAR + B_GF + 8 * c.g.s, c.g.ph);
  const uint32_t st = ((c.sb & 0x3FFFF) >> 4) + c.g.s * (G_STAGE >> 4);
  const uint32_t da = st + (c.warp >> 2) * 512 + (1u << 16), db = st + (G_A >> 4) + ((8192u >> 4) << 16);
  wgmma_fence();
#pragma unroll
  for (int kk = 0; kk < 4; kk++) wgmma_m64n256k16_ss_tb1(acc, DESC_HI | (da + kk * 2), DESC_HI | (db + kk * 128), !(FIRST && kk == 0));
  wgmma_commit();
}

template <int N> __device__ __forceinline__ void stage_chunks(uint32_t buf, uint32_t stride, const uint32_t* pk) {
  const uint32_t ln = lane_id();
  const uint32_t a = buf + ((ln & 15) << 7);
  const uint32_t x = ln & 7, hi = ln >> 4;
#pragma unroll
  for (int i = 0; i < 4 * N; i++) stmatrix_x4(a + (i >> 2) * stride + (((2 * (i & 3) + hi) ^ x) << 4), pk[4 * i], pk[4 * i + 1], pk[4 * i + 2], pk[4 * i + 3]);
}

__device__ __forceinline__ float act2_fn(float x, float a, float b) {
  return fmaf(x, tanh_fast(x * fmaf(x * x, b, a)), x);
}
__device__ __forceinline__ float quad_sum(float v) { v += __shfl_xor_sync(0xffffffffu, v, 1); v += __shfl_xor_sync(0xffffffffu, v, 2); return v; }
__device__ __forceinline__ float quad_max(float v) { v = fmaxf(v, __shfl_xor_sync(0xffffffffu, v, 1)); v = fmaxf(v, __shfl_xor_sync(0xffffffffu, v, 2)); return v; }

__device__ __forceinline__ uint32_t load_tag(const Cons& c) { uint32_t t; asm volatile("ld.volatile.shared.u32 %0, [%1];" : "=r"(t) : "r"(c.sb + OFF_BAR + B_TAG)); return t; }

struct Shadow {
  int act;
  int store;
};
__device__ __forceinline__ void rotate16(uint32_t (&h)[64]) {
#pragma unroll
  for (int i = 0; i < 16; i++)
    asm volatile("{\n.reg .b32 t;\nmov.b32 t, %0;\nmov.b32 %0, %1;\nmov.b32 %1, %2;\nmov.b32 %2, %3;\nmov.b32 %3, t;\n}" : "+r"(h[i]), "+r"(h[i + 16]), "+r"(h[i + 32]), "+r"(h[i + 48]));
}

template <int O>
__device__ __forceinline__ void act_block(uint32_t (&held)[64], float ca, float cb, bool first, float& u0, float& u1, float& s0, float& s1, float& q0, float& q1) {
#pragma unroll
  for (int i = O; i < O + 4; i += 2) {
    const float a0 = act2_fn(bf_lo(held[i]), ca, cb), a1 = act2_fn(bf_hi(held[i]), ca, cb);
    const float b0 = act2_fn(bf_lo(held[i + 1]), ca, cb), b1 = act2_fn(bf_hi(held[i + 1]), ca, cb);
    if (i == 0 && first) { u0 = a0; u1 = b0; }
    float d;
    d = a0 - u0; s0 += d; q0 = fmaf(d, d, q0); d = a1 - u0; s0 += d; q0 = fmaf(d, d, q0);
    d = b0 - u1; s1 += d; q1 = fmaf(d, d, q1); d = b1 - u1; s1 += d; q1 = fmaf(d, d, q1);
    held[i] = pack_bf16(a0, a1); held[i + 1] = pack_bf16(b0, b1);
  }
}

template <int O> __device__ __forceinline__ void stage_half(Cons& c, uint32_t (&held)[64], bool norm) {
  if (norm) {
    uint32_t a0, a1, r0, r1;
    const uint32_t la = c.sb + OFF_LN + (c.warp * 16 + (lane_id() >> 2)) * 8;
    mbar_spin(c.sb + OFF_BAR + B_LN, 0);
    asm volatile("ld.shared.v2.b32 {%0, %1}, [%2];" : "=r"(r0), "=r"(a0) : "r"(la));
    asm volatile("ld.shared.v2.b32 {%0, %1}, [%2];" : "=r"(r1), "=r"(a1) : "r"(la + 64));
#pragma unroll
    for (int i = O; i < O + 32; i += 2) { held[i] = bf2_mul(bf2_add(held[i], a0), r0); held[i + 1] = bf2_mul(bf2_add(held[i + 1], a1), r1); }
  }
  stage_acquire(c);
  stage_chunks<2>(c.sb + OFF_Q0 + c.warp * 2048, 16384, held + O);
  stage_commit(c);
}

__device__ __forceinline__ void gemm_seg(float (&acc)[128], uint32_t (&held)[64], Cons& c, const Params& p, Shadow& sh, int nsteps) {
  const bool elected = lane_id() == 0 && (c.warp & 3) < 2;
  uint32_t rel;
  asm("mapa.shared::cluster.u32 %0, %1, %2;" : "=r"(rel) : "r"(c.sb + OFF_BAR + B_GE), "r"((uint32_t)(c.warp & 1)));
  gemm_step<true>(acc, c);
  ring_adv<4>(c.g);
  int k = 1;
#define G_STEP()                                                                                                   \
  { gemm_step<false>(acc, c);                                                                                    \
    FT(c, 70);                                                                                                          \
    wgmma_wait<1>();                                                                                                    \
    if (elected) asm volatile("mbarrier.arrive.shared::cluster.b64 _, [%0];" :: "r"(rel + 8 * ((c.g.s - 1) & 3)) : "memory"); \
    ring_adv<4>(c.g);                                                                                                             \
    k++; }
  if (sh.act != 0) {
    float u0 = 0.f, u1 = 0.f, s0 = 0.f, s1 = 0.f, q0 = 0.f, q1 = 0.f;
    const float ca = sh.act == 3 ? 0.5f : GELU_A, cb = sh.act == 3 ? 0.f : GELU_B;
#pragma unroll 1
    while (true) {
      act_block<0>(held, ca, cb, k == 1, u0, u1, s0, s1, q0, q1);
      G_STEP()
      act_block<4>(held, ca, cb, false, u0, u1, s0, s1, q0, q1);
      G_STEP()
      act_block<8>(held, ca, cb, false, u0, u1, s0, s1, q0, q1);
      G_STEP()
      act_block<12>(held, ca, cb, false, u0, u1, s0, s1, q0, q1);
      rotate16(held);
      if (k == 16) break;
      G_STEP()
    }
    if (sh.act == 2) {
      const int zi = get_item(p, 0);
      const int ln = lane_id(), row0 = (((zi >> 5) & 31) * 2 + (blockIdx.x & 1)) * 128 + c.warp * 16 + (ln >> 2), ql = ln & 3;
      const float m0 = fmaf(s0, 1.f / 64, u0), m1 = fmaf(s1, 1.f / 64, u1);
      q0 -= s0 * s0 * (1.f / 64); q1 -= s1 * s1 * (1.f / 64);
      const float mu0 = quad_sum(m0) * 0.25f, mu1 = quad_sum(m1) * 0.25f;
      q0 = quad_sum(fmaf(64.f * (m0 - mu0), m0 - mu0, q0)); q1 = quad_sum(fmaf(64.f * (m1 - mu1), m1 - mu1, q1));
      if (ql < 2) st_tagged(&g_stats[(row0 + 8 * ql) * 8 + (zi & 31)], ql ? mu1 : mu0, ql ? q1 : q0, load_tag(c));
      if (ln == 0) mbar_arrive(c.sb + OFF_BAR + B_PUB);
    }
  }
  const int s0 = sh.store == 0 ? -9 : k + (sh.store == 2 ? Z_DELAY : 1), s1 = sh.store == 3 ? -9 : s0 + 3;
#pragma unroll 1
  while (k < nsteps) {
    G_STEP()
    if (k == s0) stage_half<0>(c, held, sh.store == 2);
    else if (k == s1) stage_half<32>(c, held, sh.store == 2);
  }
  wgmma_wait<0>();
  fence_regs(acc);
  if (elected) asm volatile("mbarrier.arrive.shared::cluster.b64 _, [%0];" :: "r"(rel + 8 * ((c.g.s - 1) & 3)) : "memory");
  sh.store = sh.act == 2 ? 2 : 0;
  sh.act = 0;
}

template <bool SUB> __device__ __forceinline__ void softmax_exp(const float (&S)[64], uint32_t (&P)[32], float m0, float m1, float& s0, float& s1) {
  float a0 = 0.f, a1 = 0.f, b0 = 0.f, b1 = 0.f;
#pragma unroll
  for (int j = 0; j < 16; j++) {
    const float p0 = ex2(SUB ? S[4 * j] - m0 : S[4 * j]), p1 = ex2(SUB ? S[4 * j + 1] - m0 : S[4 * j + 1]);
    const float p2 = ex2(SUB ? S[4 * j + 2] - m1 : S[4 * j + 2]), p3 = ex2(SUB ? S[4 * j + 3] - m1 : S[4 * j + 3]);
    a0 += p0; b0 += p1; a1 += p2; b1 += p3;
    P[2 * j] = pack_bf16(p0, p1); P[2 * j + 1] = pack_bf16(p2, p3);
  }
  s0 = a0 + b0; s1 = a1 + b1;
}
__device__ __forceinline__ void row_max(const float (&S)[64], float& x0, float& x1) {
  float a0 = fmaxf(S[0], S[1]), a1 = fmaxf(S[2], S[3]);
#pragma unroll
  for (int j = 1; j < 16; j++) { a0 = fmaxf(a0, fmaxf(S[4 * j], S[4 * j + 1])); a1 = fmaxf(a1, fmaxf(S[4 * j + 2], S[4 * j + 3])); }
  x0 = quad_max(a0); x1 = quad_max(a1);
}

__device__ __forceinline__ void issue_qk(float (&S)[64], uint32_t da, uint32_t db) {
#pragma unroll
  for (int kk = 0; kk < 8; kk++) {
    const uint32_t o = (kk >> 2) * 1024 + (kk & 3) * 2;
    wgmma_m64n128k16_ss_tb0(S, DESC_HI | (da + o), DESC_HI | (db + o), kk > 0);
  }
}
template <int K0, int K1> __device__ __forceinline__ void issue_pv(float (&O)[64], const uint32_t (&P)[32], uint32_t db, int acc) {
#pragma unroll
  for (int kk = K0; kk < K1; kk++) wgmma_m64n128k16_rs_tb1(O, P[4 * kk], P[4 * kk + 1], P[4 * kk + 2], P[4 * kk + 3], DESC_HI | (db + kk * 128), (acc || kk > 0));
}

#define FA(k)
__device__ __forceinline__ void att_pack(const float (&O)[64], uint32_t (&pk)[32], float i0, float i1) {
#pragma unroll
  for (int j = 0; j < 16; j++) {
    pk[2 * j] = pack_bf16(O[4 * j] * i0, O[4 * j + 1] * i0);
    pk[2 * j + 1] = pack_bf16(O[4 * j + 2] * i1, O[4 * j + 3] * i1);
  }
}
__device__ __forceinline__ void att_stage(Cons& c, const uint32_t (&pk)[32], uint32_t qbuf) {
  stage_chunks<2>(c.sb + (qbuf ? OFF_Q1 : OFF_Q0) + c.warp * 2048, 16384, pk);
  stage_commit(c);
}

#define ATT_ISSUE(PIN, ACC)                                                        \
  if (g < 20) FT(c, 15);                                                           \
  wgmma_fence();                                                                   \
  issue_qk(S, qd, kd); wgmma_commit();                                             \
  if (g > 1) release_slot(c, vrel, true);                                          \
  vready = mbar_test(vbar, vph);                                                   \
  mbar_spin(vbar, vph);                                                            \
  wgmma_fence();                                                                   \
  issue_pv<0, 8>(O, PIN, vd, ACC); wgmma_commit();                                 \
  krel = kbar + (B_KE - B_KF); vrel = vbar + (B_KE - B_KF);                        \
  g++;                                                                             \
  if (g < total) { kd = kd0 + kv.s * (KV_SLOT >> 4); kbar = bars + B_KF + 8 * kv.s; kph = kv.ph; ring_adv<5>(kv); } \
  vd = vd0 + kv.s * (KV_SLOT >> 4); vbar = bars + B_KF + 8 * kv.s; vph = kv.ph; ring_adv<5>(kv);

#define ATT_WAIT_S()                                                               \
  wgmma_wait<1>();                                                                 \
  fence_regs(S);                                                                   \
  release_slot(c, krel, true);                                                     \
  if (c.warp == 2) asm volatile("st.volatile.shared.u32 [%0], %1;" :: "r"(bars + B_PROG), "r"(g) : "memory");

#define ATT_SOFTMAX(POUT, FIRST)                                                   \
  fresh = FIRST;                                                                   \
  _Pragma("unroll 1")                                                              \
  while (true) {                                                                   \
    if (__builtin_expect(fresh, 0)) {                                              \
      float x0, x1;                                                                \
      row_max(S, x0, x1);                                                          \
      x0 = fmaxf(x0, m0); x1 = fmaxf(x1, m1);                                      \
      zero = MZERO && (FIRST) && !__any_sync(0xffffffffu, !(fabsf(x0) <= SM_ZERO && fabsf(x1) <= SM_ZERO)); \
      if (zero) x0 = x1 = 0.f;                                                     \
      f0 = ex2(m0 - x0); f1 = ex2(m1 - x1);                                        \
      m0 = x0; m1 = x1; l0 *= f0; l1 *= f1;                                        \
    }                                                                              \
    if (MZERO && zero) { softmax_exp<false>(S, POUT, m0, m1, s0, s1); bad = !(s0 <= SM_THR_Z && s1 <= SM_THR_Z); } \
    else { softmax_exp<true>(S, POUT, m0, m1, s0, s1); bad = !(s0 <= SM_THR && s1 <= SM_THR); } \
    kready = mbar_test(kbar, kph) && vready;                                       \
    slow = fresh || __any_sync(0xffffffffu, bad || !kready);                       \
    if (__builtin_expect(!slow, 1)) break;                                         \
    if (fresh || !__any_sync(0xffffffffu, bad)) break;                             \
    fresh = true;                                                                  \
  }                                                                                \
  l0 += s0; l1 += s1;                                                              \
  wgmma_wait<0>(); fence_regs(O);

#define ATT_RESCALE()                                                              \
  { _Pragma("unroll")                                                              \
    for (int i = 0; i < 16; i++) { O[4 * i] *= f0; O[4 * i + 1] *= f0; O[4 * i + 2] *= f1; O[4 * i + 3] *= f1; } }

__device__ __forceinline__ void att_stagger(const Cons& c, int g) {
  if (c.warp >= 4)
    asm volatile("{\n.reg .pred p;\n.reg .s32 v;\nLOOP:\nld.volatile.shared.s32 v, [%0];\nsetp.le.s32 p, v, %1;\n@p bra LOOP;\n}" :: "r"(c.sb + OFF_BAR + B_PROG), "r"(g) : "memory");
}

__device__ __forceinline__ void att_run(Cons& c, int n) {
  const uint32_t bars = c.sb + OFF_BAR;
  float S[64], O[64];
  uint32_t P0[32], P1[32];
#pragma unroll
  for (int i = 0; i < 64; i++) O[i] = 0.f;
#pragma unroll
  for (int i = 0; i < 32; i++) P0[i] = P1[i] = 0u;
  fence_regs(O); fence_regs(P0); fence_regs(P1);
  float m0 = 0.f, m1 = 0.f, l0 = 0.f, l1 = 0.f, f0 = 1.f, f1 = 1.f, s0, s1, pl0 = 0.f, pl1 = 0.f;
  const int total = 16 * n;
  int g = 0;
  Ring kv = {1, 0};
  uint32_t kbar = bars + B_KF, kph = 0, vbar = bars + B_KF, vph = 0, krel, vrel = 0;
  const uint32_t kd0 = (uint32_t)make_desc(c.sb, 16, 1024), vd0 = (uint32_t)make_desc(c.sb, 16384, 1024);
  uint32_t qd = kd0 + ((OFF_Q1 + (c.warp >> 2) * 8192) >> 4), kd = kd0, vd = vd0;
  bool fresh, kready, vready, bad, slow, zero = false;
  FT(c, 16);
  mbar_spin(bars + B_QF + 8, 0);
  FT(c, 17);
  mbar_spin(bars + B_KF, 0);
  att_stagger(c, 0);
#pragma unroll 1
  while (true) {
    ATT_ISSUE(P1, 1)
    ATT_WAIT_S()
    const bool first = ((g - 1) & 15) == 0;
    if (first) { pl0 = l0; pl1 = l1; m0 = m1 = -1e38f; l0 = l1 = 0.f; }
    ATT_SOFTMAX(P0, first)
    if (__builtin_expect(slow, 0)) {
      if (first) {
        if (g > 1) {
          att_pack(O, P1, __fdividef(1.f, quad_sum(pl0)), __fdividef(1.f, quad_sum(pl1)));
          att_stage(c, P1, (g >> 4) & 1); TRACE(c.warp >> 2, c.tr + (g >> 4)); FT(c, 24);
        }
      } else if (fresh) ATT_RESCALE();
      mbar_spin(kbar, kph);
      if (__any_sync(0xffffffffu, !kready)) att_stagger(c, g);
    }
    ATT_ISSUE(P0, !first)
    ATT_WAIT_S()
    ATT_SOFTMAX(P1, false)
    if (__builtin_expect(slow || (g & 15) == 0, 0)) {
      if (fresh) ATT_RESCALE();
      if (g == total) break;
      mbar_spin(kbar, kph);
      if (__any_sync(0xffffffffu, !kready)) att_stagger(c, g);
      if ((g & 15) == 0) {
        const int t = g >> 4;
        const uint32_t qb = (t & 1) ^ 1;
        mbar_spin(bars + B_QF + 8 * qb, (t >> 1) & 1);
        qd = kd0 + (((qb ? OFF_Q1 : OFF_Q0) + (c.warp >> 2) * 8192) >> 4);
      }
    }
  }
  release_slot(c, vrel, true);
  mbar_spin(vbar, vph);
  wgmma_fence();
  issue_pv<0, 8>(O, P1, vd, 1); wgmma_commit();
  pl0 = __fdividef(1.f, quad_sum(l0)); pl1 = __fdividef(1.f, quad_sum(l1));
  wgmma_wait<0>();
  fence_regs(O);
  release_slot(c, vbar + (B_KE - B_KF), true);
  att_pack(O, P0, pl0, pl1);
  att_stage(c, P0, n & 1);
  FT(c, 24);
}

__global__ void __cluster_dims__(2, 1, 1) __launch_bounds__(384, 1) fused_kernel(const __grid_constant__ Params p) {
  const uint32_t sb = smem_base();
  const uint32_t bars = sb + OFF_BAR;
  const int tid = threadIdx.x, lane = tid & 31;
  const int warp_id = __shfl_sync(0xffffffffu, tid >> 5, 0), wg = warp_id >> 2;
  const uint32_t rank = blockIdx.x & 1;
  const uint16_t* items = p.items[blockIdx.x >> 1];
  const int gw = blockIdx.x * 8 + warp_id - 4;
  uint4 xv[2][4];
  if (wg != 0 && gw < SEQ / 2) {
#pragma unroll
    for (int rr = 0; rr < 2; rr++)
#pragma unroll
      for (int i = 0; i < 4; i++) xv[rr][i] = __ldg(reinterpret_cast<const uint4*>(p.x + (size_t)(gw * 2 + rr) * DM) + i * 32 + lane);
  }
  if (warp_id == 1 && lane < TM_COUNT) asm volatile("prefetch.tensormap [%0];" :: "l"(&p.tm[lane]) : "memory");
  if (tid == 0) {
    for (int i = 0; i < 4; i++) { mbar_init(bars + B_GF + 8 * i, 1); mbar_init(bars + B_GE + 8 * i, 4); }
    for (int i = 0; i < 5; i++) { mbar_init(bars + B_KF + 8 * i, 1); mbar_init(bars + B_KE + 8 * i, 4); }
    for (int i = 0; i < 2; i++) { mbar_init(bars + B_QF + 8 * i, 1); mbar_init(bars + B_QE + 8 * i, 1); }
    mbar_init(bars + B_XF, 2); mbar_init(bars + B_XR, 2); mbar_init(bars + B_STG, 8); mbar_init(bars + B_FREE, 1); mbar_init(bars + B_GO, 1); mbar_init(bars + B_LN, 2); mbar_init(bars + B_PUB, 8);
    asm volatile("fence.mbarrier_init.release.cluster;" ::: "memory");
  }
  asm volatile("barrier.cluster.arrive.relaxed.aligned;" ::: "memory");

  if (wg == 0) {
    asm volatile("setmaxnreg.dec.sync.aligned.u32 40;");
    asm volatile("barrier.cluster.wait.acquire.aligned;" ::: "memory");
    if (warp_id >= 2 && (items[0] >> 12) == T_Z2) {
      if (lane == 0) mbar_wait_sleep(bars + B_PUB, 0, 200);
      __syncwarp();
      uint32_t tag;
      asm volatile("ld.volatile.shared.u32 %0, [%1];" : "=r"(tag) : "r"(bars + B_TAG));
#pragma unroll 1
      for (int r = (warp_id - 2) * 64 + lane; r < (warp_id - 1) * 64; r += 32) {
        const uint4* ps = &g_stats[((((items[0] >> 5) & 31) * 2 + rank) * 128 + r) * 8];
        float2 t[7];
        uint32_t cnt = 0;
        while (true) {
          bool ok = true;
#pragma unroll
          for (int i = 0; i < 7; i++) ok = ld_tagged(ps + i, t[i].x, t[i].y, tag) && ok;
          if (__all_sync(0xffffffffu, ok)) break;
          trap_if(++cnt > SPIN_LIMIT);
          __nanosleep(100);
        }
        float u = 0.f, v = 0.f;
#pragma unroll
        for (int i = 0; i < 7; i++) u += t[i].x;
        u *= 1.f / 7;
#pragma unroll
        for (int i = 0; i < 7; i++) v += fmaf(256.f * (t[i].x - u), t[i].x - u, t[i].y);
        const float rs = rsqrtf(fmaxf(v, 0.f) * (1.f / FH) + 4e-5f);
        asm volatile("st.shared.v2.b32 [%0], {%1, %2};" :: "r"(sb + OFF_LN + r * 8), "r"(pack_bf16(rs, rs)), "r"(pack_bf16(-u, -u)) : "memory");
      }
      __syncwarp();
      if (lane == 0) mbar_arrive(bars + B_LN);
      __syncwarp();
    }
    if (warp_id == 0) {
      trap_if(sb & 1023);
      Ring g = {0, 1};
      int it = 0;
      uint32_t xph = 0;
      if (elect_one()) {
#pragma unroll 1
        for (;; it++) {
          const int item = items[it], type = item >> 12, b = item & 31, row = (((item >> 5) & 31) * 2 + rank) * 128;
          if (type >= T_ATT) break;
#pragma unroll 1
          for (int seg = 0; seg < (type == T_U ? 2 : 1); seg++) {
            const CUtensorMap* tA = &p.tm[seg ? TM_WSP : TM_XN];
            const CUtensorMap* tB = &p.tm[seg ? TM_Z2 : (type == T_Q ? TM_WQ : TM_WIN)];
            const int bchunk = b * 4 + (type == T_Z2 ? 28 : 0) + rank * 2;
            const unsigned* fl = seg ? &g_flags[F_Z2 + b * 32] : &g_flags[F_XN + (row >> 2)];
            const unsigned tgt = seg ? 16 : 128;
            int k = 0;
            if (it == 0 && seg == 0) {
              for (; k < 4; k++) {
                mbar_expect_tx(bars + B_GF + 8 * k, G_STAGE);
                tma_load_3d_mc(sb + k * G_STAGE + G_A + rank * 16384, tB, k * 64, bchunk, bars + B_GF + 8 * k);
              }
              g.ph ^= 1;
              asm volatile("st.volatile.shared.v4.u32 [%0], {%1, %2, %2, %2};" :: "r"(bars + B_TAG), "r"(__ldcg(&g_epoch) + 1), "r"(0) : "memory");
            }
            if (seg || type != T_U) { flag_wait(fl, tgt); fence_async_global(); }
            for (int x = 0; x < k; x++) tma_load_2d(sb + x * G_STAGE, tA, x * 64, row, bars + B_GF + 8 * x);
#pragma unroll 1
            for (; k < (seg ? 32 : 16); k++) {
              if (k == 3 && type == T_U && seg == 0) { mbar_wait(bars + B_XF, xph); xph ^= 1; }
              mbar_wait(bars + B_GE + 8 * g.s, g.ph);
              const uint32_t st = sb + g.s * G_STAGE, fb = bars + B_GF + 8 * g.s;
              mbar_expect_tx(fb, G_STAGE);
              tma_load_2d(st, tA, k * 64, row, fb);
              tma_load_3d_mc(st + G_A + rank * 16384, tB, k * 64, bchunk, fb);
              ring_adv<4>(g);
            }
          }
        }
      }
      it = __shfl_sync(0xffffffffu, it, 0); g.ph = __shfl_sync(0xffffffffu, g.ph, 0);
      const int n = ((items[it] >> 10) & 3) + 2;
      Ring kv = {0, 1};
      if (elect_one()) {
        const uint64_t pol = policy_evict_normal(), polq = pol;
        int prow = 0;
#pragma unroll 1
        for (int x = -1; x <= 32 * n; x++) {
          const int gb = x >> 1, t = x < 0 ? 0 : gb >> 4;
          const int hrow = ((items[it + t] >> 5) & 31) * SEQ;
          const bool isv = (x & 1) || x == 32 * n;
          if (x >= 0 && x != 1) {
            if (x == 4) { mbar_wait(bars + B_XF, xph); xph ^= 1; }
            mbar_wait(bars + B_KE + 8 * kv.s, kv.ph);
            mbar_expect_tx(bars + B_KF + 8 * kv.s, KV_SLOT);
            tma_load_2d_mc_hint(sb + kv.s * KV_SLOT + rank * 16384, &p.tm[isv ? TM_V : TM_K], rank * 64, isv ? prow : hrow + (gb & 15) * 128,
                                bars + B_KF + 8 * kv.s, pol);
            ring_adv<5>(kv);
          }
          if (KV_PF > 0 && x >= 0) {
            const int gp = gb + KV_PF, ip = items[it + (gp >> 4)];
            if (gp < 16 * n && (KV_ALL || ((gp ^ ip) & 7) == 0)) tma_prefetch_2d(&p.tm[(x & 1) ? TM_V : TM_K], rank * 64, ((ip >> 5) & 31) * SEQ + (gp & 15) * 128);
          }
          if (x == 32 * n - 8) mbar_arrive(bars + B_GO);
          if (x & 1) prow = hrow + (gb & 15) * 128;
          if (x < 0 || ((x & 31) == 11 && t + 1 < n)) {
            const int tq = x < 0 ? 0 : t + 1;
            const int im = items[it + tq], h = (im >> 5) & 31, m = (im & 31) * 2 + rank;
            const uint32_t qb = (tq & 1) ^ 1;
            flag_wait(&g_flags[F_Q + m * 16 + (h >> 1)], 1);
            fence_async_global();
            if (x < 0) {
              if (KV_PF0 < 0) { const int y = (im & 7) >> 1; tma_prefetch_2d(&p.tm[(im & 1) ? TM_V : TM_K], rank * 64, hrow + y * 128); }
              for (int y = 0; y < KV_PF0; y++) { tma_prefetch_2d(&p.tm[TM_K], rank * 64, hrow + y * 128); tma_prefetch_2d(&p.tm[TM_V], rank * 64, hrow + y * 128); }
              tma_prefetch_2d(&p.tm[TM_Q], h * 128, m * 128); tma_prefetch_2d(&p.tm[TM_Q], h * 128 + 64, m * 128);
              for (int i = 0; i < 4; i++) mbar_wait(bars + B_GE + 8 * i, g.ph);
            }
            mbar_wait(bars + B_QE + 8 * qb, ((tq >> 1) & 1) ^ qb);
            const uint32_t dst = sb + (qb ? OFF_Q1 : OFF_Q0), fb = bars + B_QF + 8 * qb;
            mbar_expect_tx(fb, 32768);
            tma_load_2d_hint(dst, &p.tm[TM_Q], h * 128, m * 128, fb, polq);
            tma_load_2d_hint(dst + 16384, &p.tm[TM_Q], h * 128 + 64, m * 128, fb, polq);
          }
        }
      }
      __syncwarp();
      it += n;
      uint32_t ready = 0;
      auto wait_head = [&](int h) {
        if ((ready >> h) & 1) return;
        uint32_t cnt = 0;
        while (true) {
          asm volatile("ld.acquire.cta.shared.u32 %0, [%1];" : "=r"(ready) : "r"(bars + B_RDY) : "memory");
          if ((ready >> h) & 1) break;
          trap_if(++cnt > SPIN_LIMIT * 8);
          __nanosleep(20);
        }
        fence_async_global();
      };
      int item = items[it];
      if ((item >> 12) == T_SA) {
        const int m = ((item >> 5) & 31) * 2 + rank, b = item & 31;
        if (lane == 0) flag_wait(&g_flags[F_U + m * 32], 7);
        __syncwarp();
        fence_async_global();
#pragma unroll 1
        for (int i = -OUT_PF; i < 28 + 2 * SA_HEADS; i++) {
          if (i >= 0) {
            const bool so = i >= 28;
            const int k = so ? i - 28 : i;
            if (so) wait_head(k >> 1);
            if (elect_one()) {
              if (i == 0) { Ring h = kv; for (int x = 0; x < 5; x++) { mbar_wait(bars + B_KE + 8 * h.s, h.ph); ring_adv<5>(h); } }
              if (i == 3) { mbar_wait(bars + B_XF, xph); xph ^= 1; }
              mbar_wait(bars + B_GE + 8 * g.s, g.ph);
              const uint32_t st = sb + g.s * G_STAGE, fb = bars + B_GF + 8 * g.s;
              mbar_expect_tx(fb, G_STAGE);
              tma_load_2d(st, &p.tm[so ? TM_O : TM_U], k * 64, m * 128, fb);
              tma_load_3d_mc(st + G_A + rank * 16384, &p.tm[so ? TM_WO : TM_WOUT], k * 64, b * 4 + rank * 2, fb);
            }
            ring_adv<4>(g);
          }
          const int ip = i + OUT_PF;
          if (ip < 28 + 2 * SA_HEADS && elect_one()) {
            const bool so = ip >= 28;
            const int k = so ? ip - 28 : ip;
            if ((ip & 3) == b && (!so || ((ready >> (k >> 1)) & 1))) tma_prefetch_2d(&p.tm[so ? TM_O : TM_U], k * 64, m * 128);
            if ((ip & 7) == (m >> 1)) tma_prefetch_3d(&p.tm[so ? TM_WO : TM_WOUT], k * 64, b * 4 + rank * 2);
          }
          __syncwarp();
        }
        item = items[++it];
      }
      if ((item >> 12) == T_FIN) {
        const bool own = item & 4;
        const int m = ((item >> 5) & 31) * 2 + rank, col = (item & 3) * 256 + (own ? 128 : 0);
#pragma unroll 1
        for (int k = 2 * SA_HEADS; k < 2 * NH + (own ? 0 : 1); k++) {
          if (k < 2 * NH) wait_head(k >> 1);
          if (elect_one()) {
            if (k == 2 * SA_HEADS) {
              for (int y = k; y < k + 4; y++) if ((ready >> (y >> 1)) & 1) tma_prefetch_2d(&p.tm[TM_O], y * 64, m * 128);
              for (int x = 0; x < 4; x++) { mbar_wait(bars + B_GE + 8 * g.s, g.ph); ring_adv<4>(g); }
            }
            if (k == 2 * NH) { flag_wait(&g_flags[F_S + m * 4 + (item & 3)], 2); fence_async_global(); }
            mbar_wait(bars + B_KE + 8 * kv.s, kv.ph);
            const uint32_t dst = sb + kv.s * KV_SLOT, fb = bars + B_KF + 8 * kv.s;
            mbar_expect_tx(fb, KV_SLOT);
            if (k < 2 * NH) {
              tma_load_2d(dst, &p.tm[TM_O], k * 64, m * 128, fb);
              tma_load_2d_mc(dst + 16384 + rank * 8192, &p.tm[TM_WO64], col + rank * 64, k * 64, fb);
            } else {
              tma_load_2d(dst, &p.tm[TM_SA], col, m * 128, fb);
              tma_load_2d(dst + 16384, &p.tm[TM_SA], col + 64, m * 128, fb);
            }
            ring_adv<5>(kv);
          }
          __syncwarp();
        }
      }
      unsigned last = 0;
      if (lane == 0 && (item >> 12) == T_FIN) mbar_wait_long(bars + B_XR, 0);
      if (lane == 0) { __threadfence(); last = atomicInc(&g_done, gridDim.x - 1) == gridDim.x - 1; }
      last = __shfl_sync(0xffffffffu, last, 0);
      if (last) {
        for (int i = lane; i < F_TOTAL / 4; i += 32) reinterpret_cast<uint4*>(g_flags)[i] = make_uint4(0, 0, 0, 0);
        if (lane == 0) g_epoch = g_epoch + 1;
      }
    } else if (warp_id == 1) {
      if (elect_one()) {
        uint32_t ph = 0;
        int t = 0;
        unsigned* fq = nullptr;
        const bool z = (items[0] >> 12) == T_Z2;
#pragma unroll 1
        for (int it = 0;; it++) {
          const int ii = (z && it < 2) ? it ^ 1 : it;
          const int item = items[ii], type = item >> 12, a = (item >> 5) & 31, b = item & 31;
          if (type == T_END) break;
          const int nt = items[ii + 1] >> 12;
          int row = (a * 2 + rank) * 128, col = b * 256;
          unsigned* f = &g_flags[F_S + (a * 2 + rank) * 4 + b];
          int tm = TS_G, npair = 2;
          bool quad = false;
          uint32_t src = sb + OFF_Q0;
          if (type == T_Z2) { tm = TS_Z2; f = &g_flags[F_Z2 + b * 32]; }
          else if (type == T_Q) { tm = TS_Q; f = &g_flags[F_Q + (a * 2 + rank) * 16 + b]; if (z || nt >= T_ATT) { npair = 0; quad = true; } }
          else if (type == T_U) { tm = TS_U; f = &g_flags[F_U + (a * 2 + rank) * 32]; npair = 0; quad = true; }
          else if (type == T_ATT) { tm = TS_O; f = &g_flags[F_O + (b * 2 + rank) * 32 + a]; npair = 1; row = (b * 2 + rank) * 128; col = a * 128; if (!(t & 1)) src = sb + OFF_Q1; }
          else if (type == T_FIN) npair = 1;
          auto load_fin = [&](int fi, int tmi, uint32_t qb) {
            const int fc = (fi & 3) * 256 + ((fi & 4) ? 128 : 0), fr = (((fi >> 5) & 31) * 2 + rank) * 128;
            mbar_expect_tx(bars + B_QF + 8 * qb, 32768);
            tma_load_2d(sb + (qb ? OFF_Q1 : OFF_Q0), &p.tm[tmi], fc, fr, bars + B_QF + 8 * qb);
            tma_load_2d(sb + (qb ? OFF_Q1 : OFF_Q0) + 16384, &p.tm[tmi], fc + 64, fr, bars + B_QF + 8 * qb);
          };
          if (type == T_ATT && nt == T_FIN) load_fin(items[ii + 1], TM_X, t & 1);
          if (type == T_FIN) {
            if (!(item & 4)) { flag_wait(&g_flags[F_S + (a * 2 + rank) * 4 + (b & 3)], 1); fence_async_global(); load_fin(item, TM_G, t & 1); }
            mbar_arrive(bars + B_XR);
          }
#pragma unroll 1
          for (int op = 0; op < npair + quad; op++) {
            const bool q = op == npair;
            const int c0 = (q || type == T_SA) ? col : col + op * 128;
            mbar_wait_sleep(bars + B_STG, ph, (type == T_ATT && nt == T_ATT) ? SW_ATT : SW_NS);
            if (type == T_FIN) break;
            ph ^= 1;
            fence_async_smem();
            if (type == T_SA && op == 1) { tm = TS_SA; load_fin(items[ii + 1], TM_X, 1); }
            if (q) {
              const CUtensorMap* tb = &p.tm[type == T_U ? TM_U : TM_Q];
              tma_store_2d(tb, sb + (nt == T_U ? OFF_Q1 : 2 * G_STAGE), c0 + 128, row);
              tma_store_2d(tb, sb + (nt == T_U ? OFF_Q1 + 16384 : 3 * G_STAGE), c0 + 192, row);
              bulk_commit();
              bulk_wait_read<0>();
              mbar_arrive_cta(bars + B_XF, 0); mbar_arrive_cta(bars + B_XF, 1);
            }
#pragma unroll 1
            for (int r = 0; r < 256; r += ST_ROWS) {
              tma_store_2d(&p.tm[tm], src + r * 128, c0 + (r >> 7) * 64, row + (r & 127));
              bulk_commit();
              if (nt != T_END) bulk_wait_read<ST_FLY>();
            }
            bulk_wait_read<0>();
            mbar_arrive(bars + B_FREE);
            if (type == T_ATT && nt == T_SA) { mbar_arrive_cta(bars + B_XF, 0); mbar_arrive_cta(bars + B_XF, 1); }
            if (type == T_ATT) mbar_arrive(bars + B_QE + ((t & 1) ? 0 : 8));
            else if (nt == T_ATT) mbar_arrive(bars + B_QE);
            if (z && it == 0) { fq = f; continue; }
            if (op + 1 >= npair || type == T_SA) {
              bulk_wait<0>();
              red_release(f, 1);
              if (type == T_Z2) red_release(fq, 1);
            }
          }
          if (type == T_ATT) t++;
        }
      }
      __syncwarp();
    } else if (warp_id == 2) {
      int it = 0;
      while ((items[it] >> 12) <= T_ATT) it++;
      if ((items[it] >> 12) != T_END) {
        const bool sa = (items[it] >> 12) == T_SA;
        const int m = ((items[it] >> 5) & 31) * 2 + rank;
        if (lane == 0) {
          mbar_wait_sleep(bars + B_GO, 0, 1000);
          if (!sa) for (int y = (blockIdx.x & 63); y < 16 * (NH - SA_HEADS); y += 64) tma_prefetch_3d(&p.tm[TM_WO], (2 * SA_HEADS + (y >> 3)) * 64, (y & 7) * 2);
        }
        __syncwarp();
        uint32_t cnt = 0;
        while (true) {
          const uint32_t r = __ballot_sync(0xffffffffu, ld_acquire(&g_flags[F_O + m * 32 + lane]) != 0);
          if (lane == 0) asm volatile("st.release.cta.shared.u32 [%0], %1;" :: "r"(bars + B_RDY), "r"(r) : "memory");
          if (r == ~0u) break;
          trap_if(++cnt > SPIN_LIMIT);
          __nanosleep(r >> 28 ? 20 : 300);
        }
        if (lane == 0) mbar_arrive(bars + B_XR);
      }
      __syncwarp();
    }
    cluster_sync_relaxed();
  } else {
    Cons c;
    c.sb = sb; c.warp = warp_id - 4; c.g = {0, 0}; c.fph = 1;
    TRACE(c.warp >> 2, 0);
    FT(c, 1);
    if (gw < SEQ / 2) {
      float f[2][32], rs[2];
#pragma unroll
      for (int rr = 0; rr < 2; rr++) {
#pragma unroll
        for (int i = 0; i < 4; i++) {
          const uint4 v = xv[rr][i];
          f[rr][8 * i + 0] = bf_lo(v.x); f[rr][8 * i + 1] = bf_hi(v.x); f[rr][8 * i + 2] = bf_lo(v.y); f[rr][8 * i + 3] = bf_hi(v.y);
          f[rr][8 * i + 4] = bf_lo(v.z); f[rr][8 * i + 5] = bf_hi(v.z); f[rr][8 * i + 6] = bf_lo(v.w); f[rr][8 * i + 7] = bf_hi(v.w);
        }
        float s = 0.f;
#pragma unroll
        for (int i = 0; i < 32; i++) s += f[rr][i];
#pragma unroll
        for (int o = 16; o; o >>= 1) s += __shfl_xor_sync(0xffffffffu, s, o);
        const float mean = s * (1.f / DM);
        float q = 0.f;
#pragma unroll
        for (int i = 0; i < 32; i++) { f[rr][i] -= mean; q = fmaf(f[rr][i], f[rr][i], q); }
#pragma unroll
        for (int o = 16; o; o >>= 1) q += __shfl_xor_sync(0xffffffffu, q, o);
        rs[rr] = rsqrtf(q * (1.f / DM) + 1e-5f);
      }
      uint4* dst = reinterpret_cast<uint4*>(g_xn + (size_t)gw * 2 * DM) + lane;
#pragma unroll
      for (int rr = 0; rr < 2; rr++) {
        const float r = rs[rr];
#pragma unroll
        for (int i = 0; i < 4; i++) {
          const float* y = &f[rr][8 * i];
          dst[rr * 128 + i * 32] = make_uint4(pack_bf16(y[0] * r, y[1] * r), pack_bf16(y[2] * r, y[3] * r), pack_bf16(y[4] * r, y[5] * r), pack_bf16(y[6] * r, y[7] * r));
        }
      }
      __syncwarp();
      if (lane == 0) red_release(&g_flags[F_XN + (gw >> 6) * 32], 2);
    }
    asm volatile("setmaxnreg.inc.sync.aligned.u32 232;");
    asm volatile("barrier.cluster.wait.acquire.aligned;" ::: "memory");
#define stg (c.sb + OFF_Q0 + c.warp * 2048)
    int natt = 0;
    int it = 0;
    uint32_t held[64];
#pragma unroll
    for (int i = 0; i < 64; i++) held[i] = 0u;
    Shadow sh = {0, 0};
    float facc[64];
#pragma unroll 1
    while (true) {
      const int item = get_item(p, it), type = item >> 12, a = (item >> 5) & 31;
      c.warp = fresh_warp();
      TRACE(c.warp >> 2, 1 + it);
      FT(c, 2);
      if (type == T_ATT) {
        const int n = ((item >> 10) & 3) + 2;
        att_run(c, n);
#pragma unroll
        for (int i = 0; i < 64; i++) held[i] = 0u;
        natt = n;
        it += n;
        if ((get_item(p, it) >> 12) == T_SA) continue;
#pragma unroll
        for (int i = 0; i < 64; i++) facc[i] = 0.f;
        break;
      }
      float acc[128];
      const bool sa = type == T_SA;
      bool more = type >= T_U;
      int nsteps = sa ? 28 : 16;
      const bool direct = sh.act == 2 || (get_item(p, it + 1) >> 12) >= T_ATT;
      uint32_t bias0 = 0, bias1 = 0;
#pragma unroll 1
      while (true) {
        gemm_seg(acc, held, c, p, sh, nsteps);
        if (type == T_Q) {
#pragma unroll
          for (int i = 0; i < 128; i++) acc[i] *= SM_C;
        }
        if (!more && direct) break;
#pragma unroll
        for (int i = 0; i < 64; i++) held[i] = pack_bf16(acc[2 * i], acc[2 * i + 1]);
        if (!more) break;
        more = false;
        nsteps = sa ? 2 * SA_HEADS : 32;
        sh.act = sa ? 3 : 1;
        if (sa) {
          sh.store = 3;
        } else {
          const int row0 = (a * 2 + rank) * 128 + c.warp * 16 + (lane_id() >> 2);
          asm volatile("ld.global.nc.u16 %0, [%1];" : "=r"(bias0) : "l"(p.b_sp + row0));
          asm volatile("ld.global.nc.u16 %0, [%1];" : "=r"(bias1) : "l"(p.b_sp + row0 + 8));
        }
      }
      TRACE(c.warp >> 2, 32 + it);
      FT(c, 3);
      c.warp = fresh_warp();
      if (direct) {
        const bool zq = sh.store == 2;
        const uint32_t hb0 = bf2_mul(bias0 * 0x10001u, BF2_HALF), hb1 = bf2_mul(bias1 * 0x10001u, BF2_HALF);
        stage_acquire(c);
#pragma unroll
        for (int h = 0; h < 2; h++) {
          uint32_t pk[32];
#pragma unroll
          for (int i = 0; i < 32; i++) pk[i] = pack_bf16(acc[64 * h + 2 * i], acc[64 * h + 2 * i + 1]);
          if (type == T_U) {
#pragma unroll
            for (int i = 0; i < 32; i++) pk[i] = bf2_mul(bf2_fma(pk[i], BF2_HALF, (i & 1) ? hb1 : hb0), held[32 * h + i]);
          }
          if (h && zq) named_sync(5);
          stage_chunks<2>(h ? sb + (zq ? OFF_Q1 : 2 * G_STAGE) + c.warp * 2048 : stg, (h && !zq) ? G_STAGE : 16384, pk);
          if (sa) break;
        }
        stage_commit(c);
        if (sa) {
#pragma unroll
          for (int i = 0; i < 64; i++) facc[i] = acc[64 + i];
          it++;
          break;
        }
      } else if (type == T_Q) {
        sh.store = 1;
      } else {
        sh.act = 2;
      }
      it++;
    }
    const int fin = get_item(p, it);
    if ((fin >> 12) == T_FIN) {
      c.warp = fresh_warp();
      TRACE(c.warp >> 2, 1 + it);
      FT(c, 2);
      const bool own = fin & 4;
      Ring kv = {(uint32_t)(32 * natt) % 5, ((uint32_t)(32 * natt) / 5) & 1};
      uint32_t prev = 0;
      fence_regs(facc);
#pragma unroll 1
      for (int k = 2 * SA_HEADS; k < 2 * NH; k++) {
        mbar_spin(bars + B_KF + 8 * kv.s, kv.ph);
        const uint32_t st = ((c.sb & 0x3FFFF) >> 4) + kv.s * (KV_SLOT >> 4);
        const uint32_t da = st + (c.warp >> 2) * 512 + (1u << 16), db = st + 1024 + ((8192u >> 4) << 16);
        wgmma_fence();
#pragma unroll
        for (int kk = 0; kk < 4; kk++) wgmma_m64n128k16_ss_tb1(facc, DESC_HI | (da + kk * 2), DESC_HI | (db + kk * 128), 1);
        wgmma_commit();
        FT(c, 70);
        wgmma_wait<1>();
        if (k > 2 * SA_HEADS) release_slot(c, prev, true);
        prev = bars + B_KE + 8 * kv.s;
        ring_adv<5>(kv);
      }
      const uint32_t ln = lane_id(), xb = own ? 1 : (natt - 1) & 1;
      const uint32_t lo = c.warp * 2048 + ((ln & 15) << 7);
      uint32_t xs[32], ss[32];
      auto load_tile = [&](uint32_t base, uint32_t* d) {
#pragma unroll
        for (int i = 0; i < 8; i++) ldmatrix_x4(base + lo + (i >> 2) * 16384 + (((2 * (i & 3) + (ln >> 4)) ^ (ln & 7)) << 4), d[4 * i], d[4 * i + 1], d[4 * i + 2], d[4 * i + 3]);
      };
      const uint32_t xa = sb + (xb ? OFF_Q1 : OFF_Q0);
      mbar_spin(bars + B_QF + 8 * xb, ((natt + xb) >> 1) & 1);
      load_tile(xa, xs);
#pragma unroll
      for (int i = 0; i < 32; i++) ss[i] = 0u;
      if (!own) {
        mbar_spin(bars + B_QF + 8 * (xb ^ 1), ((natt + (xb ^ 1)) >> 1) & 1);
        load_tile(sb + (xb ? OFF_Q0 : OFF_Q1), held + 32);
        mbar_spin(bars + B_KF + 8 * kv.s, kv.ph);
        load_tile(sb + kv.s * KV_SLOT, ss);
      }
      wgmma_wait<0>();
      fence_regs(facc);
      TRACE(c.warp >> 2, 32 + it);
      FT(c, 3);
#pragma unroll
      for (int i = 0; i < 32; i++)
        xs[i] = bf2_fma(bf2_mul(pack_bf16(facc[2 * i] + bf_lo(ss[i]), facc[2 * i + 1] + bf_hi(ss[i])), held[32 + i]), BF2_HALF, xs[i]);
      __syncwarp();
      stage_chunks<2>(xa + c.warp * 2048, 16384, xs);
      fence_async_smem();
      __syncwarp();
      if (elect_one()) {
        const int col = (fin & 3) * 256 + (own ? 128 : 0), row = (((fin >> 5) & 31) * 2 + rank) * 128 + c.warp * 16;
        tma_store_2d(&p.tm[TS_OUT], xa + c.warp * 2048, col, row);
        tma_store_2d(&p.tm[TS_OUT], xa + c.warp * 2048 + 16384, col + 64, row);
        bulk_commit();
        mbar_arrive(bars + B_STG);
        bulk_wait_read<0>();
      }
    }
    FT(c, 63);
    FT(c, 0);
    TRACE(c.warp >> 2, 31);
    __syncwarp();
    cluster_sync_relaxed();
  }
}

typedef CUresult (*PFN_encodeTiled)(CUtensorMap*, CUtensorMapDataType, cuuint32_t, void*, const cuuint64_t*, const cuuint64_t*, const cuuint32_t*, const cuuint32_t*,
                                    CUtensorMapInterleave, CUtensorMapSwizzle, CUtensorMapL2promotion, CUtensorMapFloatOOBfill);
static PFN_encodeTiled s_encode = nullptr;
static void tm_2d(CUtensorMap* tm, const void* ptr, uint64_t rows, uint64_t cols, uint32_t box_rows) {
  cuuint64_t dims[2] = {cols, rows}; cuuint64_t strides[1] = {cols * 2}; cuuint32_t box[2] = {64, box_rows}; cuuint32_t es[2] = {1, 1};
  CUresult r = s_encode(tm, CU_TENSOR_MAP_DATA_TYPE_BFLOAT16, 2, (void*)ptr, dims, strides, box, es, CU_TENSOR_MAP_INTERLEAVE_NONE,
                        CU_TENSOR_MAP_SWIZZLE_128B, CU_TENSOR_MAP_L2_PROMOTION_L2_256B, CU_TENSOR_MAP_FLOAT_OOB_FILL_NONE);
  if (r != CUDA_SUCCESS) fprintf(stderr, "tensor map encode failed (%d)\n", (int)r);
}
static void tm_3d(CUtensorMap* tm, const void* ptr, uint64_t rows, uint64_t cols) {
  cuuint64_t dims[3] = {64, rows, cols / 64}; cuuint64_t strides[2] = {cols * 2, 128}; cuuint32_t box[3] = {64, 64, 2}; cuuint32_t es[3] = {1, 1, 1};
  CUresult r = s_encode(tm, CU_TENSOR_MAP_DATA_TYPE_BFLOAT16, 3, (void*)ptr, dims, strides, box, es, CU_TENSOR_MAP_INTERLEAVE_NONE,
                        CU_TENSOR_MAP_SWIZZLE_128B, CU_TENSOR_MAP_L2_PROMOTION_L2_256B, CU_TENSOR_MAP_FLOAT_OOB_FILL_NONE);
  if (r != CUDA_SUCCESS) fprintf(stderr, "tensor map encode failed (%d)\n", (int)r);
}
static inline uint16_t mk(int type, int a, int b) { return (uint16_t)(type << 12 | a << 5 | b); }

static void build_schedule(Params& P) {
  int cnt[NCLUSTER];
  for (int c = 0; c < NCLUSTER; c++) { cnt[c] = 0; for (int i = 0; i < MAXI; i++) P.items[c][i] = mk(T_END, 0, 0); }
  auto push = [&](int c, uint16_t v) { P.items[c][cnt[c]++] = v; };
  int natt[NCLUSTER], nq[NCLUSTER];
  for (int c = 0; c < NCLUSTER; c++) { natt[c] = c < 32 ? 3 : (c < 56 ? 5 : (c < 62 ? 4 : (c < 64 ? 3 : 5))); nq[c] = c < 56 ? 1 : (c < 62 ? 7 : (c < 64 ? 9 : 6)); }
  for (int c = 0; c < 56; c++) push(c, mk(T_Z2, c % 8, c / 8));
  int qi = 0;
  for (int slot = 0; slot < 9; slot++)
    for (int c = NCLUSTER - 1; c >= 0; c--) {
      const int first = c < 56 ? 1 : 0;
      if (slot >= first && slot < first + nq[c]) { push(c, mk(T_Q, qi % 8, qi / 8)); qi++; }
    }
  for (int c = 0; c < 56; c++) push(c, mk(T_U, c % 8, c / 8));
  int ai = 0;
  for (int slot = 0; slot < 5; slot++)
    for (int c = 0; c < NCLUSTER; c++) {
      const int first = c < 32 ? 0 : 5 - natt[c];
      if (slot >= first && slot < first + natt[c]) { push(c, mk(T_ATT, ai / 8, ai % 8) | (natt[c] - 2) << 10); ai++; }
    }
  for (int c = 0; c < 32; c++) push(c, mk(T_SA, c % 8, c / 8));
  for (int c = 0; c < 64; c++) push(c, mk(T_FIN, c % 8, (c / 8) % 4 | (c < 32 ? 4 : 0)));
  if (qi != 128 || ai != 256) fprintf(stderr, "bad schedule %d %d\n", qi, ai);
}

static Params s_params;
extern "C" void kernel_launch(void* const* d_in, const int* in_sizes, int n_in, void* d_out, int out_size) {
  (void)in_sizes; (void)n_in; (void)out_size;
  if (!s_encode) {
    void* fn = nullptr; cudaDriverEntryPointQueryResult qr;
    cudaGetDriverEntryPoint("cuTensorMapEncodeTiled", &fn, cudaEnableDefault, &qr);
    s_encode = (PFN_encodeTiled)fn;
    cudaFuncSetAttribute(fused_kernel, cudaFuncAttributeMaxDynamicSharedMemorySize, SMEM_BYTES);
    build_schedule(s_params);
  }
  Params& P = s_params;
  void *xn, *q, *o, *z2, *u, *gg, *sa;
  cudaGetSymbolAddress(&gg, g_g); cudaGetSymbolAddress(&sa, g_sa);
  cudaGetSymbolAddress(&xn, g_xn); cudaGetSymbolAddress(&q, g_q); cudaGetSymbolAddress(&o, g_o);
  cudaGetSymbolAddress(&z2, g_z2); cudaGetSymbolAddress(&u, g_u);
  tm_2d(&P.tm[TM_XN], xn, SEQ, DM, 128); tm_2d(&P.tm[TM_WSP], d_in[7], SEQ, SEQ, 128); tm_2d(&P.tm[TM_U], u, SEQ, FH, 128);
  tm_2d(&P.tm[TM_O], o, SEQ, HD, 128); tm_2d(&P.tm[TM_Q], q, SEQ, HD, 128); tm_2d(&P.tm[TM_X], d_in[0], SEQ, DM, 128);
  tm_2d(&P.tm[TM_K], d_in[1], NH * SEQ, 128, 128); tm_2d(&P.tm[TM_V], d_in[2], NH * SEQ, 128, 128);
  tm_2d(&P.tm[TM_SA], sa, SEQ, DM, 128); tm_2d(&P.tm[TM_G], gg, SEQ, DM, 128); tm_2d(&P.tm[TM_WO64], d_in[4], HD, DM, 64);
  tm_3d(&P.tm[TM_WIN], d_in[6], DM, FF); tm_3d(&P.tm[TM_WQ], d_in[3], DM, HD); tm_3d(&P.tm[TM_Z2], z2, SEQ, FH);
  tm_3d(&P.tm[TM_WOUT], d_in[9], FH, DM); tm_3d(&P.tm[TM_WO], d_in[4], HD, DM);
  tm_2d(&P.tm[TS_Q], q, SEQ, HD, ST_ROWS); tm_2d(&P.tm[TS_O], o, SEQ, HD, ST_ROWS); tm_2d(&P.tm[TS_Z2], z2, SEQ, FH, ST_ROWS); tm_2d(&P.tm[TS_U], u, SEQ, FH, ST_ROWS);
  tm_2d(&P.tm[TS_SA], sa, SEQ, DM, ST_ROWS); tm_2d(&P.tm[TS_G], gg, SEQ, DM, ST_ROWS); tm_2d(&P.tm[TS_OUT], d_out, SEQ, DM, 16);
  P.x = (const bf16*)d_in[0]; P.b_sp = (const bf16*)d_in[8];
  fused_kernel<<<2 * NCLUSTER, 384, SMEM_BYTES, cudaStreamPerThread>>>(P);
}
```

```cpp
#include <cuda_runtime.h>
#include <cuda_bf16.h>
#include <cuda.h>
#include <stdint.h>
#include <stdio.h>

typedef __nv_bfloat16 bf16;

constexpr int SEQ = 2048, DM = 1024, NH = 32, HD = 4096, FF = 3584, FH = 1792;

__device__ __align__(1024) bf16 g_xn[SEQ * DM];
__device__ __align__(1024) bf16 g_q[SEQ * HD];
__device__ __align__(1024) bf16 g_o[SEQ * HD];
__device__ __align__(1024) bf16 g_z2[SEQ * FH];
__device__ __align__(1024) bf16 g_u[SEQ * FH];
__device__ __align__(1024) uint2 g_stats[SEQ * 8];
__device__ __align__(1024) bf16 g_g[SEQ * DM];
__device__ __align__(1024) bf16 g_sa[SEQ * DM];
constexpr int F_XN = 0;
constexpr int F_Z2 = 512;
constexpr int F_Q = 768;
constexpr int F_U = 1024;
constexpr int F_O = 1536;
constexpr int F_S = 2048;
constexpr int F_TOTAL = 2112;
__device__ __align__(1024) unsigned g_flags[F_TOTAL];
__device__ unsigned g_done;
__device__ unsigned g_epoch;

__device__ __forceinline__ uint32_t smem_u32(const void* p) { return (uint32_t)__cvta_generic_to_shared(p); }
__device__ __forceinline__ void mbar_init(uint32_t bar, uint32_t cnt) { asm volatile("mbarrier.init.shared::cta.b64 [%0], %1;" :: "r"(bar), "r"(cnt)); }
__device__ __forceinline__ void mbar_expect_tx(uint32_t bar, uint32_t bytes) { asm volatile("mbarrier.arrive.expect_tx.shared::cta.b64 _, [%0], %1;" :: "r"(bar), "r"(bytes) : "memory"); }
__device__ __forceinline__ void mbar_arrive(uint32_t bar) { asm volatile("mbarrier.arrive.shared::cta.b64 _, [%0];" :: "r"(bar) : "memory"); }
__device__ __forceinline__ void mbar_arrive_cta(uint32_t bar, uint32_t cta) {
  asm volatile("{\n.reg .b32 ra;\nmapa.shared::cluster.u32 ra, %0, %1;\nmbarrier.arrive.shared::cluster.b64 _, [ra];\n}" :: "r"(bar), "r"(cta) : "memory");
}
__device__ __forceinline__ bool mbar_test(uint32_t bar, uint32_t parity) {
  uint32_t ok;
  asm volatile("{\n.reg .pred P1;\nmbarrier.test_wait.parity.shared::cta.b64 P1, [%1], %2;\nselp.u32 %0, 1, 0, P1;\n}" : "=r"(ok) : "r"(bar), "r"(parity) : "memory");
  return ok;
}
constexpr uint32_t SPIN_LIMIT = 1u << 22;
__device__ __forceinline__ void trap_if(bool c) { asm volatile("{\n.reg .pred P;\nsetp.ne.u32 P, %0, 0;\n@P trap;\n}" :: "r"((uint32_t)c)); }
__device__ __forceinline__ void mbar_wait(uint32_t bar, uint32_t parity) {
  asm volatile("{\n.reg .pred P1;\n.reg .u32 n;\nmbarrier.try_wait.parity.shared::cta.b64 P1, [%0], %1;\n@P1 bra DONE;\nmov.u32 n, 0;\n"
               "LOOP:\nmbarrier.try_wait.parity.shared::cta.b64 P1, [%0], %1;\n@P1 bra DONE;\nadd.u32 n, n, 1;\nsetp.gt.u32 P1, n, %2;\n@P1 trap;\nbra LOOP;\nDONE:\n}"
               :: "r"(bar), "r"(parity), "n"(SPIN_LIMIT) : "memory");
}
__device__ __forceinline__ void mbar_spin(uint32_t bar, uint32_t parity) {
  asm volatile("{\n.reg .pred P1;\nLOOP:\nmbarrier.try_wait.parity.shared::cta.b64 P1, [%0], %1;\n@!P1 bra LOOP;\n}" :: "r"(bar), "r"(parity) : "memory");
}
__device__ __forceinline__ void mbar_wait_sleep(uint32_t bar, uint32_t parity, uint32_t ns) {
  uint32_t n = 0;
  while (!mbar_test(bar, parity)) { trap_if(++n > SPIN_LIMIT * 4); __nanosleep(ns); }
}
__device__ __forceinline__ void tma_load_2d(uint32_t dst, const CUtensorMap* tm, int c0, int c1, uint32_t bar) {
  asm volatile("cp.async.bulk.tensor.2d.shared::cluster.global.mbarrier::complete_tx::bytes [%0], [%1, {%3, %4}], [%2];"
    :: "r"(dst), "l"(tm), "r"(bar), "r"(c0), "r"(c1) : "memory");
}
__device__ __forceinline__ void tma_load_2d_mc(uint32_t dst, const CUtensorMap* tm, int c0, int c1, uint32_t bar) {
  asm volatile("cp.async.bulk.tensor.2d.shared::cluster.global.mbarrier::complete_tx::bytes.multicast::cluster [%0], [%1, {%3, %4}], [%2], %5;"
    :: "r"(dst), "l"(tm), "r"(bar), "r"(c0), "r"(c1), "h"((uint16_t)3) : "memory");
}
__device__ __forceinline__ void tma_prefetch_2d(const CUtensorMap* tm, int c0, int c1) {
  asm volatile("cp.async.bulk.prefetch.tensor.2d.L2.global [%0, {%1, %2}];" :: "l"(tm), "r"(c0), "r"(c1) : "memory");
}
__device__ __forceinline__ void tma_prefetch_3d(const CUtensorMap* tm, int c1, int c2) {
  asm volatile("cp.async.bulk.prefetch.tensor.3d.L2.global [%0, {%1, %2, %3}];" :: "l"(tm), "r"(0), "r"(c1), "r"(c2) : "memory");
}
__device__ __forceinline__ void tma_load_3d_mc(uint32_t dst, const CUtensorMap* tm, int c1, int c2, uint32_t bar) {
  asm volatile("cp.async.bulk.tensor.3d.shared::cluster.global.mbarrier::complete_tx::bytes.multicast::cluster [%0], [%1, {%3, %4, %5}], [%2], %6;"
    :: "r"(dst), "l"(tm), "r"(bar), "r"(0), "r"(c1), "r"(c2), "h"((uint16_t)3) : "memory");
}
__device__ __forceinline__ void tma_store_2d(const CUtensorMap* tm, uint32_t src, int c0, int c1) {
  asm volatile("cp.async.bulk.tensor.2d.global.shared::cta.bulk_group [%0, {%2, %3}], [%1];" :: "l"(tm), "r"(src), "r"(c0), "r"(c1) : "memory");
}
__device__ __forceinline__ void bulk_commit() { asm volatile("cp.async.bulk.commit_group;" ::: "memory"); }
template <int N> __device__ __forceinline__ void bulk_wait_read() { asm volatile("cp.async.bulk.wait_group.read %0;" :: "n"(N) : "memory"); }
template <int N> __device__ __forceinline__ void bulk_wait() { asm volatile("cp.async.bulk.wait_group %0;" :: "n"(N) : "memory"); }
__device__ __forceinline__ void fence_async_smem() { asm volatile("fence.proxy.async.shared::cta;" ::: "memory"); }
__device__ __forceinline__ void fence_async_global() { asm volatile("fence.proxy.async.global;" ::: "memory"); }
__device__ __forceinline__ void wgmma_fence() { asm volatile("wgmma.fence.sync.aligned;" ::: "memory"); }
__device__ __forceinline__ void wgmma_commit() { asm volatile("wgmma.commit_group.sync.aligned;" ::: "memory"); }
template <int N> __device__ __forceinline__ void wgmma_wait() { asm volatile("wgmma.wait_group.sync.aligned %0;" :: "n"(N) : "memory"); }
__device__ __forceinline__ uint64_t make_desc(uint32_t addr, uint32_t lbo, uint32_t sbo) {
  return (uint64_t)((addr & 0x3FFFF) >> 4) | ((uint64_t)(lbo >> 4) << 16) | ((uint64_t)(sbo >> 4) << 32) | (1ull << 62);
}
template <int N> __device__ __forceinline__ void fence_regs(float (&d)[N]) {
#pragma unroll
  for (int i = 0; i < N; i++) asm volatile("" : "+f"(d[i]) :: "memory");
}
template <int N> __device__ __forceinline__ void fence_regs(uint32_t (&d)[N]) {
#pragma unroll
  for (int i = 0; i < N; i++) asm volatile("" : "+r"(d[i]) :: "memory");
}
__device__ __forceinline__ void named_sync(int id) { asm volatile("bar.sync %0, 256;" :: "r"(id) : "memory"); }
__device__ __forceinline__ bool wg_any(bool w, bool v) {
  uint32_t r;
  asm volatile("{\n.reg .pred p, q;\nsetp.ne.u32 p, %1, 0;\nbar.red.or.pred q, %2, 128, p;\nselp.u32 %0, 1, 0, q;\n}" : "=r"(r) : "r"((uint32_t)v), "r"(w ? 4 : 3) : "memory");
  return __any_sync(0xffffffffu, r);
}
__device__ __forceinline__ int fresh_warp() { uint32_t t; asm volatile("mov.u32 %0, %%tid.x;" : "=r"(t)); return __shfl_sync(0xffffffffu, (int)(t >> 5) - 4, 0); }
__device__ __forceinline__ void cluster_sync_relaxed() { asm volatile("barrier.cluster.arrive.relaxed.aligned;\nbarrier.cluster.wait.aligned;" ::: "memory"); }
__device__ __forceinline__ unsigned ld_acquire(const unsigned* p) { unsigned v; asm volatile("ld.acquire.gpu.global.u32 %0, [%1];" : "=r"(v) : "l"(p) : "memory"); return v; }
__device__ __forceinline__ void red_release(unsigned* p, unsigned v) { asm volatile("red.release.gpu.global.add.u32 [%0], %1;" :: "l"(p), "r"(v) : "memory"); }
__device__ __forceinline__ void flag_wait(const unsigned* p, unsigned target) {
  uint32_t n = 0;
  while (ld_acquire(p) < target) { trap_if(++n > SPIN_LIMIT); __nanosleep(20); }
}
__device__ __forceinline__ void st_tagged(uint2* p, float a, float b, uint32_t tag) {
  asm volatile("{\n.reg .b64 x;\nmov.b64 x, {%1, %2};\nst.relaxed.gpu.global.b64 [%0], x;\n}" :: "l"(p),
               "r"((__float_as_uint(a) & ~63u) | (tag & 63u)), "r"((__float_as_uint(b) & ~63u) | (tag >> 6)) : "memory");
}
__device__ __forceinline__ uint4 ld_tagged2(const uint2* p) {
  uint4 v;
  asm volatile("{\n.reg .b64 x, y;\nld.relaxed.gpu.global.v2.b64 {x, y}, [%4];\nmov.b64 {%0, %1}, x;\nmov.b64 {%2, %3}, y;\n}" : "=r"(v.x), "=r"(v.y), "=r"(v.z), "=r"(v.w) : "l"(p) : "memory");
  return v;
}
__device__ __forceinline__ bool tag_ok(uint32_t a, uint32_t b, uint32_t tag) { return ((a & 63u) | ((b & 63u) << 6)) == tag; }
__device__ __forceinline__ uint32_t pack_bf16(float lo, float hi) { uint32_t r; asm("cvt.rn.bf16x2.f32 %0, %1, %2;" : "=r"(r) : "f"(hi), "f"(lo)); return r; }
__device__ __forceinline__ uint32_t bf2_fma(uint32_t a, uint32_t b, uint32_t c) { uint32_t r; asm("fma.rn.bf16x2 %0, %1, %2, %3;" : "=r"(r) : "r"(a), "r"(b), "r"(c)); return r; }
__device__ __forceinline__ uint32_t bf2_mul(uint32_t a, uint32_t b) { uint32_t r; asm("mul.rn.bf16x2 %0, %1, %2;" : "=r"(r) : "r"(a), "r"(b)); return r; }
__device__ __forceinline__ uint32_t bf2_add(uint32_t a, uint32_t b) { uint32_t r; asm("add.rn.bf16x2 %0, %1, %2;" : "=r"(r) : "r"(a), "r"(b)); return r; }
constexpr uint32_t BF2_HALF = 0x3f003f00u;
__device__ __forceinline__ float bf_lo(uint32_t v) { return __uint_as_float(v << 16); }
__device__ __forceinline__ float bf_hi(uint32_t v) { return __uint_as_float(v & 0xffff0000u); }
__device__ __forceinline__ float ex2(float x) { float y; asm("ex2.approx.ftz.f32 %0, %1;" : "=f"(y) : "f"(x)); return y; }
__device__ __forceinline__ float tanh_fast(float x) { float y; asm("tanh.approx.f32 %0, %1;" : "=f"(y) : "f"(x)); return y; }
__device__ __forceinline__ void stmatrix_x4(uint32_t addr, uint32_t a, uint32_t b, uint32_t c, uint32_t d) {
  asm volatile("stmatrix.sync.aligned.m8n8.x4.shared.b16 [%0], {%1, %2, %3, %4};" :: "r"(addr), "r"(a), "r"(b), "r"(c), "r"(d) : "memory");
}
__device__ __forceinline__ void ldmatrix_x4(uint32_t addr, uint32_t& a, uint32_t& b, uint32_t& c, uint32_t& d) {
  asm volatile("ldmatrix.sync.aligned.m8n8.x4.shared.b16 {%0, %1, %2, %3}, [%4];" : "=r"(a), "=r"(b), "=r"(c), "=r"(d) : "r"(addr) : "memory");
}
__device__ __forceinline__ uint32_t lane_id() { uint32_t l; asm volatile("mov.u32 %0, %%laneid;" : "=r"(l)); return l; }
__device__ __forceinline__ bool elect_one() {
  uint32_t r;
  asm volatile("{\n.reg .pred P;\nelect.sync _|P, 0xffffffff;\nselp.u32 %0, 1, 0, P;\n}" : "=r"(r));
  return r;
}

__device__ __forceinline__ void wgmma_m64n128k16_ss_tb0(float (&d)[64], uint64_t da, uint64_t db, int scale_d) {
  asm volatile("{\n.reg .pred p;\nsetp.ne.b32 p, %66, 0;\n"
    "wgmma.mma_async.sync.aligned.m64n128k16.f32.bf16.bf16 "
    "{%0, %1, %2, %3, %4, %5, %6, %7, %8, %9, %10, %11, %12, %13, %14, %15, %16, %17, %18, %19, %20, %21, %22, %23, %24, %25, %26, %27, %28, %29, %30, %31, %32, %33, %34, %35, %36, %37, %38, %39, %40, %41, %42, %43, %44, %45, %46, %47, %48, %49, %50, %51, %52, %53, %54, %55, %56, %57, %58, %59, %60, %61, %62, %63}, "
    "%64, %65, p, 1, 1, 0, 0;\n}\n"
    : "+f"(d[0]), "+f"(d[1]), "+f"(d[2]), "+f"(d[3]), "+f"(d[4]), "+f"(d[5]), "+f"(d[6]), "+f"(d[7]), "+f"(d[8]), "+f"(d[9]), "+f"(d[10]), "+f"(d[11]), "+f"(d[12]), "+f"(d[13]), "+f"(d[14]), "+f"(d[15]), "+f"(d[16]), "+f"(d[17]), "+f"(d[18]), "+f"(d[19]), "+f"(d[20]), "+f"(d[21]), "+f"(d[22]), "+f"(d[23]), "+f"(d[24]), "+f"(d[25]), "+f"(d[26]), "+f"(d[27]), "+f"(d[28]), "+f"(d[29]), "+f"(d[30]), "+f"(d[31]), "+f"(d[32]), "+f"(d[33]), "+f"(d[34]), "+f"(d[35]), "+f"(d[36]), "+f"(d[37]), "+f"(d[38]), "+f"(d[39]), "+f"(d[40]), "+f"(d[41]), "+f"(d[42]), "+f"(d[43]), "+f"(d[44]), "+f"(d[45]), "+f"(d[46]), "+f"(d[47]), "+f"(d[48]), "+f"(d[49]), "+f"(d[50]), "+f"(d[51]), "+f"(d[52]), "+f"(d[53]), "+f"(d[54]), "+f"(d[55]), "+f"(d[56]), "+f"(d[57]), "+f"(d[58]), "+f"(d[59]), "+f"(d[60]), "+f"(d[61]), "+f"(d[62]), "+f"(d[63])
    : "l"(da), "l"(db), "r"(scale_d));
}
__device__ __forceinline__ void wgmma_m64n256k16_ss_tb1(float (&d)[128], uint64_t da, uint64_t db, int scale_d) {
  asm volatile("{\n.reg .pred p;\nsetp.ne.b32 p, %130, 0;\n"
    "wgmma.mma_async.sync.aligned.m64n256k16.f32.bf16.bf16 "
    "{%0, %1, %2, %3, %4, %5, %6, %7, %8, %9, %10, %11, %12, %13, %14, %15, %16, %17, %18, %19, %20, %21, %22, %23, %24, %25, %26, %27, %28, %29, %30, %31, %32, %33, %34, %35, %36, %37, %38, %39, %40, %41, %42, %43, %44, %45, %46, %47, %48, %49, %50, %51, %52, %53, %54, %55, %56, %57, %58, %59, %60, %61, %62, %63, %64, %65, %66, %67, %68, %69, %70, %71, %72, %73, %74, %75, %76, %77, %78, %79, %80, %81, %82, %83, %84, %85, %86, %87, %88, %89, %90, %91, %92, %93, %94, %95, %96, %97, %98, %99, %100, %101, %102, %103, %104, %105, %106, %107, %108, %109, %110, %111, %112, %113, %114, %115, %116, %117, %118, %119, %120, %121, %122, %123, %124, %125, %126, %127}, "
    "%128, %129, p, 1, 1, 0, 1;\n}\n"
    : "+f"(d[0]), "+f"(d[1]), "+f"(d[2]), "+f"(d[3]), "+f"(d[4]), "+f"(d[5]), "+f"(d[6]), "+f"(d[7]), "+f"(d[8]), "+f"(d[9]), "+f"(d[10]), "+f"(d[11]), "+f"(d[12]), "+f"(d[13]), "+f"(d[14]), "+f"(d[15]), "+f"(d[16]), "+f"(d[17]), "+f"(d[18]), "+f"(d[19]), "+f"(d[20]), "+f"(d[21]), "+f"(d[22]), "+f"(d[23]), "+f"(d[24]), "+f"(d[25]), "+f"(d[26]), "+f"(d[27]), "+f"(d[28]), "+f"(d[29]), "+f"(d[30]), "+f"(d[31]), "+f"(d[32]), "+f"(d[33]), "+f"(d[34]), "+f"(d[35]), "+f"(d[36]), "+f"(d[37]), "+f"(d[38]), "+f"(d[39]), "+f"(d[40]), "+f"(d[41]), "+f"(d[42]), "+f"(d[43]), "+f"(d[44]), "+f"(d[45]), "+f"(d[46]), "+f"(d[47]), "+f"(d[48]), "+f"(d[49]), "+f"(d[50]), "+f"(d[51]), "+f"(d[52]), "+f"(d[53]), "+f"(d[54]), "+f"(d[55]), "+f"(d[56]), "+f"(d[57]), "+f"(d[58]), "+f"(d[59]), "+f"(d[60]), "+f"(d[61]), "+f"(d[62]), "+f"(d[63]), "+f"(d[64]), "+f"(d[65]), "+f"(d[66]), "+f"(d[67]), "+f"(d[68]), "+f"(d[69]), "+f"(d[70]), "+f"(d[71]), "+f"(d[72]), "+f"(d[73]), "+f"(d[74]), "+f"(d[75]), "+f"(d[76]), "+f"(d[77]), "+f"(d[78]), "+f"(d[79]), "+f"(d[80]), "+f"(d[81]), "+f"(d[82]), "+f"(d[83]), "+f"(d[84]), "+f"(d[85]), "+f"(d[86]), "+f"(d[87]), "+f"(d[88]), "+f"(d[89]), "+f"(d[90]), "+f"(d[91]), "+f"(d[92]), "+f"(d[93]), "+f"(d[94]), "+f"(d[95]), "+f"(d[96]), "+f"(d[97]), "+f"(d[98]), "+f"(d[99]), "+f"(d[100]), "+f"(d[101]), "+f"(d[102]), "+f"(d[103]), "+f"(d[104]), "+f"(d[105]), "+f"(d[106]), "+f"(d[107]), "+f"(d[108]), "+f"(d[109]), "+f"(d[110]), "+f"(d[111]), "+f"(d[112]), "+f"(d[113]), "+f"(d[114]), "+f"(d[115]), "+f"(d[116]), "+f"(d[117]), "+f"(d[118]), "+f"(d[119]), "+f"(d[120]), "+f"(d[121]), "+f"(d[122]), "+f"(d[123]), "+f"(d[124]), "+f"(d[125]), "+f"(d[126]), "+f"(d[127])
    : "l"(da), "l"(db), "r"(scale_d));
}
__device__ __forceinline__ void wgmma_m64n128k16_rs_tb1(float (&d)[64], uint32_t a0, uint32_t a1, uint32_t a2, uint32_t a3, uint64_t db, int scale_d) {
  asm volatile("{\n.reg .pred p;\nsetp.ne.b32 p, %69, 0;\n"
    "wgmma.mma_async.sync.aligned.m64n128k16.f32.bf16.bf16 "
    "{%0, %1, %2, %3, %4, %5, %6, %7, %8, %9, %10, %11, %12, %13, %14, %15, %16, %17, %18, %19, %20, %21, %22, %23, %24, %25, %26, %27, %28, %29, %30, %31, %32, %33, %34, %35, %36, %37, %38, %39, %40, %41, %42, %43, %44, %45, %46, %47, %48, %49, %50, %51, %52, %53, %54, %55, %56, %57, %58, %59, %60, %61, %62, %63}, "
    "{%64, %65, %66, %67}, %68, p, 1, 1, 1;\n}\n"
    : "+f"(d[0]), "+f"(d[1]), "+f"(d[2]), "+f"(d[3]), "+f"(d[4]), "+f"(d[5]), "+f"(d[6]), "+f"(d[7]), "+f"(d[8]), "+f"(d[9]), "+f"(d[10]), "+f"(d[11]), "+f"(d[12]), "+f"(d[13]), "+f"(d[14]), "+f"(d[15]), "+f"(d[16]), "+f"(d[17]), "+f"(d[18]), "+f"(d[19]), "+f"(d[20]), "+f"(d[21]), "+f"(d[22]), "+f"(d[23]), "+f"(d[24]), "+f"(d[25]), "+f"(d[26]), "+f"(d[27]), "+f"(d[28]), "+f"(d[29]), "+f"(d[30]), "+f"(d[31]), "+f"(d[32]), "+f"(d[33]), "+f"(d[34]), "+f"(d[35]), "+f"(d[36]), "+f"(d[37]), "+f"(d[38]), "+f"(d[39]), "+f"(d[40]), "+f"(d[41]), "+f"(d[42]), "+f"(d[43]), "+f"(d[44]), "+f"(d[45]), "+f"(d[46]), "+f"(d[47]), "+f"(d[48]), "+f"(d[49]), "+f"(d[50]), "+f"(d[51]), "+f"(d[52]), "+f"(d[53]), "+f"(d[54]), "+f"(d[55]), "+f"(d[56]), "+f"(d[57]), "+f"(d[58]), "+f"(d[59]), "+f"(d[60]), "+f"(d[61]), "+f"(d[62]), "+f"(d[63])
    : "r"(a0), "r"(a1), "r"(a2), "r"(a3), "l"(db), "r"(scale_d));
}
__device__ __forceinline__ void wgmma_m64n128k16_ss_tb1(float (&d)[64], uint64_t da, uint64_t db, int scale_d) {
  asm volatile("{\n.reg .pred p;\nsetp.ne.b32 p, %66, 0;\n"
    "wgmma.mma_async.sync.aligned.m64n128k16.f32.bf16.bf16 "
    "{%0, %1, %2, %3, %4, %5, %6, %7, %8, %9, %10, %11, %12, %13, %14, %15, %16, %17, %18, %19, %20, %21, %22, %23, %24, %25, %26, %27, %28, %29, %30, %31, %32, %33, %34, %35, %36, %37, %38, %39, %40, %41, %42, %43, %44, %45, %46, %47, %48, %49, %50, %51, %52, %53, %54, %55, %56, %57, %58, %59, %60, %61, %62, %63}, "
    "%64, %65, p, 1, 1, 0, 1;\n}\n"
    : "+f"(d[0]), "+f"(d[1]), "+f"(d[2]), "+f"(d[3]), "+f"(d[4]), "+f"(d[5]), "+f"(d[6]), "+f"(d[7]), "+f"(d[8]), "+f"(d[9]), "+f"(d[10]), "+f"(d[11]), "+f"(d[12]), "+f"(d[13]), "+f"(d[14]), "+f"(d[15]), "+f"(d[16]), "+f"(d[17]), "+f"(d[18]), "+f"(d[19]), "+f"(d[20]), "+f"(d[21]), "+f"(d[22]), "+f"(d[23]), "+f"(d[24]), "+f"(d[25]), "+f"(d[26]), "+f"(d[27]), "+f"(d[28]), "+f"(d[29]), "+f"(d[30]), "+f"(d[31]), "+f"(d[32]), "+f"(d[33]), "+f"(d[34]), "+f"(d[35]), "+f"(d[36]), "+f"(d[37]), "+f"(d[38]), "+f"(d[39]), "+f"(d[40]), "+f"(d[41]), "+f"(d[42]), "+f"(d[43]), "+f"(d[44]), "+f"(d[45]), "+f"(d[46]), "+f"(d[47]), "+f"(d[48]), "+f"(d[49]), "+f"(d[50]), "+f"(d[51]), "+f"(d[52]), "+f"(d[53]), "+f"(d[54]), "+f"(d[55]), "+f"(d[56]), "+f"(d[57]), "+f"(d[58]), "+f"(d[59]), "+f"(d[60]), "+f"(d[61]), "+f"(d[62]), "+f"(d[63])
    : "l"(da), "l"(db), "r"(scale_d));
}


enum { TM_XN, TM_WSP, TM_U, TM_O, TM_Q, TM_X, TM_SA, TM_G, TM_K, TM_V, TM_WO64,
       TM_WIN, TM_WQ, TM_Z2, TM_WOUT, TM_WO, TS_Q, TS_O, TS_Z2, TS_U, TS_SA, TS_G, TS_OUT, TM_COUNT };
enum { T_Z2 = 0, T_Q = 1, T_U = 2, T_ATT = 3, T_SA = 4, T_FIN = 5, T_END = 7 };
constexpr int NCLUSTER = 66, MAXI = 14;
struct alignas(64) Params {
  const bf16* x;
  const bf16* b_sp;
  CUtensorMap tm[TM_COUNT];
  uint16_t items[NCLUSTER][MAXI];
};

constexpr uint32_t G_STAGE = 49152, G_A = 16384, KV_SLOT = 32768;
constexpr uint32_t OFF_Q1 = 163840, OFF_Q0 = 196608, OFF_BAR = 229376, OFF_LN = OFF_BAR + 256, SMEM_BYTES = OFF_LN + 1024;
constexpr uint32_t B_GF = 0, B_GE = 32, B_KF = 64, B_KE = 104, B_QF = 144, B_QE = 160, B_XF = 176, B_XR = 184, B_STG = 192, B_FREE = 200, B_GO = 208, B_LN = 216, B_TAG = 224, B_RDY = 228, B_PROG = 232, B_PUB = 248;
constexpr int SA_HEADS = 18;
constexpr int SW_NS = 40;
constexpr int ST_ROWS = 16;
constexpr int ST_FLY = 2;
constexpr int KV_PF = 4;
constexpr int POLL_NS = 20;
constexpr int FIN_PREP = 8;
constexpr int SCOUT = 5;
constexpr int OWN_OFF = 8;
constexpr int Z_DELAY = 3;
constexpr int SW_ATT = 800;
constexpr int OUT_PF = 8;
constexpr int SA_ROT = 1;
constexpr uint32_t FIN_SLOT0 = (0x0320u >> (4 * ((28 + 2 * SA_HEADS + SA_ROT) & 3))) & 15;
constexpr float SM_C = 0.08838834764831845f * 1.4426950408889634f;
constexpr float GELU_A = 0.7978845608028654f, GELU_B = 0.7978845608028654f * 0.044715f;
constexpr float SM_LO = 1e-7f, SM_HI = 1e12f;
constexpr float SM_THR = 1024.f;


extern __shared__ __align__(1024) uint8_t smem_raw[];
__device__ __forceinline__ uint32_t smem_base() { return smem_u32(smem_raw); }

struct Ring { uint32_t s, ph; };
template <int N> __device__ __forceinline__ void ring_adv(Ring& r) { if (++r.s == N) { r.s = 0; r.ph ^= 1; } }

__device__ __forceinline__ int get_item(const Params& p, int i) {
  uint32_t b; asm volatile("mov.u32 %0, %%ctaid.x;" : "=r"(b));
  return p.items[b >> 1][i];
}
struct Cons {
  uint32_t sb;
  int warp;
  Ring g;
  uint32_t rot;
  uint32_t fph;
};

__device__ __forceinline__ void stage_acquire(const Cons& c) { mbar_spin(c.sb + OFF_BAR + B_FREE, c.fph); }
__device__ __forceinline__ void stage_commit(Cons& c) {
  __syncwarp();
  if (lane_id() == 0) mbar_arrive(c.sb + OFF_BAR + B_STG);
  c.fph ^= 1;
}

__device__ __forceinline__ void release_slot(const Cons& c, uint32_t bar) {
  if (lane_id() == 0 && (c.warp & 3) < 2) mbar_arrive_cta(bar, c.warp & 1);
}
constexpr uint64_t DESC_HI = (uint64_t)0x40000040u << 32;

template <bool FIRST> __device__ __forceinline__ void gemm_step(float (&acc)[128], Cons& c) {
  mbar_spin(c.sb + OFF_BAR + B_GF + 8 * c.g.s, c.g.ph);
  const uint32_t st = ((c.sb & 0x3FFFF) >> 4) + ((c.g.s + c.rot) & 3) * (G_STAGE >> 4);
  const uint32_t da = st + (c.warp >> 2) * 512 + (1u << 16), db = st + (G_A >> 4) + ((8192u >> 4) << 16);
  wgmma_fence();
#pragma unroll
  for (int kk = 0; kk < 4; kk++) wgmma_m64n256k16_ss_tb1(acc, DESC_HI | (da + kk * 2), DESC_HI | (db + kk * 128), !(FIRST && kk == 0));
  wgmma_commit();
}

template <int N> __device__ __forceinline__ void stage_chunks(uint32_t buf, uint32_t stride, const uint32_t* pk) {
  const uint32_t ln = lane_id();
  const uint32_t a = buf + ((ln & 15) << 7);
  const uint32_t x = ln & 7, hi = ln >> 4;
#pragma unroll
  for (int i = 0; i < 4 * N; i++) stmatrix_x4(a + (i >> 2) * stride + (((2 * (i & 3) + hi) ^ x) << 4), pk[4 * i], pk[4 * i + 1], pk[4 * i + 2], pk[4 * i + 3]);
}

__device__ __forceinline__ float act2_fn(float x, float a, float b) {
  return fmaf(x, tanh_fast(x * fmaf(x * x, b, a)), x);
}
__device__ __forceinline__ float quad_sum(float v) { v += __shfl_xor_sync(0xffffffffu, v, 1); v += __shfl_xor_sync(0xffffffffu, v, 2); return v; }
__device__ __forceinline__ float quad_max(float v) { v = fmaxf(v, __shfl_xor_sync(0xffffffffu, v, 1)); v = fmaxf(v, __shfl_xor_sync(0xffffffffu, v, 2)); return v; }

__device__ __forceinline__ uint32_t load_tag(const Cons& c) { uint32_t t; asm volatile("ld.volatile.shared.u32 %0, [%1];" : "=r"(t) : "r"(c.sb + OFF_BAR + B_TAG)); return t; }

struct Shadow {
  int act;
  int store;
};
__device__ __forceinline__ void rotate16(uint32_t (&h)[64]) {
#pragma unroll
  for (int i = 0; i < 16; i++)
    asm volatile("{\n.reg .b32 t;\nmov.b32 t, %0;\nmov.b32 %0, %1;\nmov.b32 %1, %2;\nmov.b32 %2, %3;\nmov.b32 %3, t;\n}" : "+r"(h[i]), "+r"(h[i + 16]), "+r"(h[i + 32]), "+r"(h[i + 48]));
}

template <int O>
__device__ __forceinline__ void act_block(uint32_t (&held)[64], float ca, float cb, bool first, float& u0, float& u1, float& s0, float& s1, float& q0, float& q1) {
#pragma unroll
  for (int i = O; i < O + 4; i += 2) {
    const float a0 = act2_fn(bf_lo(held[i]), ca, cb), a1 = act2_fn(bf_hi(held[i]), ca, cb);
    const float b0 = act2_fn(bf_lo(held[i + 1]), ca, cb), b1 = act2_fn(bf_hi(held[i + 1]), ca, cb);
    if (i == 0 && first) { u0 = a0; u1 = b0; }
    float d;
    d = a0 - u0; s0 += d; q0 = fmaf(d, d, q0); d = a1 - u0; s0 += d; q0 = fmaf(d, d, q0);
    d = b0 - u1; s1 += d; q1 = fmaf(d, d, q1); d = b1 - u1; s1 += d; q1 = fmaf(d, d, q1);
    held[i] = pack_bf16(a0, a1); held[i + 1] = pack_bf16(b0, b1);
  }
}

template <int O> __device__ __forceinline__ void stage_half(Cons& c, uint32_t (&held)[64], int mode) {
  if (mode == 2) {
    uint32_t a0, a1, r0, r1;
    const uint32_t la = c.sb + OFF_LN + (c.warp * 16 + (lane_id() >> 2)) * 8;
    mbar_spin(c.sb + OFF_BAR + B_LN, 0);
    asm volatile("ld.shared.v2.b32 {%0, %1}, [%2];" : "=r"(r0), "=r"(a0) : "r"(la));
    asm volatile("ld.shared.v2.b32 {%0, %1}, [%2];" : "=r"(r1), "=r"(a1) : "r"(la + 64));
#pragma unroll
    for (int i = O; i < O + 32; i += 2) { held[i] = bf2_mul(bf2_add(held[i], a0), r0); held[i + 1] = bf2_mul(bf2_add(held[i + 1], a1), r1); }
  }
  stage_acquire(c);
  stage_chunks<2>(c.sb + OFF_Q0 + c.warp * 2048, 16384, held + O);
  stage_commit(c);
}

__device__ __forceinline__ void gemm_seg(float (&acc)[128], uint32_t (&held)[64], Cons& c, const Params& p, Shadow& sh, int nsteps) {
  const bool elected = lane_id() == 0 && (c.warp & 3) < 2;
  uint32_t rel;
  asm("mapa.shared::cluster.u32 %0, %1, %2;" : "=r"(rel) : "r"(c.sb + OFF_BAR + B_GE), "r"((uint32_t)(c.warp & 1)));
  gemm_step<true>(acc, c);
  ring_adv<4>(c.g);
  int k = 1;
#define G_STEP()                                                                                                       \
  { gemm_step<false>(acc, c);                                                                                          \
    wgmma_wait<1>();                                                                                                   \
    if (elected) asm volatile("mbarrier.arrive.shared::cluster.b64 _, [%0];" :: "r"(rel + 8 * ((c.g.s - 1) & 3)) : "memory"); \
    ring_adv<4>(c.g);                                                                                                  \
    k++; }
  if (sh.act != 0) {
    float u0 = 0.f, u1 = 0.f, s0 = 0.f, s1 = 0.f, q0 = 0.f, q1 = 0.f;
    const float ca = sh.act == 3 ? 0.5f : GELU_A, cb = sh.act == 3 ? 0.f : GELU_B;
#pragma unroll 1
    while (true) {
      act_block<0>(held, ca, cb, k == 1, u0, u1, s0, s1, q0, q1);
      G_STEP()
      act_block<4>(held, ca, cb, false, u0, u1, s0, s1, q0, q1);
      G_STEP()
      act_block<8>(held, ca, cb, false, u0, u1, s0, s1, q0, q1);
      G_STEP()
      act_block<12>(held, ca, cb, false, u0, u1, s0, s1, q0, q1);
      rotate16(held);
      if (k == 16) break;
      G_STEP()
    }
    if (sh.act == 2) {
      const int zi = get_item(p, 0);
      const int ln = lane_id(), row0 = (((zi >> 5) & 31) * 2 + (blockIdx.x & 1)) * 128 + c.warp * 16 + (ln >> 2), ql = ln & 3;
      const float m0 = fmaf(s0, 1.f / 64, u0), m1 = fmaf(s1, 1.f / 64, u1);
      q0 -= s0 * s0 * (1.f / 64); q1 -= s1 * s1 * (1.f / 64);
      const float mu0 = quad_sum(m0) * 0.25f, mu1 = quad_sum(m1) * 0.25f;
      q0 = quad_sum(fmaf(64.f * (m0 - mu0), m0 - mu0, q0)); q1 = quad_sum(fmaf(64.f * (m1 - mu1), m1 - mu1, q1));
      if (ql < 2) st_tagged(&g_stats[(row0 + 8 * ql) * 8 + (zi & 31)], ql ? mu1 : mu0, ql ? q1 : q0, load_tag(c));
      if (ln == 0) mbar_arrive(c.sb + OFF_BAR + B_PUB);
    }
  }
  const int s0 = sh.store == 0 ? -9 : k + (sh.store == 2 ? Z_DELAY : 1), s1 = sh.store == 3 ? -9 : s0 + 3;
#pragma unroll 1
  while (k < nsteps) {
    G_STEP()
    if (k == s0) stage_half<0>(c, held, sh.store);
    else if (k == s1) stage_half<32>(c, held, sh.store);
  }
  wgmma_wait<0>();
  fence_regs(acc);
  if (elected) asm volatile("mbarrier.arrive.shared::cluster.b64 _, [%0];" :: "r"(rel + 8 * ((c.g.s - 1) & 3)) : "memory");
  sh.store = sh.act == 2 ? 2 : 0;
  sh.act = 0;
}

template <bool SUB> __device__ __forceinline__ void softmax_exp(const float (&S)[64], uint32_t (&P)[32], float m0, float m1, float& s0, float& s1) {
  float a0 = 0.f, a1 = 0.f, b0 = 0.f, b1 = 0.f;
#pragma unroll
  for (int j = 0; j < 16; j++) {
    const float p0 = ex2(SUB ? S[4 * j] - m0 : S[4 * j]), p1 = ex2(SUB ? S[4 * j + 1] - m0 : S[4 * j + 1]);
    const float p2 = ex2(SUB ? S[4 * j + 2] - m1 : S[4 * j + 2]), p3 = ex2(SUB ? S[4 * j + 3] - m1 : S[4 * j + 3]);
    a0 += p0; b0 += p1; a1 += p2; b1 += p3;
    P[2 * j] = pack_bf16(p0, p1); P[2 * j + 1] = pack_bf16(p2, p3);
  }
  s0 = a0 + b0; s1 = a1 + b1;
}
__device__ __forceinline__ void row_max(const float (&S)[64], float& x0, float& x1) {
  float a0 = fmaxf(S[0], S[1]), a1 = fmaxf(S[2], S[3]);
#pragma unroll
  for (int j = 1; j < 16; j++) { a0 = fmaxf(a0, fmaxf(S[4 * j], S[4 * j + 1])); a1 = fmaxf(a1, fmaxf(S[4 * j + 2], S[4 * j + 3])); }
  x0 = quad_max(a0); x1 = quad_max(a1);
}

__device__ __forceinline__ void issue_qk(float (&S)[64], uint32_t da, uint32_t db) {
#pragma unroll
  for (int kk = 0; kk < 8; kk++) {
    const uint32_t o = (kk >> 2) * 1024 + (kk & 3) * 2;
    wgmma_m64n128k16_ss_tb0(S, DESC_HI | (da + o), DESC_HI | (db + o), kk > 0);
  }
}
__device__ __forceinline__ void issue_pv(float (&O)[64], const uint32_t (&P)[32], uint32_t db, int acc) {
#pragma unroll
  for (int kk = 0; kk < 8; kk++) wgmma_m64n128k16_rs_tb1(O, P[4 * kk], P[4 * kk + 1], P[4 * kk + 2], P[4 * kk + 3], DESC_HI | (db + kk * 128), (acc || kk > 0));
}

__device__ __forceinline__ void att_pack(const float (&O)[64], uint32_t (&pk)[32], float i0, float i1) {
#pragma unroll
  for (int j = 0; j < 16; j++) {
    pk[2 * j] = pack_bf16(O[4 * j] * i0, O[4 * j + 1] * i0);
    pk[2 * j + 1] = pack_bf16(O[4 * j + 2] * i1, O[4 * j + 3] * i1);
  }
}
__device__ __forceinline__ void att_stage(Cons& c, const uint32_t (&pk)[32], uint32_t qbuf) {
  stage_chunks<2>(c.sb + (qbuf ? OFF_Q1 : OFF_Q0) + c.warp * 2048, 16384, pk);
  stage_commit(c);
}

#define ATT_ISSUE(PIN, ACC)                                                                                            \
  wgmma_fence();                                                                                                       \
  issue_qk(S, qd, kd); wgmma_commit();                                                                                 \
  if (g > 1) release_slot(c, vrel);                                                                                    \
  vready = mbar_test(vbar, vph);                                                                                       \
  mbar_spin(vbar, vph);                                                                                                \
  wgmma_fence();                                                                                                       \
  issue_pv(O, PIN, vd, ACC); wgmma_commit();                                                                           \
  krel = kbar + (B_KE - B_KF); vrel = vbar + (B_KE - B_KF);                                                            \
  g++;                                                                                                                 \
  if (g < total) { kd = kd0 + kv.s * (KV_SLOT >> 4); kbar = bars + B_KF + 8 * kv.s; kph = kv.ph; ring_adv<5>(kv); }    \
  vd = vd0 + kv.s * (KV_SLOT >> 4); vbar = bars + B_KF + 8 * kv.s; vph = kv.ph; ring_adv<5>(kv);

#define ATT_WAIT_S()                                                                                                   \
  wgmma_wait<1>();                                                                                                     \
  fence_regs(S);                                                                                                       \
  release_slot(c, krel);                                                                                               \
  if (c.warp == 2) asm volatile("st.volatile.shared.u32 [%0], %1;" :: "r"(bars + B_PROG), "r"(g) : "memory");

#define ATT_SOFTMAX(POUT, FIRST)                                                                                       \
  fresh = false;                                                                                                       \
  _Pragma("unroll 1")                                                                                                  \
  while (true) {                                                                                                       \
    if (__builtin_expect(fresh, 0)) {                                                                                  \
      float x0, x1;                                                                                                    \
      row_max(S, x0, x1);                                                                                              \
      if (FIRST) m0 = m1 = -1e38f;                                                                                     \
      x0 = fmaxf(x0, m0); x1 = fmaxf(x1, m1);                                                                          \
      f0 = ex2(m0 - x0); f1 = ex2(m1 - x1);                                                                            \
      m0 = x0; m1 = x1; l0 *= f0; l1 *= f1;                                                                            \
      zero = false;                                                                                                    \
    }                                                                                                                  \
    if (zero) {                                                                                                        \
      softmax_exp<false>(S, POUT, m0, m1, s0, s1);                                                                     \
      bad = !(s0 <= SM_HI && s1 <= SM_HI) || ((FIRST) && (s0 < SM_LO || s1 < SM_LO));                                  \
    } else {                                                                                                           \
      softmax_exp<true>(S, POUT, m0, m1, s0, s1);                                                                      \
      bad = !(s0 <= SM_THR && s1 <= SM_THR);                                                                           \
    }                                                                                                                  \
    kready = mbar_test(kbar, kph) && vready;                                                                           \
    slow = fresh || __any_sync(0xffffffffu, bad || !kready);                                                           \
    if (__builtin_expect(!slow, 1)) break;                                                                             \
    if (fresh || !__any_sync(0xffffffffu, bad)) break;                                                                 \
    fresh = true;                                                                                                      \
  }                                                                                                                    \
  l0 += s0; l1 += s1;                                                                                                  \
  wgmma_wait<0>(); fence_regs(O);

#define ATT_RESCALE()                                                                                                  \
  { _Pragma("unroll")                                                                                                  \
    for (int i = 0; i < 16; i++) { O[4 * i] *= f0; O[4 * i + 1] *= f0; O[4 * i + 2] *= f1; O[4 * i + 3] *= f1; } }

__device__ __forceinline__ void att_stagger(const Cons& c, int g) {
  if (c.warp >= 4)
    asm volatile("{\n.reg .pred p;\n.reg .s32 v;\nLOOP:\nld.volatile.shared.s32 v, [%0];\nsetp.le.s32 p, v, %1;\n@p bra LOOP;\n}" :: "r"(c.sb + OFF_BAR + B_PROG), "r"(g) : "memory");
}

__device__ __forceinline__ void att_run(Cons& c, const Params& p, int it, int n) {
  const uint32_t bars = c.sb + OFF_BAR;
  float S[64], O[64];
  uint32_t P0[32], P1[32];
#pragma unroll
  for (int i = 0; i < 64; i++) O[i] = 0.f;
#pragma unroll
  for (int i = 0; i < 32; i++) P0[i] = P1[i] = 0u;
  fence_regs(O); fence_regs(P0); fence_regs(P1);
  float m0 = 0.f, m1 = 0.f, l0 = 0.f, l1 = 0.f, f0 = 1.f, f1 = 1.f, s0, s1, pl0 = 0.f, pl1 = 0.f;
  const int total = 16 * n;
  int g = 0;
  Ring kv = {1, 0};
  uint32_t kbar = bars + B_KF, kph = 0, vbar = bars + B_KF, vph = 0, krel, vrel = 0;
  const uint32_t kd0 = (uint32_t)make_desc(c.sb, 16, 1024), vd0 = (uint32_t)make_desc(c.sb, 16384, 1024);
  uint32_t qd = kd0 + ((OFF_Q0 + (c.warp >> 2) * 8192) >> 4), kd = kd0, vd = vd0;
  bool fresh, kready, vready, bad, slow, zero = false;
  mbar_spin(bars + B_QF, 0);
  mbar_spin(bars + B_KF, 0);
  att_stagger(c, 0);
#pragma unroll 1
  while (true) {
    ATT_ISSUE(P1, 1)
    const bool first = ((g - 1) & 15) == 0;
    if (first) { pl0 = l0; pl1 = l1; m0 = m1 = l0 = l1 = 0.f; zero = true; }
    ATT_WAIT_S()
    ATT_SOFTMAX(P0, first)
    if (__builtin_expect(slow || first, 0)) {
      if (first) {
        if (g > 1) {
          att_pack(O, P1, __fdividef(1.f, quad_sum(pl0)), __fdividef(1.f, quad_sum(pl1)));
          att_stage(c, P1, ((g >> 4) & 1) ^ 1);
        }
      } else if (fresh) ATT_RESCALE();
      mbar_spin(kbar, kph);
      if (__any_sync(0xffffffffu, !kready)) att_stagger(c, g);
    }
    ATT_ISSUE(P0, !first)
    ATT_WAIT_S()
    ATT_SOFTMAX(P1, false)
    if (__builtin_expect(slow || (g & 15) == 0, 0)) {
      if (fresh) ATT_RESCALE();
      if (g == total) break;
      mbar_spin(kbar, kph);
      if (__any_sync(0xffffffffu, !kready)) att_stagger(c, g);
      if ((g & 15) == 0) {
        const int t = g >> 4;
        const uint32_t qb = t & 1;
        mbar_spin(bars + B_QF + 8 * qb, (t >> 1) & 1);
        qd = kd0 + (((qb ? OFF_Q1 : OFF_Q0) + (c.warp >> 2) * 8192) >> 4);
      }
    }
  }
  release_slot(c, vrel);
  mbar_spin(vbar, vph);
  wgmma_fence();
  issue_pv(O, P1, vd, 1); wgmma_commit();
  pl0 = __fdividef(1.f, quad_sum(l0)); pl1 = __fdividef(1.f, quad_sum(l1));
  wgmma_wait<0>();
  fence_regs(O);
  release_slot(c, vbar + (B_KE - B_KF));
  att_pack(O, P0, pl0, pl1);
  if ((get_item(p, it + n) >> 12) == T_END) {
    const uint32_t buf = c.sb + (((n - 1) & 1) ? OFF_Q1 : OFF_Q0) + c.warp * 2048;
    stage_chunks<2>(buf, 16384, P0);
    fence_async_smem();
    __syncwarp();
    if (elect_one()) {
      const int im = get_item(p, it + n - 1), col = ((im >> 5) & 31) * 128, row = ((im & 31) * 2 + (blockIdx.x & 1)) * 128 + c.warp * 16;
      tma_store_2d(&p.tm[TS_O], buf, col, row); tma_store_2d(&p.tm[TS_O], buf + 16384, col + 64, row);
      bulk_commit();
      bulk_wait<0>();
      mbar_arrive(bars + B_STG);
    }
    __syncwarp();
  } else {
    att_stage(c, P0, (n - 1) & 1);
  }
}

__global__ void __cluster_dims__(2, 1, 1) __launch_bounds__(384, 1) fused_kernel(const __grid_constant__ Params p) {
  const uint32_t sb = smem_base();
  const uint32_t bars = sb + OFF_BAR;
  const int tid = threadIdx.x, lane = tid & 31;
  const int warp_id = __shfl_sync(0xffffffffu, tid >> 5, 0), wg = warp_id >> 2;
  const uint32_t rank = blockIdx.x & 1;
  const uint16_t* items = p.items[blockIdx.x >> 1];
  const int gw = blockIdx.x * 8 + warp_id - 4;
  uint4 xv[2][4];
  if (wg != 0 && gw < SEQ / 2) {
#pragma unroll
    for (int rr = 0; rr < 2; rr++)
#pragma unroll
      for (int i = 0; i < 4; i++) xv[rr][i] = __ldg(reinterpret_cast<const uint4*>(p.x + (size_t)(gw * 2 + rr) * DM) + i * 32 + lane);
  }
  if (warp_id == 1 && lane < TM_COUNT) asm volatile("prefetch.tensormap [%0];" :: "l"(&p.tm[lane]) : "memory");
  if (tid == 0) {
    for (int i = 0; i < 4; i++) { mbar_init(bars + B_GF + 8 * i, 1); mbar_init(bars + B_GE + 8 * i, 4); }
    for (int i = 0; i < 5; i++) { mbar_init(bars + B_KF + 8 * i, 1); mbar_init(bars + B_KE + 8 * i, 4); }
    for (int i = 0; i < 2; i++) { mbar_init(bars + B_QF + 8 * i, 1); mbar_init(bars + B_QE + 8 * i, 1); }
    mbar_init(bars + B_XF, 2); mbar_init(bars + B_XR, 2); mbar_init(bars + B_STG, 8); mbar_init(bars + B_FREE, 1); mbar_init(bars + B_GO, 1); mbar_init(bars + B_LN, 2); mbar_init(bars + B_PUB, 8);
    asm volatile("fence.mbarrier_init.release.cluster;" ::: "memory");
  }
  asm volatile("barrier.cluster.arrive.relaxed.aligned;" ::: "memory");

  if (wg == 0) {
    asm volatile("setmaxnreg.dec.sync.aligned.u32 40;");
    asm volatile("barrier.cluster.wait.acquire.aligned;" ::: "memory");
    if (warp_id >= 2 && (items[0] >> 12) == T_Z2) {
      if (lane == 0) mbar_wait_sleep(bars + B_PUB, 0, 100);
      __syncwarp();
      uint32_t tag;
      asm volatile("ld.volatile.shared.u32 %0, [%1];" : "=r"(tag) : "r"(bars + B_TAG));
      const int r = (warp_id - 2) * 64 + lane;
      const uint2* ps = &g_stats[((((items[0] >> 5) & 31) * 2 + rank) * 128 + r) * 8];
      uint4 t[2][4];
      uint32_t cnt = 0;
      while (true) {
        bool ok = true;
#pragma unroll
        for (int i = 0; i < 8; i++) t[i >> 2][i & 3] = ld_tagged2(ps + (i >> 2) * 256 + (i & 3) * 2);
#pragma unroll
        for (int i = 0; i < 8; i++) { const uint4 v = t[i >> 2][i & 3]; ok = ok && tag_ok(v.x, v.y, tag) && ((i & 3) == 3 || tag_ok(v.z, v.w, tag)); }
        if (__all_sync(0xffffffffu, ok)) break;
        trap_if(++cnt > SPIN_LIMIT);
        __nanosleep(100);
      }
#pragma unroll
      for (int y = 0; y < 2; y++) {
        float u = 0.f, v = 0.f;
#pragma unroll
        for (int i = 0; i < 7; i++) u += __uint_as_float((i & 1) ? t[y][i >> 1].z : t[y][i >> 1].x);
        u *= 1.f / 7;
#pragma unroll
        for (int i = 0; i < 7; i++) {
          const float d = __uint_as_float((i & 1) ? t[y][i >> 1].z : t[y][i >> 1].x) - u;
          v += fmaf(256.f * d, d, __uint_as_float((i & 1) ? t[y][i >> 1].w : t[y][i >> 1].y));
        }
        const float rs = rsqrtf(fmaxf(v, 0.f) * (1.f / FH) + 4e-5f);
        asm volatile("st.shared.v2.b32 [%0], {%1, %2};" :: "r"(sb + OFF_LN + (r + 32 * y) * 8), "r"(pack_bf16(rs, rs)), "r"(pack_bf16(-u, -u)) : "memory");
      }
      __syncwarp();
      if (lane == 0) mbar_arrive(bars + B_LN);
      __syncwarp();
    }
    if (warp_id == 0) {
      trap_if(sb & 1023);
      Ring g = {0, 1};
      int it = 0;
      uint32_t xph = 0;
      if (elect_one()) {
#pragma unroll 1
        for (;; it++) {
          const int item = items[it], type = item >> 12, b = item & 31, row = (((item >> 5) & 31) * 2 + rank) * 128;
          if (type >= T_ATT) break;
#pragma unroll 1
          for (int seg = 0; seg < (type == T_U ? 2 : 1); seg++) {
            const CUtensorMap* tA = &p.tm[seg ? TM_WSP : TM_XN];
            const CUtensorMap* tB = &p.tm[seg ? TM_Z2 : (type == T_Q ? TM_WQ : TM_WIN)];
            const int bchunk = b * 4 + (type == T_Z2 ? 28 : 0) + rank * 2;
            const unsigned* fl = seg ? &g_flags[F_Z2 + b * 32] : &g_flags[F_XN + (row >> 2)];
            const unsigned tgt = seg ? 16 : 128;
            int k = 0;
            if (it == 0 && seg == 0) {
              for (; k < 4; k++) {
                mbar_expect_tx(bars + B_GF + 8 * k, G_STAGE);
                tma_load_3d_mc(sb + k * G_STAGE + G_A + rank * 16384, tB, k * 64, bchunk, bars + B_GF + 8 * k);
              }
              g.ph ^= 1;
              asm volatile("st.volatile.shared.v4.u32 [%0], {%1, %2, %2, %2};" :: "r"(bars + B_TAG), "r"(__ldcg(&g_epoch) % 4095u + 1), "r"(0) : "memory");
            }
            if (seg || type != T_U) { flag_wait(fl, tgt); fence_async_global(); }
            for (int x = 0; x < k; x++) tma_load_2d(sb + x * G_STAGE, tA, x * 64, row, bars + B_GF + 8 * x);
#pragma unroll 1
            for (; k < (seg ? 32 : 16); k++) {
              if (k == 3 && type == T_U && seg == 0) { mbar_wait(bars + B_XF, xph); xph ^= 1; }
              mbar_wait(bars + B_GE + 8 * g.s, g.ph);
              const uint32_t st = sb + g.s * G_STAGE, fb = bars + B_GF + 8 * g.s;
              mbar_expect_tx(fb, G_STAGE);
              tma_load_2d(st, tA, k * 64, row, fb);
              tma_load_3d_mc(st + G_A + rank * 16384, tB, k * 64, bchunk, fb);
              ring_adv<4>(g);
            }
          }
        }
      }
      { const int e = __ffs(__ballot_sync(0xffffffffu, elect_one())) - 1; it = __shfl_sync(0xffffffffu, it, e); g.ph = __shfl_sync(0xffffffffu, g.ph, e); }
      const int n = ((items[it] >> 10) & 3) + 3;
      Ring kv = {0, 1};
      if (elect_one()) {
        int prow = 0;
        {
          const int im = items[it];
          tma_prefetch_2d(&p.tm[(im & 1) ? TM_V : TM_K], rank * 64, ((im >> 5) & 31) * SEQ + ((im & 7) >> 1) * 128);
        }
#pragma unroll 1
        for (int x = 0; x <= 32 * n; x++) {
          const int gb = x >> 1, t = gb >> 4;
          const int hrow = ((items[it + t] >> 5) & 31) * SEQ;
          const bool isv = (x & 1) || x == 32 * n;
          if (x != 1) {
            if (x == 0 || x == 2) mbar_wait(bars + B_GE + 4 * x, g.ph);
            if (x == 4) { mbar_wait(bars + B_XF, xph); xph ^= 1; }
            mbar_wait(bars + B_KE + 8 * kv.s, kv.ph);
            mbar_expect_tx(bars + B_KF + 8 * kv.s, KV_SLOT);
            tma_load_2d_mc(sb + kv.s * KV_SLOT + rank * 16384, &p.tm[isv ? TM_V : TM_K], rank * 64, isv ? prow : hrow + (gb & 15) * 128, bars + B_KF + 8 * kv.s);
            ring_adv<5>(kv);
          }
          {
            const int gp = gb + KV_PF, ip = items[it + (gp >> 4)];
            if (gp < 16 * n && ((gp ^ ip) & 7) == 0) tma_prefetch_2d(&p.tm[(x & 1) ? TM_V : TM_K], rank * 64, ((ip >> 5) & 31) * SEQ + (gp & 15) * 128);
          }
          if (x == 32 * n - 8) mbar_arrive(bars + B_GO);
          if (x & 1) prow = hrow + (gb & 15) * 128;
          if ((x & 31) == 11 && t + 1 < n) {
            const int tq = t + 1;
            const int im = items[it + tq], h = (im >> 5) & 31, m = (im & 31) * 2 + rank;
            const uint32_t qb = tq & 1;
            flag_wait(&g_flags[F_Q + m * 16 + (h >> 1)], 1);
            fence_async_global();
            mbar_wait(bars + B_QE + 8 * qb, ((tq - 1) >> 1) & 1);
            const uint32_t dst = sb + (qb ? OFF_Q1 : OFF_Q0), fb = bars + B_QF + 8 * qb;
            mbar_expect_tx(fb, 32768);
            tma_load_2d(dst, &p.tm[TM_Q], h * 128, m * 128, fb);
            tma_load_2d(dst + 16384, &p.tm[TM_Q], h * 128 + 64, m * 128, fb);
          }
        }
      }
      __syncwarp();
      it += n;
      uint32_t ready = 0;
      auto wait_head = [&](int h) {
        if ((ready >> h) & 1) return;
        uint32_t cnt = 0;
        while (true) {
          asm volatile("ld.acquire.cta.shared.u32 %0, [%1];" : "=r"(ready) : "r"(bars + B_RDY) : "memory");
          if ((ready >> h) & 1) break;
          trap_if(++cnt > SPIN_LIMIT * 8);
          __nanosleep(20);
        }
        fence_async_global();
      };
      int item = items[it];
      if ((item >> 12) == T_SA) {
        const int m = ((item >> 5) & 31) * 2 + rank, b = item & 31;
        Ring dr = kv;
        wait_head(0);
#pragma unroll 1
        for (int i = 0; i < 28 + 2 * SA_HEADS; i++) {
          {
            const bool so = i >= 28;
            const int k = so ? i - 28 : i;
            if (so) wait_head(k >> 1);
            if (elect_one()) {
              if (i < 4) { for (int x = 0; x < (SA_ROT ? (0x1022 >> (4 * i)) & 3 : (i ? 0 : 5)); x++) { mbar_wait(bars + B_KE + 8 * dr.s, dr.ph); ring_adv<5>(dr); } }
              if (i == 2) { mbar_wait(bars + B_XF, xph); xph ^= 1; }
              mbar_wait(bars + B_GE + 8 * g.s, g.ph);
              const uint32_t st = sb + ((g.s + SA_ROT) & 3) * G_STAGE, fb = bars + B_GF + 8 * g.s;
              mbar_expect_tx(fb, G_STAGE);
              tma_load_2d(st, &p.tm[so ? TM_O : TM_U], k * 64, m * 128, fb);
              tma_load_3d_mc(st + G_A + rank * 16384, &p.tm[so ? TM_WO : TM_WOUT], k * 64, b * 4 + rank * 2, fb);
            }
            ring_adv<4>(g);
          }
          const int ip = i + OUT_PF;
          if (ip < 28 + 2 * SA_HEADS && elect_one()) {
            const bool so = ip >= 28;
            const int k = so ? ip - 28 : ip;
            if ((ip & 3) == b && (!so || ((ready >> (k >> 1)) & 1))) tma_prefetch_2d(&p.tm[so ? TM_O : TM_U], k * 64, m * 128);
            if ((ip & 7) == (m >> 1)) tma_prefetch_3d(&p.tm[so ? TM_WO : TM_WOUT], k * 64, b * 4 + rank * 2);
          }
          __syncwarp();
        }
        item = items[++it];
      }
      if ((item >> 12) == T_FIN) {
        const bool own = item & 4;
        const int m = ((item >> 5) & 31) * 2 + rank, col = (item & 3) * 256 + (own ? 128 : 0);
        uint32_t ps = own ? FIN_SLOT0 : kv.s;
#pragma unroll 1
        for (int i = 2 * SA_HEADS; i <= 2 * NH; i++) {
          const bool extra = i == 2 * NH - FIN_PREP;
          if (extra && own) continue;
          const int k = i > 2 * NH - FIN_PREP ? i - 1 : i;
          if (!extra) wait_head(k >> 1);
          if (elect_one()) {
            if (i == 2 * SA_HEADS) {
              for (int y = k; y < k + 4; y++) if ((ready >> (y >> 1)) & 1) tma_prefetch_2d(&p.tm[TM_O], y * 64, m * 128);
            }
            if (own && i < 2 * SA_HEADS + 5) {
              const uint32_t s0 = ((0x22100u >> (4 * ps)) - SA_ROT) & 3, s1 = ((0x32110u >> (4 * ps)) - SA_ROT) & 3;
              mbar_wait(bars + B_GE + 8 * s0, g.ph ^ (s0 < g.s)); mbar_wait(bars + B_GE + 8 * s1, g.ph ^ (s1 < g.s));
            }
            if (extra) { flag_wait(&g_flags[F_S + m * 4 + (item & 3)], 2); fence_async_global(); }
            mbar_wait(bars + B_KE + 8 * kv.s, kv.ph);
            const uint32_t dst = sb + ps * KV_SLOT, fb = bars + B_KF + 8 * kv.s;
            if (++ps == 5) ps = 0;
            mbar_expect_tx(fb, KV_SLOT);
            if (!extra) {
              tma_load_2d(dst, &p.tm[TM_O], k * 64, m * 128, fb);
              tma_load_2d_mc(dst + 16384 + rank * 8192, &p.tm[TM_WO64], col + rank * 64, k * 64, fb);
            } else {
              tma_load_2d(dst, &p.tm[TM_SA], col, m * 128, fb);
              tma_load_2d(dst + 16384, &p.tm[TM_SA], col + 64, m * 128, fb);
            }
            ring_adv<5>(kv);
          }
          __syncwarp();
        }
      }
      unsigned last = 0;
      if (lane == 0 && (item >> 12) == T_FIN) mbar_wait_sleep(bars + B_XR, 0, 100);
      if (lane == 0) { __threadfence(); last = atomicInc(&g_done, gridDim.x - 1) == gridDim.x - 1; }
      last = __shfl_sync(0xffffffffu, last, 0);
      if (last) {
        for (int i = lane; i < F_TOTAL / 4; i += 32) reinterpret_cast<uint4*>(g_flags)[i] = make_uint4(0, 0, 0, 0);
        if (lane == 0) g_epoch = g_epoch + 1;
      }
    } else if (warp_id == 1) {
      if (elect_one()) {
        uint32_t ph = 0;
        int t = 0;
        unsigned* fq = nullptr;
        const bool z = (items[0] >> 12) == T_Z2;
#pragma unroll 1
        for (int it = 0;; it++) {
          const int ii = (z && it < 2) ? it ^ 1 : it;
          const int item = items[ii], type = item >> 12, a = (item >> 5) & 31, b = item & 31;
          if (type == T_END) break;
          const int nt = items[ii + 1] >> 12;
          int row = (a * 2 + rank) * 128, col = b * 256;
          unsigned* f = &g_flags[F_S + (a * 2 + rank) * 4 + b];
          int tm = TS_G, npair = 2;
          bool quad = false;
          uint32_t src = sb + OFF_Q0;
          if (type == T_Z2) { tm = TS_Z2; f = &g_flags[F_Z2 + b * 32]; }
          else if (type == T_Q) { tm = TS_Q; f = &g_flags[F_Q + (a * 2 + rank) * 16 + b]; if (z || nt >= T_ATT) { npair = 0; quad = true; } }
          else if (type == T_U) { tm = TS_U; f = &g_flags[F_U + (a * 2 + rank) * 32]; npair = 0; quad = true; }
          else if (type == T_ATT) { tm = TS_O; f = &g_flags[F_O + (b * 2 + rank) * 32 + a]; npair = 1; row = (b * 2 + rank) * 128; col = a * 128; if (t & 1) src = sb + OFF_Q1; }
          else if (type == T_FIN) npair = 1;
          auto load_fin = [&](int fi, int tmi, uint32_t qb) {
            const int fc = (fi & 3) * 256 + ((fi & 4) ? 128 : 0), fr = (((fi >> 5) & 31) * 2 + rank) * 128;
            mbar_expect_tx(bars + B_QF + 8 * qb, 32768);
            tma_load_2d(sb + (qb ? OFF_Q1 : OFF_Q0), &p.tm[tmi], fc, fr, bars + B_QF + 8 * qb);
            tma_load_2d(sb + (qb ? OFF_Q1 : OFF_Q0) + 16384, &p.tm[tmi], fc + 64, fr, bars + B_QF + 8 * qb);
          };
          if (type == T_ATT && nt == T_FIN) load_fin(items[ii + 1], TM_X, (t & 1) ^ 1);
          if (type == T_FIN) {
            if (!(item & 4)) { flag_wait(&g_flags[F_S + (a * 2 + rank) * 4 + (b & 3)], 1); fence_async_global(); load_fin(item, TM_G, (t & 1) ^ 1); }
            mbar_arrive(bars + B_XR);
          }
#pragma unroll 1
          for (int op = 0; op < npair + quad; op++) {
            const bool q = op == npair;
            const int c0 = (q || type == T_SA) ? col : col + op * 128;
            mbar_wait_sleep(bars + B_STG, ph, (type == T_ATT && nt == T_ATT) ? SW_ATT : SW_NS);
            if (type == T_FIN) break;
            ph ^= 1;
            fence_async_smem();
            if (type == T_SA && op == 1) { tm = TS_SA; load_fin(items[ii + 1], TM_X, 1); }
            int c1 = c0;
            if (q) {
              const CUtensorMap* tb = &p.tm[type == T_U ? TM_U : TM_Q];
              const bool pre = nt == T_ATT;
              tma_store_2d(tb, sb + (pre ? 2 * G_STAGE : OFF_Q1), c0 + (pre ? 0 : 128), row);
              tma_store_2d(tb, sb + (pre ? 3 * G_STAGE : OFF_Q1 + 16384), c0 + (pre ? 64 : 192), row);
              bulk_commit();
              bulk_wait_read<0>();
              mbar_arrive_cta(bars + B_XF, 0); mbar_arrive_cta(bars + B_XF, 1);
              if (pre) { src = sb + OFF_Q1; c1 += 128; }
            }
            if (nt != T_END) {
#pragma unroll 1
              for (int r = 0; r < 256; r += ST_ROWS) {
                tma_store_2d(&p.tm[tm], src + r * 128, c1 + (r >> 7) * 64, row + (r & 127));
                bulk_commit();
                bulk_wait_read<ST_FLY>();
              }
            }
            bulk_wait_read<0>();
            mbar_arrive(bars + B_FREE);
            if (type == T_ATT && (t & 1) && (nt == T_SA || (items[ii + 2] >> 12) == T_SA)) { mbar_arrive_cta(bars + B_XF, 0); mbar_arrive_cta(bars + B_XF, 1); }
            if (type == T_ATT) mbar_arrive(bars + B_QE + 8 * (t & 1));
            else if (nt == T_ATT) mbar_arrive(bars + B_QE + 8);
            if (z && it == 0) { fq = f; continue; }
            if (op + 1 >= npair || type == T_SA) {
              bulk_wait<0>();
              red_release(f, 1);
              if (type == T_Z2) red_release(fq, 1);
            }
          }
          if (type == T_ATT) t++;
          else if (t == 0 && (items[it + 1] >> 12) < T_ATT && (items[it + 2] >> 12) == T_ATT) {
            const int im = items[it + 2], h = (im >> 5) & 31, m = (im & 31) * 2 + rank;
            flag_wait(&g_flags[F_Q + m * 16 + (h >> 1)], 1);
            fence_async_global();
            mbar_expect_tx(bars + B_QF, 32768);
            tma_load_2d(sb + OFF_Q0, &p.tm[TM_Q], h * 128, m * 128, bars + B_QF);
            tma_load_2d(sb + OFF_Q0 + 16384, &p.tm[TM_Q], h * 128 + 64, m * 128, bars + B_QF);
          }
        }
      }
      __syncwarp();
    } else if (warp_id == 2) {
      int it = 0;
      while ((items[it] >> 12) <= T_ATT) it++;
      if ((items[it] >> 12) != T_END) {
        const bool sa = (items[it] >> 12) == T_SA;
        const int m = ((items[it] >> 5) & 31) * 2 + rank;
        if (lane == 0) {
          mbar_wait_sleep(bars + B_GO, 0, 500);
          if (sa) {
            const int b = items[it] & 3;
            flag_wait(&g_flags[F_U + m * 32], 7);
            fence_async_global();
            for (int y = b; y < OUT_PF; y += 4) tma_prefetch_2d(&p.tm[TM_U], y * 64, m * 128);
            tma_prefetch_3d(&p.tm[TM_WOUT], (m >> 1) * 64, b * 4 + rank * 2);
          }
          if (!sa) for (int y = m * 4 + (items[it] & 3); y < 16 * (NH - SA_HEADS); y += 64) tma_prefetch_3d(&p.tm[TM_WO], (2 * SA_HEADS + (y >> 3)) * 64, (y & 7) * 2);
        }
        __syncwarp();
        uint32_t cnt = 0;
        while (true) {
          const uint32_t r = __ballot_sync(0xffffffffu, ld_acquire(&g_flags[F_O + m * 32 + lane]) != 0);
          if (lane == 0) asm volatile("st.release.cta.shared.u32 [%0], %1;" :: "r"(bars + B_RDY), "r"(r) : "memory");
          if (r == ~0u) break;
          trap_if(++cnt > SPIN_LIMIT);
          __nanosleep(r >> 28 ? POLL_NS : 300);
        }
        if (lane == 0) mbar_arrive(bars + B_XR);
      }
      __syncwarp();
    }
    cluster_sync_relaxed();
  } else {
    Cons c;
    c.sb = sb; c.warp = warp_id - 4; c.g = {0, 0}; c.fph = 1; c.rot = 0;
    if (gw < SEQ / 2) {
      float f[2][32], rs[2];
#pragma unroll
      for (int rr = 0; rr < 2; rr++) {
#pragma unroll
        for (int i = 0; i < 4; i++) {
          const uint4 v = xv[rr][i];
          f[rr][8 * i + 0] = bf_lo(v.x); f[rr][8 * i + 1] = bf_hi(v.x); f[rr][8 * i + 2] = bf_lo(v.y); f[rr][8 * i + 3] = bf_hi(v.y);
          f[rr][8 * i + 4] = bf_lo(v.z); f[rr][8 * i + 5] = bf_hi(v.z); f[rr][8 * i + 6] = bf_lo(v.w); f[rr][8 * i + 7] = bf_hi(v.w);
        }
        float s = 0.f;
#pragma unroll
        for (int i = 0; i < 32; i++) s += f[rr][i];
#pragma unroll
        for (int o = 16; o; o >>= 1) s += __shfl_xor_sync(0xffffffffu, s, o);
        const float mean = s * (1.f / DM);
        float q = 0.f;
#pragma unroll
        for (int i = 0; i < 32; i++) { f[rr][i] -= mean; q = fmaf(f[rr][i], f[rr][i], q); }
#pragma unroll
        for (int o = 16; o; o >>= 1) q += __shfl_xor_sync(0xffffffffu, q, o);
        rs[rr] = rsqrtf(q * (1.f / DM) + 1e-5f);
      }
      uint4* dst = reinterpret_cast<uint4*>(g_xn + (size_t)gw * 2 * DM) + lane;
#pragma unroll
      for (int rr = 0; rr < 2; rr++) {
        const float r = rs[rr];
#pragma unroll
        for (int i = 0; i < 4; i++) {
          const float* y = &f[rr][8 * i];
          dst[rr * 128 + i * 32] = make_uint4(pack_bf16(y[0] * r, y[1] * r), pack_bf16(y[2] * r, y[3] * r), pack_bf16(y[4] * r, y[5] * r), pack_bf16(y[6] * r, y[7] * r));
        }
      }
      __syncwarp();
      if (lane == 0) red_release(&g_flags[F_XN + (gw >> 6) * 32], 2);
    }
    asm volatile("setmaxnreg.inc.sync.aligned.u32 232;");
    asm volatile("barrier.cluster.wait.acquire.aligned;" ::: "memory");
#define stg (c.sb + OFF_Q0 + c.warp * 2048)
    int natt = 0;
    int it = 0;
    uint32_t held[64];
#pragma unroll
    for (int i = 0; i < 64; i++) held[i] = 0u;
    Shadow sh = {0, 0};
    float facc[64];
#pragma unroll 1
    while (true) {
      const int item = get_item(p, it), type = item >> 12, a = (item >> 5) & 31;
      c.warp = fresh_warp();
      if (type == T_ATT) {
        const int n = ((item >> 10) & 3) + 3;
        att_run(c, p, it, n);
#pragma unroll
        for (int i = 0; i < 64; i++) held[i] = 0u;
        natt = n;
        it += n;
        c.rot = SA_ROT;
        if ((get_item(p, it) >> 12) == T_SA) continue;
#pragma unroll
        for (int i = 0; i < 64; i++) facc[i] = 0.f;
        break;
      }
      float acc[128];
      const bool sa = type == T_SA;
      bool more = type >= T_U;
      int nsteps = sa ? 28 : 16;
      const bool direct = sh.act == 2 || (get_item(p, it + 1) >> 12) >= T_ATT;
      uint32_t bias0 = 0, bias1 = 0;
#pragma unroll 1
      while (true) {
        gemm_seg(acc, held, c, p, sh, nsteps);
        if (type == T_Q) {
#pragma unroll
          for (int i = 0; i < 128; i++) acc[i] *= SM_C;
        }
        if (!more && direct) break;
#pragma unroll
        for (int i = 0; i < 64; i++) held[i] = pack_bf16(acc[2 * i], acc[2 * i + 1]);
        if (!more) break;
        more = false;
        nsteps = sa ? 2 * SA_HEADS : 32;
        sh.act = sa ? 3 : 1;
        if (sa) {
          sh.store = 3;
        } else {
          const int row0 = (a * 2 + rank) * 128 + c.warp * 16 + (lane_id() >> 2);
          asm volatile("ld.global.nc.u16 %0, [%1];" : "=r"(bias0) : "l"(p.b_sp + row0));
          asm volatile("ld.global.nc.u16 %0, [%1];" : "=r"(bias1) : "l"(p.b_sp + row0 + 8));
        }
      }
      c.warp = fresh_warp();
      if (direct) {
        const bool pre = !sa && sh.store != 2;
        const uint32_t hb0 = bf2_mul(bias0 * 0x10001u, BF2_HALF), hb1 = bf2_mul(bias1 * 0x10001u, BF2_HALF);
        stage_acquire(c);
#pragma unroll
        for (int h = 0; h < 2; h++) {
          uint32_t pk[32];
#pragma unroll
          for (int i = 0; i < 32; i++) pk[i] = pack_bf16(acc[64 * h + 2 * i], acc[64 * h + 2 * i + 1]);
          if (type == T_U) {
#pragma unroll
            for (int i = 0; i < 32; i++) pk[i] = bf2_mul(bf2_fma(pk[i], BF2_HALF, (i & 1) ? hb1 : hb0), held[32 * h + i]);
          }
          if (h) named_sync(5);
          stage_chunks<2>(sb + (h ? OFF_Q1 : (pre ? 2 * G_STAGE : OFF_Q0)) + c.warp * 2048, (!h && pre) ? G_STAGE : 16384, pk);
          if (sa) break;
        }
        stage_commit(c);
        if (sa) {
#pragma unroll
          for (int i = 0; i < 64; i++) facc[i] = acc[64 + i];
          it++;
          break;
        }
      } else if (type == T_Q) {
        sh.store = 1;
      } else {
        sh.act = 2;
      }
      it++;
    }
    const int fin = get_item(p, it);
    if ((fin >> 12) == T_FIN) {
      c.warp = fresh_warp();
      const bool own = fin & 4;
      Ring kv = {(uint32_t)(32 * natt) % 5, ((uint32_t)(32 * natt) / 5) & 1};
      uint32_t prev = 0, ps = own ? FIN_SLOT0 : kv.s;
      fence_regs(facc);
      auto fin_steps = [&](int k0, int k1) {
#pragma unroll 1
        for (int k = k0; k < k1; k++) {
          mbar_spin(bars + B_KF + 8 * kv.s, kv.ph);
          const uint32_t st = ((c.sb & 0x3FFFF) >> 4) + ps * (KV_SLOT >> 4);
          if (++ps == 5) ps = 0;
          const uint32_t da = st + (c.warp >> 2) * 512 + (1u << 16), db = st + 1024 + ((8192u >> 4) << 16);
          wgmma_fence();
#pragma unroll
          for (int kk = 0; kk < 4; kk++) wgmma_m64n128k16_ss_tb1(facc, DESC_HI | (da + kk * 2), DESC_HI | (db + kk * 128), 1);
          wgmma_commit();
          wgmma_wait<1>();
          if (k > 2 * SA_HEADS) release_slot(c, prev);
          prev = bars + B_KE + 8 * kv.s;
          ring_adv<5>(kv);
        }
      };
      const int kp = (SCOUT && own && ((fin >> 5) & 31) == 7) ? 2 * SA_HEADS + SCOUT : 2 * NH - FIN_PREP - (own ? OWN_OFF : 0);
      fin_steps(2 * SA_HEADS, kp);
      const uint32_t ln = lane_id(), xb = own ? 1 : natt & 1;
      const uint32_t lo = c.warp * 2048 + ((ln & 15) << 7);
      uint32_t xs[32], ss[32];
      auto load_tile = [&](uint32_t base, uint32_t* d) {
#pragma unroll
        for (int i = 0; i < 8; i++) ldmatrix_x4(base + lo + (i >> 2) * 16384 + (((2 * (i & 3) + (ln >> 4)) ^ (ln & 7)) << 4), d[4 * i], d[4 * i + 1], d[4 * i + 2], d[4 * i + 3]);
      };
      const uint32_t xa = sb + (xb ? OFF_Q1 : OFF_Q0);
      mbar_spin(bars + B_QF + 8 * xb, ((natt + 1 - xb) >> 1) & 1);
      load_tile(xa, xs);
#pragma unroll
      for (int i = 0; i < 32; i++) ss[i] = 0u;
      if (!own) {
        mbar_spin(bars + B_QF + 8 * (xb ^ 1), ((natt + xb) >> 1) & 1);
        load_tile(sb + (xb ? OFF_Q0 : OFF_Q1), held + 32);
        mbar_spin(bars + B_KF + 8 * kv.s, kv.ph);
        load_tile(sb + ps * KV_SLOT, ss);
        wg_any(c.warp >= 4, false);
        release_slot(c, bars + B_KE + 8 * kv.s);
        if (++ps == 5) ps = 0;
        ring_adv<5>(kv);
      }
      float gf[64], rf[64];
#pragma unroll
      for (int i = 0; i < 32; i++) {
        const uint32_t gt = bf2_mul(held[32 + i], BF2_HALF);
        gf[2 * i] = bf_lo(gt); gf[2 * i + 1] = bf_hi(gt);
        rf[2 * i] = fmaf(bf_lo(ss[i]), gf[2 * i], bf_lo(xs[i])); rf[2 * i + 1] = fmaf(bf_hi(ss[i]), gf[2 * i + 1], bf_hi(xs[i]));
      }
      fence_regs(gf); fence_regs(rf);
      fin_steps(kp, 2 * NH);
      wgmma_wait<0>();
      fence_regs(facc);
#pragma unroll
      for (int i = 0; i < 32; i++) xs[i] = pack_bf16(fmaf(facc[2 * i], gf[2 * i], rf[2 * i]), fmaf(facc[2 * i + 1], gf[2 * i + 1], rf[2 * i + 1]));
      __syncwarp();
      stage_chunks<2>(xa + c.warp * 2048, 16384, xs);
      fence_async_smem();
      __syncwarp();
      if (elect_one()) {
        const int col = (fin & 3) * 256 + (own ? 128 : 0), row = (((fin >> 5) & 31) * 2 + rank) * 128 + c.warp * 16;
        tma_store_2d(&p.tm[TS_OUT], xa + c.warp * 2048, col, row);
        tma_store_2d(&p.tm[TS_OUT], xa + c.warp * 2048 + 16384, col + 64, row);
        bulk_commit();
        mbar_arrive(bars + B_STG);
        bulk_wait_read<0>();
      }
    }
    __syncwarp();
    cluster_sync_relaxed();
  }
}

typedef CUresult (*PFN_encodeTiled)(CUtensorMap*, CUtensorMapDataType, cuuint32_t, void*, const cuuint64_t*, const cuuint64_t*, const cuuint32_t*, const cuuint32_t*,
                                    CUtensorMapInterleave, CUtensorMapSwizzle, CUtensorMapL2promotion, CUtensorMapFloatOOBfill);
static PFN_encodeTiled s_encode = nullptr;
static void tm_2d(CUtensorMap* tm, const void* ptr, uint64_t rows, uint64_t cols, uint32_t box_rows) {
  cuuint64_t dims[2] = {cols, rows}; cuuint64_t strides[1] = {cols * 2}; cuuint32_t box[2] = {64, box_rows}; cuuint32_t es[2] = {1, 1};
  CUresult r = s_encode(tm, CU_TENSOR_MAP_DATA_TYPE_BFLOAT16, 2, (void*)ptr, dims, strides, box, es, CU_TENSOR_MAP_INTERLEAVE_NONE,
                        CU_TENSOR_MAP_SWIZZLE_128B, CU_TENSOR_MAP_L2_PROMOTION_L2_256B, CU_TENSOR_MAP_FLOAT_OOB_FILL_NONE);
  if (r != CUDA_SUCCESS) fprintf(stderr, "tensor map encode failed (%d)\n", (int)r);
}
static void tm_3d(CUtensorMap* tm, const void* ptr, uint64_t rows, uint64_t cols) {
  cuuint64_t dims[3] = {64, rows, cols / 64}; cuuint64_t strides[2] = {cols * 2, 128}; cuuint32_t box[3] = {64, 64, 2}; cuuint32_t es[3] = {1, 1, 1};
  CUresult r = s_encode(tm, CU_TENSOR_MAP_DATA_TYPE_BFLOAT16, 3, (void*)ptr, dims, strides, box, es, CU_TENSOR_MAP_INTERLEAVE_NONE,
                        CU_TENSOR_MAP_SWIZZLE_128B, CU_TENSOR_MAP_L2_PROMOTION_L2_256B, CU_TENSOR_MAP_FLOAT_OOB_FILL_NONE);
  if (r != CUDA_SUCCESS) fprintf(stderr, "tensor map encode failed (%d)\n", (int)r);
}
static inline uint16_t mk(int type, int a, int b) { return (uint16_t)(type << 12 | a << 5 | b); }

static void build_schedule(Params& P) {
  int cnt[NCLUSTER];
  for (int c = 0; c < NCLUSTER; c++) { cnt[c] = 0; for (int i = 0; i < MAXI; i++) P.items[c][i] = mk(T_END, 0, 0); }
  auto phys = [](int c) { return c == 64 ? 9 : c == 65 ? 17 : c == 9 ? 64 : c == 17 ? 65 : c; };
  auto push = [&](int c, uint16_t v) { P.items[phys(c)][cnt[c]++] = v; };
  int natt[NCLUSTER], nq[NCLUSTER];
  for (int c = 0; c < NCLUSTER; c++) { natt[c] = c < 32 ? 3 : (c < 56 ? 5 : (c < 62 ? 4 : (c < 64 ? 3 : 5))); nq[c] = c < 56 ? 1 : (c < 62 ? 7 : (c < 64 ? 9 : 6)); }
  for (int c = 0; c < 56; c++) push(c, mk(T_Z2, c % 8, c / 8));
  int qi = 0;
  for (int slot = 0; slot < 9; slot++)
    for (int c = NCLUSTER - 1; c >= 0; c--) {
      const int first = c < 56 ? 1 : 0;
      if (slot >= first && slot < first + nq[c]) { push(c, mk(T_Q, qi % 8, qi / 8)); qi++; }
    }
  for (int c = 0; c < 56; c++) push(c, mk(T_U, c % 8, c / 8));
  int ai = 0;
  for (int slot = 0; slot < 5; slot++)
    for (int c = 0; c < NCLUSTER; c++) {
      const int first = c < 32 ? 0 : 5 - natt[c];
      if (slot >= first && slot < first + natt[c]) { push(c, mk(T_ATT, ai / 8, ai % 8) | (natt[c] - 3) << 10); ai++; }
    }
  for (int c = 0; c < 32; c++) push(c, mk(T_SA, c % 8, c / 8));
  for (int c = 0; c < 64; c++) push(c, mk(T_FIN, c % 8, (c / 8) % 4 | (c < 32 ? 4 : 0)));
  if (qi != 128 || ai != 256) fprintf(stderr, "bad schedule %d %d\n", qi, ai);
}

static Params s_params;
extern "C" void kernel_launch(void* const* d_in, const int* in_sizes, int n_in, void* d_out, int out_size) {
  (void)in_sizes; (void)n_in; (void)out_size;
  if (!s_encode) {
    void* fn = nullptr; cudaDriverEntryPointQueryResult qr;
    cudaGetDriverEntryPoint("cuTensorMapEncodeTiled", &fn, cudaEnableDefault, &qr);
    s_encode = (PFN_encodeTiled)fn;
    cudaFuncSetAttribute(fused_kernel, cudaFuncAttributeMaxDynamicSharedMemorySize, SMEM_BYTES);
    build_schedule(s_params);
  }
  Params& P = s_params;
  void *xn, *q, *o, *z2, *u, *gg, *sa;
  cudaGetSymbolAddress(&gg, g_g); cudaGetSymbolAddress(&sa, g_sa);
  cudaGetSymbolAddress(&xn, g_xn); cudaGetSymbolAddress(&q, g_q); cudaGetSymbolAddress(&o, g_o);
  cudaGetSymbolAddress(&z2, g_z2); cudaGetSymbolAddress(&u, g_u);
  tm_2d(&P.tm[TM_XN], xn, SEQ, DM, 128); tm_2d(&P.tm[TM_WSP], d_in[7], SEQ, SEQ, 128); tm_2d(&P.tm[TM_U], u, SEQ, FH, 128);
  tm_2d(&P.tm[TM_O], o, SEQ, HD, 128); tm_2d(&P.tm[TM_Q], q, SEQ, HD, 128); tm_2d(&P.tm[TM_X], d_in[0], SEQ, DM, 128);
  tm_2d(&P.tm[TM_K], d_in[1], NH * SEQ, 128, 128); tm_2d(&P.tm[TM_V], d_in[2], NH * SEQ, 128, 128);
  tm_2d(&P.tm[TM_SA], sa, SEQ, DM, 128); tm_2d(&P.tm[TM_G], gg, SEQ, DM, 128); tm_2d(&P.tm[TM_WO64], d_in[4], HD, DM, 64);
  tm_3d(&P.tm[TM_WIN], d_in[6], DM, FF); tm_3d(&P.tm[TM_WQ], d_in[3], DM, HD); tm_3d(&P.tm[TM_Z2], z2, SEQ, FH);
  tm_3d(&P.tm[TM_WOUT], d_in[9], FH, DM); tm_3d(&P.tm[TM_WO], d_in[4], HD, DM);
  tm_2d(&P.tm[TS_Q], q, SEQ, HD, ST_ROWS); tm_2d(&P.tm[TS_O], o, SEQ, HD, ST_ROWS); tm_2d(&P.tm[TS_Z2], z2, SEQ, FH, ST_ROWS); tm_2d(&P.tm[TS_U], u, SEQ, FH, ST_ROWS);
  tm_2d(&P.tm[TS_SA], sa, SEQ, DM, ST_ROWS); tm_2d(&P.tm[TS_G], gg, SEQ, DM, ST_ROWS); tm_2d(&P.tm[TS_OUT], d_out, SEQ, DM, 16);
  P.x = (const bf16*)d_in[0]; P.b_sp = (const bf16*)d_in[8];
  fused_kernel<<<2 * NCLUSTER, 384, SMEM_BYTES, cudaStreamPerThread>>>(P);
}
```

```cpp
#include <cuda_runtime.h>
#include <cuda_bf16.h>
#include <cuda.h>
#include <stdint.h>
#include <stdio.h>

typedef __nv_bfloat16 bf16;

constexpr int SEQ = 2048, DM = 1024, NH = 32, HD = 4096, FF = 3584, FH = 1792;

__device__ __align__(1024) bf16 g_xn[SEQ * DM];
__device__ __align__(1024) bf16 g_q[SEQ * HD];
__device__ __align__(1024) bf16 g_o[SEQ * HD];
__device__ __align__(1024) bf16 g_z2[SEQ * FH];
__device__ __align__(1024) bf16 g_u[SEQ * FH];
__device__ __align__(1024) uint2 g_stats[SEQ * 8];
__device__ __align__(1024) bf16 g_g[SEQ * DM];
__device__ __align__(1024) bf16 g_sa[SEQ * DM];
constexpr int F_XN = 0;
constexpr int F_Z2 = 512;
constexpr int F_Q = 768;
constexpr int F_U = 1024;
constexpr int F_O = 1536;
constexpr int F_S = 2048;
constexpr int F_TOTAL = 2112;
__device__ __align__(1024) unsigned g_flags[F_TOTAL];
__device__ unsigned g_done;
__device__ unsigned g_epoch;

__device__ __forceinline__ uint32_t smem_u32(const void* p) { return (uint32_t)__cvta_generic_to_shared(p); }
__device__ __forceinline__ void mbar_init(uint32_t bar, uint32_t cnt) { asm volatile("mbarrier.init.shared::cta.b64 [%0], %1;" :: "r"(bar), "r"(cnt)); }
__device__ __forceinline__ void mbar_expect_tx(uint32_t bar, uint32_t bytes) { asm volatile("mbarrier.arrive.expect_tx.shared::cta.b64 _, [%0], %1;" :: "r"(bar), "r"(bytes) : "memory"); }
__device__ __forceinline__ void mbar_arrive(uint32_t bar) { asm volatile("mbarrier.arrive.shared::cta.b64 _, [%0];" :: "r"(bar) : "memory"); }
__device__ __forceinline__ void mbar_arrive_cta(uint32_t bar, uint32_t cta) {
  asm volatile("{\n.reg .b32 ra;\nmapa.shared::cluster.u32 ra, %0, %1;\nmbarrier.arrive.shared::cluster.b64 _, [ra];\n}" :: "r"(bar), "r"(cta) : "memory");
}
__device__ __forceinline__ bool mbar_test(uint32_t bar, uint32_t parity) {
  uint32_t ok;
  asm volatile("{\n.reg .pred P1;\nmbarrier.test_wait.parity.shared::cta.b64 P1, [%1], %2;\nselp.u32 %0, 1, 0, P1;\n}" : "=r"(ok) : "r"(bar), "r"(parity) : "memory");
  return ok;
}
constexpr uint32_t SPIN_LIMIT = 1u << 22;
__device__ __forceinline__ void trap_if(bool c) { asm volatile("{\n.reg .pred P;\nsetp.ne.u32 P, %0, 0;\n@P trap;\n}" :: "r"((uint32_t)c)); }
__device__ __forceinline__ void mbar_wait(uint32_t bar, uint32_t parity) {
  asm volatile("{\n.reg .pred P1;\n.reg .u32 n;\nmbarrier.try_wait.parity.shared::cta.b64 P1, [%0], %1;\n@P1 bra DONE;\nmov.u32 n, 0;\n"
               "LOOP:\nmbarrier.try_wait.parity.shared::cta.b64 P1, [%0], %1;\n@P1 bra DONE;\nadd.u32 n, n, 1;\nsetp.gt.u32 P1, n, %2;\n@P1 trap;\nbra LOOP;\nDONE:\n}"
               :: "r"(bar), "r"(parity), "n"(SPIN_LIMIT) : "memory");
}
__device__ __forceinline__ void mbar_spin(uint32_t bar, uint32_t parity) {
  asm volatile("{\n.reg .pred P1;\nLOOP:\nmbarrier.try_wait.parity.shared::cta.b64 P1, [%0], %1;\n@!P1 bra LOOP;\n}" :: "r"(bar), "r"(parity) : "memory");
}
__device__ __forceinline__ void mbar_wait_sleep(uint32_t bar, uint32_t parity, uint32_t ns) {
  uint32_t n = 0;
  while (!mbar_test(bar, parity)) { trap_if(++n > SPIN_LIMIT * 4); __nanosleep(ns); }
}
__device__ __forceinline__ void tma_load_2d(uint32_t dst, const CUtensorMap* tm, int c0, int c1, uint32_t bar) {
  asm volatile("cp.async.bulk.tensor.2d.shared::cluster.global.mbarrier::complete_tx::bytes [%0], [%1, {%3, %4}], [%2];"
    :: "r"(dst), "l"(tm), "r"(bar), "r"(c0), "r"(c1) : "memory");
}
__device__ __forceinline__ void tma_load_2d_mc(uint32_t dst, const CUtensorMap* tm, int c0, int c1, uint32_t bar) {
  asm volatile("cp.async.bulk.tensor.2d.shared::cluster.global.mbarrier::complete_tx::bytes.multicast::cluster [%0], [%1, {%3, %4}], [%2], %5;"
    :: "r"(dst), "l"(tm), "r"(bar), "r"(c0), "r"(c1), "h"((uint16_t)3) : "memory");
}
__device__ __forceinline__ void tma_prefetch_2d(const CUtensorMap* tm, int c0, int c1) {
  asm volatile("cp.async.bulk.prefetch.tensor.2d.L2.global [%0, {%1, %2}];" :: "l"(tm), "r"(c0), "r"(c1) : "memory");
}
__device__ __forceinline__ void tma_prefetch_3d(const CUtensorMap* tm, int c1, int c2) {
  asm volatile("cp.async.bulk.prefetch.tensor.3d.L2.global [%0, {%1, %2, %3}];" :: "l"(tm), "r"(0), "r"(c1), "r"(c2) : "memory");
}
__device__ __forceinline__ void tma_load_3d_mc(uint32_t dst, const CUtensorMap* tm, int c1, int c2, uint32_t bar) {
  asm volatile("cp.async.bulk.tensor.3d.shared::cluster.global.mbarrier::complete_tx::bytes.multicast::cluster [%0], [%1, {%3, %4, %5}], [%2], %6;"
    :: "r"(dst), "l"(tm), "r"(bar), "r"(0), "r"(c1), "r"(c2), "h"((uint16_t)3) : "memory");
}
__device__ __forceinline__ void tma_store_2d(const CUtensorMap* tm, uint32_t src, int c0, int c1) {
  asm volatile("cp.async.bulk.tensor.2d.global.shared::cta.bulk_group [%0, {%2, %3}], [%1];" :: "l"(tm), "r"(src), "r"(c0), "r"(c1) : "memory");
}
__device__ __forceinline__ void bulk_commit() { asm volatile("cp.async.bulk.commit_group;" ::: "memory"); }
template <int N> __device__ __forceinline__ void bulk_wait_read() { asm volatile("cp.async.bulk.wait_group.read %0;" :: "n"(N) : "memory"); }
template <int N> __device__ __forceinline__ void bulk_wait() { asm volatile("cp.async.bulk.wait_group %0;" :: "n"(N) : "memory"); }
__device__ __forceinline__ void fence_async_smem() { asm volatile("fence.proxy.async.shared::cta;" ::: "memory"); }
__device__ __forceinline__ void fence_async_global() { asm volatile("fence.proxy.async.global;" ::: "memory"); }
__device__ __forceinline__ void wgmma_fence() { asm volatile("wgmma.fence.sync.aligned;" ::: "memory"); }
__device__ __forceinline__ void wgmma_commit() { asm volatile("wgmma.commit_group.sync.aligned;" ::: "memory"); }
template <int N> __device__ __forceinline__ void wgmma_wait() { asm volatile("wgmma.wait_group.sync.aligned %0;" :: "n"(N) : "memory"); }
__device__ __forceinline__ uint64_t make_desc(uint32_t addr, uint32_t lbo, uint32_t sbo) {
  return (uint64_t)((addr & 0x3FFFF) >> 4) | ((uint64_t)(lbo >> 4) << 16) | ((uint64_t)(sbo >> 4) << 32) | (1ull << 62);
}
template <int N> __device__ __forceinline__ void fence_regs(float (&d)[N]) {
#pragma unroll
  for (int i = 0; i < N; i++) asm volatile("" : "+f"(d[i]) :: "memory");
}
template <int N> __device__ __forceinline__ void fence_regs(uint32_t (&d)[N]) {
#pragma unroll
  for (int i = 0; i < N; i++) asm volatile("" : "+r"(d[i]) :: "memory");
}
__device__ __forceinline__ void named_sync(int id) { asm volatile("bar.sync %0, 256;" :: "r"(id) : "memory"); }
__device__ __forceinline__ bool wg_any(bool w, bool v) {
  uint32_t r;
  asm volatile("{\n.reg .pred p, q;\nsetp.ne.u32 p, %1, 0;\nbar.red.or.pred q, %2, 128, p;\nselp.u32 %0, 1, 0, q;\n}" : "=r"(r) : "r"((uint32_t)v), "r"(w ? 4 : 3) : "memory");
  return __any_sync(0xffffffffu, r);
}
__device__ __forceinline__ int fresh_warp() { uint32_t t; asm volatile("mov.u32 %0, %%tid.x;" : "=r"(t)); return __shfl_sync(0xffffffffu, (int)(t >> 5) - 4, 0); }
__device__ __forceinline__ void cluster_sync_relaxed() { asm volatile("barrier.cluster.arrive.relaxed.aligned;\nbarrier.cluster.wait.aligned;" ::: "memory"); }
__device__ __forceinline__ unsigned ld_acquire(const unsigned* p) { unsigned v; asm volatile("ld.acquire.gpu.global.u32 %0, [%1];" : "=r"(v) : "l"(p) : "memory"); return v; }
__device__ __forceinline__ void red_release(unsigned* p, unsigned v) { asm volatile("red.release.gpu.global.add.u32 [%0], %1;" :: "l"(p), "r"(v) : "memory"); }
__device__ __forceinline__ void flag_wait(const unsigned* p, unsigned target) {
  uint32_t n = 0;
  while (ld_acquire(p) < target) { trap_if(++n > SPIN_LIMIT); __nanosleep(20); }
}
__device__ __forceinline__ void st_tagged(uint2* p, float a, float b, uint32_t tag) {
  asm volatile("{\n.reg .b64 x;\nmov.b64 x, {%1, %2};\nst.relaxed.gpu.global.b64 [%0], x;\n}" :: "l"(p),
               "r"((__float_as_uint(a) & ~63u) | (tag & 63u)), "r"((__float_as_uint(b) & ~63u) | (tag >> 6)) : "memory");
}
__device__ __forceinline__ uint4 ld_tagged2(const uint2* p) {
  uint4 v;
  asm volatile("{\n.reg .b64 x, y;\nld.relaxed.gpu.global.v2.b64 {x, y}, [%4];\nmov.b64 {%0, %1}, x;\nmov.b64 {%2, %3}, y;\n}" : "=r"(v.x), "=r"(v.y), "=r"(v.z), "=r"(v.w) : "l"(p) : "memory");
  return v;
}
__device__ __forceinline__ bool tag_ok(uint32_t a, uint32_t b, uint32_t tag) { return ((a & 63u) | ((b & 63u) << 6)) == tag; }
__device__ __forceinline__ uint32_t pack_bf16(float lo, float hi) { uint32_t r; asm("cvt.rn.bf16x2.f32 %0, %1, %2;" : "=r"(r) : "f"(hi), "f"(lo)); return r; }
__device__ __forceinline__ uint32_t bf2_fma(uint32_t a, uint32_t b, uint32_t c) { uint32_t r; asm("fma.rn.bf16x2 %0, %1, %2, %3;" : "=r"(r) : "r"(a), "r"(b), "r"(c)); return r; }
__device__ __forceinline__ uint32_t bf2_mul(uint32_t a, uint32_t b) { uint32_t r; asm("mul.rn.bf16x2 %0, %1, %2;" : "=r"(r) : "r"(a), "r"(b)); return r; }
__device__ __forceinline__ uint32_t bf2_add(uint32_t a, uint32_t b) { uint32_t r; asm("add.rn.bf16x2 %0, %1, %2;" : "=r"(r) : "r"(a), "r"(b)); return r; }
constexpr uint32_t BF2_HALF = 0x3f003f00u;
__device__ __forceinline__ float bf_lo(uint32_t v) { return __uint_as_float(v << 16); }
__device__ __forceinline__ float bf_hi(uint32_t v) { return __uint_as_float(v & 0xffff0000u); }
__device__ __forceinline__ float ex2(float x) { float y; asm("ex2.approx.ftz.f32 %0, %1;" : "=f"(y) : "f"(x)); return y; }
__device__ __forceinline__ float tanh_fast(float x) { float y; asm("tanh.approx.f32 %0, %1;" : "=f"(y) : "f"(x)); return y; }
__device__ __forceinline__ void stmatrix_x4(uint32_t addr, uint32_t a, uint32_t b, uint32_t c, uint32_t d) {
  asm volatile("stmatrix.sync.aligned.m8n8.x4.shared.b16 [%0], {%1, %2, %3, %4};" :: "r"(addr), "r"(a), "r"(b), "r"(c), "r"(d) : "memory");
}
__device__ __forceinline__ void ldmatrix_x4(uint32_t addr, uint32_t& a, uint32_t& b, uint32_t& c, uint32_t& d) {
  asm volatile("ldmatrix.sync.aligned.m8n8.x4.shared.b16 {%0, %1, %2, %3}, [%4];" : "=r"(a), "=r"(b), "=r"(c), "=r"(d) : "r"(addr) : "memory");
}
__device__ __forceinline__ uint32_t lane_id() { uint32_t l; asm volatile("mov.u32 %0, %%laneid;" : "=r"(l)); return l; }
__device__ __forceinline__ bool elect_one() {
  uint32_t r;
  asm volatile("{\n.reg .pred P;\nelect.sync _|P, 0xffffffff;\nselp.u32 %0, 1, 0, P;\n}" : "=r"(r));
  return r;
}

__device__ __forceinline__ void wgmma_m64n128k16_ss_tb0(float (&d)[64], uint64_t da, uint64_t db, int scale_d) {
  asm volatile("{\n.reg .pred p;\nsetp.ne.b32 p, %66, 0;\n"
    "wgmma.mma_async.sync.aligned.m64n128k16.f32.bf16.bf16 "
    "{%0, %1, %2, %3, %4, %5, %6, %7, %8, %9, %10, %11, %12, %13, %14, %15, %16, %17, %18, %19, %20, %21, %22, %23, %24, %25, %26, %27, %28, %29, %30, %31, %32, %33, %34, %35, %36, %37, %38, %39, %40, %41, %42, %43, %44, %45, %46, %47, %48, %49, %50, %51, %52, %53, %54, %55, %56, %57, %58, %59, %60, %61, %62, %63}, "
    "%64, %65, p, 1, 1, 0, 0;\n}\n"
    : "+f"(d[0]), "+f"(d[1]), "+f"(d[2]), "+f"(d[3]), "+f"(d[4]), "+f"(d[5]), "+f"(d[6]), "+f"(d[7]), "+f"(d[8]), "+f"(d[9]), "+f"(d[10]), "+f"(d[11]), "+f"(d[12]), "+f"(d[13]), "+f"(d[14]), "+f"(d[15]), "+f"(d[16]), "+f"(d[17]), "+f"(d[18]), "+f"(d[19]), "+f"(d[20]), "+f"(d[21]), "+f"(d[22]), "+f"(d[23]), "+f"(d[24]), "+f"(d[25]), "+f"(d[26]), "+f"(d[27]), "+f"(d[28]), "+f"(d[29]), "+f"(d[30]), "+f"(d[31]), "+f"(d[32]), "+f"(d[33]), "+f"(d[34]), "+f"(d[35]), "+f"(d[36]), "+f"(d[37]), "+f"(d[38]), "+f"(d[39]), "+f"(d[40]), "+f"(d[41]), "+f"(d[42]), "+f"(d[43]), "+f"(d[44]), "+f"(d[45]), "+f"(d[46]), "+f"(d[47]), "+f"(d[48]), "+f"(d[49]), "+f"(d[50]), "+f"(d[51]), "+f"(d[52]), "+f"(d[53]), "+f"(d[54]), "+f"(d[55]), "+f"(d[56]), "+f"(d[57]), "+f"(d[58]), "+f"(d[59]), "+f"(d[60]), "+f"(d[61]), "+f"(d[62]), "+f"(d[63])
    : "l"(da), "l"(db), "r"(scale_d));
}
__device__ __forceinline__ void wgmma_m64n256k16_ss_tb1(float (&d)[128], uint64_t da, uint64_t db, int scale_d) {
  asm volatile("{\n.reg .pred p;\nsetp.ne.b32 p, %130, 0;\n"
    "wgmma.mma_async.sync.aligned.m64n256k16.f32.bf16.bf16 "
    "{%0, %1, %2, %3, %4, %5, %6, %7, %8, %9, %10, %11, %12, %13, %14, %15, %16, %17, %18, %19, %20, %21, %22, %23, %24, %25, %26, %27, %28, %29, %30, %31, %32, %33, %34, %35, %36, %37, %38, %39, %40, %41, %42, %43, %44, %45, %46, %47, %48, %49, %50, %51, %52, %53, %54, %55, %56, %57, %58, %59, %60, %61, %62, %63, %64, %65, %66, %67, %68, %69, %70, %71, %72, %73, %74, %75, %76, %77, %78, %79, %80, %81, %82, %83, %84, %85, %86, %87, %88, %89, %90, %91, %92, %93, %94, %95, %96, %97, %98, %99, %100, %101, %102, %103, %104, %105, %106, %107, %108, %109, %110, %111, %112, %113, %114, %115, %116, %117, %118, %119, %120, %121, %122, %123, %124, %125, %126, %127}, "
    "%128, %129, p, 1, 1, 0, 1;\n}\n"
    : "+f"(d[0]), "+f"(d[1]), "+f"(d[2]), "+f"(d[3]), "+f"(d[4]), "+f"(d[5]), "+f"(d[6]), "+f"(d[7]), "+f"(d[8]), "+f"(d[9]), "+f"(d[10]), "+f"(d[11]), "+f"(d[12]), "+f"(d[13]), "+f"(d[14]), "+f"(d[15]), "+f"(d[16]), "+f"(d[17]), "+f"(d[18]), "+f"(d[19]), "+f"(d[20]), "+f"(d[21]), "+f"(d[22]), "+f"(d[23]), "+f"(d[24]), "+f"(d[25]), "+f"(d[26]), "+f"(d[27]), "+f"(d[28]), "+f"(d[29]), "+f"(d[30]), "+f"(d[31]), "+f"(d[32]), "+f"(d[33]), "+f"(d[34]), "+f"(d[35]), "+f"(d[36]), "+f"(d[37]), "+f"(d[38]), "+f"(d[39]), "+f"(d[40]), "+f"(d[41]), "+f"(d[42]), "+f"(d[43]), "+f"(d[44]), "+f"(d[45]), "+f"(d[46]), "+f"(d[47]), "+f"(d[48]), "+f"(d[49]), "+f"(d[50]), "+f"(d[51]), "+f"(d[52]), "+f"(d[53]), "+f"(d[54]), "+f"(d[55]), "+f"(d[56]), "+f"(d[57]), "+f"(d[58]), "+f"(d[59]), "+f"(d[60]), "+f"(d[61]), "+f"(d[62]), "+f"(d[63]), "+f"(d[64]), "+f"(d[65]), "+f"(d[66]), "+f"(d[67]), "+f"(d[68]), "+f"(d[69]), "+f"(d[70]), "+f"(d[71]), "+f"(d[72]), "+f"(d[73]), "+f"(d[74]), "+f"(d[75]), "+f"(d[76]), "+f"(d[77]), "+f"(d[78]), "+f"(d[79]), "+f"(d[80]), "+f"(d[81]), "+f"(d[82]), "+f"(d[83]), "+f"(d[84]), "+f"(d[85]), "+f"(d[86]), "+f"(d[87]), "+f"(d[88]), "+f"(d[89]), "+f"(d[90]), "+f"(d[91]), "+f"(d[92]), "+f"(d[93]), "+f"(d[94]), "+f"(d[95]), "+f"(d[96]), "+f"(d[97]), "+f"(d[98]), "+f"(d[99]), "+f"(d[100]), "+f"(d[101]), "+f"(d[102]), "+f"(d[103]), "+f"(d[104]), "+f"(d[105]), "+f"(d[106]), "+f"(d[107]), "+f"(d[108]), "+f"(d[109]), "+f"(d[110]), "+f"(d[111]), "+f"(d[112]), "+f"(d[113]), "+f"(d[114]), "+f"(d[115]), "+f"(d[116]), "+f"(d[117]), "+f"(d[118]), "+f"(d[119]), "+f"(d[120]), "+f"(d[121]), "+f"(d[122]), "+f"(d[123]), "+f"(d[124]), "+f"(d[125]), "+f"(d[126]), "+f"(d[127])
    : "l"(da), "l"(db), "r"(scale_d));
}
__device__ __forceinline__ void wgmma_m64n128k16_rs_tb1(float (&d)[64], uint32_t a0, uint32_t a1, uint32_t a2, uint32_t a3, uint64_t db, int scale_d) {
  asm volatile("{\n.reg .pred p;\nsetp.ne.b32 p, %69, 0;\n"
    "wgmma.mma_async.sync.aligned.m64n128k16.f32.bf16.bf16 "
    "{%0, %1, %2, %3, %4, %5, %6, %7, %8, %9, %10, %11, %12, %13, %14, %15, %16, %17, %18, %19, %20, %21, %22, %23, %24, %25, %26, %27, %28, %29, %30, %31, %32, %33, %34, %35, %36, %37, %38, %39, %40, %41, %42, %43, %44, %45, %46, %47, %48, %49, %50, %51, %52, %53, %54, %55, %56, %57, %58, %59, %60, %61, %62, %63}, "
    "{%64, %65, %66, %67}, %68, p, 1, 1, 1;\n}\n"
    : "+f"(d[0]), "+f"(d[1]), "+f"(d[2]), "+f"(d[3]), "+f"(d[4]), "+f"(d[5]), "+f"(d[6]), "+f"(d[7]), "+f"(d[8]), "+f"(d[9]), "+f"(d[10]), "+f"(d[11]), "+f"(d[12]), "+f"(d[13]), "+f"(d[14]), "+f"(d[15]), "+f"(d[16]), "+f"(d[17]), "+f"(d[18]), "+f"(d[19]), "+f"(d[20]), "+f"(d[21]), "+f"(d[22]), "+f"(d[23]), "+f"(d[24]), "+f"(d[25]), "+f"(d[26]), "+f"(d[27]), "+f"(d[28]), "+f"(d[29]), "+f"(d[30]), "+f"(d[31]), "+f"(d[32]), "+f"(d[33]), "+f"(d[34]), "+f"(d[35]), "+f"(d[36]), "+f"(d[37]), "+f"(d[38]), "+f"(d[39]), "+f"(d[40]), "+f"(d[41]), "+f"(d[42]), "+f"(d[43]), "+f"(d[44]), "+f"(d[45]), "+f"(d[46]), "+f"(d[47]), "+f"(d[48]), "+f"(d[49]), "+f"(d[50]), "+f"(d[51]), "+f"(d[52]), "+f"(d[53]), "+f"(d[54]), "+f"(d[55]), "+f"(d[56]), "+f"(d[57]), "+f"(d[58]), "+f"(d[59]), "+f"(d[60]), "+f"(d[61]), "+f"(d[62]), "+f"(d[63])
    : "r"(a0), "r"(a1), "r"(a2), "r"(a3), "l"(db), "r"(scale_d));
}
__device__ __forceinline__ void wgmma_m64n128k16_ss_tb1(float (&d)[64], uint64_t da, uint64_t db, int scale_d) {
  asm volatile("{\n.reg .pred p;\nsetp.ne.b32 p, %66, 0;\n"
    "wgmma.mma_async.sync.aligned.m64n128k16.f32.bf16.bf16 "
    "{%0, %1, %2, %3, %4, %5, %6, %7, %8, %9, %10, %11, %12, %13, %14, %15, %16, %17, %18, %19, %20, %21, %22, %23, %24, %25, %26, %27, %28, %29, %30, %31, %32, %33, %34, %35, %36, %37, %38, %39, %40, %41, %42, %43, %44, %45, %46, %47, %48, %49, %50, %51, %52, %53, %54, %55, %56, %57, %58, %59, %60, %61, %62, %63}, "
    "%64, %65, p, 1, 1, 0, 1;\n}\n"
    : "+f"(d[0]), "+f"(d[1]), "+f"(d[2]), "+f"(d[3]), "+f"(d[4]), "+f"(d[5]), "+f"(d[6]), "+f"(d[7]), "+f"(d[8]), "+f"(d[9]), "+f"(d[10]), "+f"(d[11]), "+f"(d[12]), "+f"(d[13]), "+f"(d[14]), "+f"(d[15]), "+f"(d[16]), "+f"(d[17]), "+f"(d[18]), "+f"(d[19]), "+f"(d[20]), "+f"(d[21]), "+f"(d[22]), "+f"(d[23]), "+f"(d[24]), "+f"(d[25]), "+f"(d[26]), "+f"(d[27]), "+f"(d[28]), "+f"(d[29]), "+f"(d[30]), "+f"(d[31]), "+f"(d[32]), "+f"(d[33]), "+f"(d[34]), "+f"(d[35]), "+f"(d[36]), "+f"(d[37]), "+f"(d[38]), "+f"(d[39]), "+f"(d[40]), "+f"(d[41]), "+f"(d[42]), "+f"(d[43]), "+f"(d[44]), "+f"(d[45]), "+f"(d[46]), "+f"(d[47]), "+f"(d[48]), "+f"(d[49]), "+f"(d[50]), "+f"(d[51]), "+f"(d[52]), "+f"(d[53]), "+f"(d[54]), "+f"(d[55]), "+f"(d[56]), "+f"(d[57]), "+f"(d[58]), "+f"(d[59]), "+f"(d[60]), "+f"(d[61]), "+f"(d[62]), "+f"(d[63])
    : "l"(da), "l"(db), "r"(scale_d));
}


enum { TM_XN, TM_WSP, TM_U, TM_O, TM_Q, TM_X, TM_SA, TM_G, TM_K, TM_V, TM_WO64,
       TM_WIN, TM_WQ, TM_Z2, TM_WOUT, TM_WO, TS_Q, TS_O, TS_Z2, TS_U, TS_SA, TS_G, TS_OUT, TM_COUNT };
enum { T_Z2 = 0, T_Q = 1, T_U = 2, T_ATT = 3, T_SA = 4, T_FIN = 5, T_END = 7 };
constexpr int NCLUSTER = 66, MAXI = 14;
struct alignas(64) Params {
  const bf16* x;
  const bf16* b_sp;
  CUtensorMap tm[TM_COUNT];
  uint16_t items[NCLUSTER][MAXI];
};

constexpr uint32_t G_STAGE = 49152, G_A = 16384, KV_SLOT = 32768;
constexpr uint32_t OFF_Q1 = 163840, OFF_Q0 = 196608, OFF_BAR = 229376, OFF_LN = OFF_BAR + 256, SMEM_BYTES = OFF_LN + 1024;
constexpr uint32_t B_GF = 0, B_GE = 32, B_KF = 64, B_KE = 104, B_QF = 144, B_QE = 160, B_XF = 176, B_XR = 184, B_STG = 192, B_FREE = 200, B_GO = 208, B_LN = 216, B_TAG = 224, B_RDY = 228, B_PROG = 232, B_PUB = 248;
constexpr int SA_HEADS = 18;
constexpr int SW_NS = 40;
constexpr int ST_ROWS = 16;
constexpr int ST_FLY = 2;
constexpr int KV_PF = 4;
constexpr int FIN_PREP = 8;
constexpr int OWN_OFF = 8;
constexpr int Z_DELAY = 3;
constexpr int SW_ATT = 800;
constexpr int OUT_PF = 8;
constexpr int SA_ROT = 1;
constexpr uint32_t FIN_SLOT0 = (0x0320u >> (4 * ((28 + 2 * SA_HEADS + SA_ROT) & 3))) & 15;
constexpr float SM_C = 0.08838834764831845f * 1.4426950408889634f;
constexpr float GELU_A = 0.7978845608028654f, GELU_B = 0.7978845608028654f * 0.044715f;
constexpr float SM_LO = 1e-7f, SM_HI = 1e12f;
constexpr float SM_THR = 1024.f;


extern __shared__ __align__(1024) uint8_t smem_raw[];
__device__ __forceinline__ uint32_t smem_base() { return smem_u32(smem_raw); }

struct Ring { uint32_t s, ph; };
template <int N> __device__ __forceinline__ void ring_adv(Ring& r) { if (++r.s == N) { r.s = 0; r.ph ^= 1; } }

__device__ __forceinline__ int get_item(const Params& p, int i) {
  uint32_t b; asm volatile("mov.u32 %0, %%ctaid.x;" : "=r"(b));
  return p.items[b >> 1][i];
}
struct Cons {
  uint32_t sb;
  int warp;
  Ring g;
  uint32_t rot;
  uint32_t fph;
};

__device__ __forceinline__ void stage_acquire(const Cons& c) { mbar_spin(c.sb + OFF_BAR + B_FREE, c.fph); }
__device__ __forceinline__ void stage_commit(Cons& c) {
  __syncwarp();
  if (lane_id() == 0) mbar_arrive(c.sb + OFF_BAR + B_STG);
  c.fph ^= 1;
}

__device__ __forceinline__ void release_slot(const Cons& c, uint32_t bar) {
  if (lane_id() == 0 && (c.warp & 3) < 2) mbar_arrive_cta(bar, c.warp & 1);
}
constexpr uint64_t DESC_HI = (uint64_t)0x40000040u << 32;

template <bool FIRST> __device__ __forceinline__ void gemm_step(float (&acc)[128], Cons& c) {
  mbar_spin(c.sb + OFF_BAR + B_GF + 8 * c.g.s, c.g.ph);
  const uint32_t st = ((c.sb & 0x3FFFF) >> 4) + ((c.g.s + c.rot) & 3) * (G_STAGE >> 4);
  const uint32_t da = st + (c.warp >> 2) * 512 + (1u << 16), db = st + (G_A >> 4) + ((8192u >> 4) << 16);
  wgmma_fence();
#pragma unroll
  for (int kk = 0; kk < 4; kk++) wgmma_m64n256k16_ss_tb1(acc, DESC_HI | (da + kk * 2), DESC_HI | (db + kk * 128), !(FIRST && kk == 0));
  wgmma_commit();
}

template <int N> __device__ __forceinline__ void stage_chunks(uint32_t buf, uint32_t stride, const uint32_t* pk) {
  const uint32_t ln = lane_id();
  const uint32_t a = buf + ((ln & 15) << 7);
  const uint32_t x = ln & 7, hi = ln >> 4;
#pragma unroll
  for (int i = 0; i < 4 * N; i++) stmatrix_x4(a + (i >> 2) * stride + (((2 * (i & 3) + hi) ^ x) << 4), pk[4 * i], pk[4 * i + 1], pk[4 * i + 2], pk[4 * i + 3]);
}

__device__ __forceinline__ float act2_fn(float x, float a, float b) {
  return fmaf(x, tanh_fast(x * fmaf(x * x, b, a)), x);
}
__device__ __forceinline__ float quad_sum(float v) { v += __shfl_xor_sync(0xffffffffu, v, 1); v += __shfl_xor_sync(0xffffffffu, v, 2); return v; }
__device__ __forceinline__ float quad_max(float v) { v = fmaxf(v, __shfl_xor_sync(0xffffffffu, v, 1)); v = fmaxf(v, __shfl_xor_sync(0xffffffffu, v, 2)); return v; }

__device__ __forceinline__ uint32_t load_tag(const Cons& c) { uint32_t t; asm volatile("ld.volatile.shared.u32 %0, [%1];" : "=r"(t) : "r"(c.sb + OFF_BAR + B_TAG)); return t; }

struct Shadow {
  int act;
  int store;
};
__device__ __forceinline__ void rotate16(uint32_t (&h)[64]) {
#pragma unroll
  for (int i = 0; i < 16; i++)
    asm volatile("{\n.reg .b32 t;\nmov.b32 t, %0;\nmov.b32 %0, %1;\nmov.b32 %1, %2;\nmov.b32 %2, %3;\nmov.b32 %3, t;\n}" : "+r"(h[i]), "+r"(h[i + 16]), "+r"(h[i + 32]), "+r"(h[i + 48]));
}

template <int O>
__device__ __forceinline__ void act_block(uint32_t (&held)[64], float ca, float cb, bool first, float& u0, float& u1, float& s0, float& s1, float& q0, float& q1) {
#pragma unroll
  for (int i = O; i < O + 4; i += 2) {
    const float a0 = act2_fn(bf_lo(held[i]), ca, cb), a1 = act2_fn(bf_hi(held[i]), ca, cb);
    const float b0 = act2_fn(bf_lo(held[i + 1]), ca, cb), b1 = act2_fn(bf_hi(held[i + 1]), ca, cb);
    if (i == 0 && first) { u0 = a0; u1 = b0; }
    float d;
    d = a0 - u0; s0 += d; q0 = fmaf(d, d, q0); d = a1 - u0; s0 += d; q0 = fmaf(d, d, q0);
    d = b0 - u1; s1 += d; q1 = fmaf(d, d, q1); d = b1 - u1; s1 += d; q1 = fmaf(d, d, q1);
    held[i] = pack_bf16(a0, a1); held[i + 1] = pack_bf16(b0, b1);
  }
}

template <int O> __device__ __forceinline__ void stage_half(Cons& c, uint32_t (&held)[64], int mode) {
  if (mode == 2) {
    uint32_t a0, a1, r0, r1;
    const uint32_t la = c.sb + OFF_LN + (c.warp * 16 + (lane_id() >> 2)) * 8;
    mbar_spin(c.sb + OFF_BAR + B_LN, 0);
    asm volatile("ld.shared.v2.b32 {%0, %1}, [%2];" : "=r"(r0), "=r"(a0) : "r"(la));
    asm volatile("ld.shared.v2.b32 {%0, %1}, [%2];" : "=r"(r1), "=r"(a1) : "r"(la + 64));
#pragma unroll
    for (int i = O; i < O + 32; i += 2) { held[i] = bf2_mul(bf2_add(held[i], a0), r0); held[i + 1] = bf2_mul(bf2_add(held[i + 1], a1), r1); }
  }
  stage_acquire(c);
  stage_chunks<2>(c.sb + OFF_Q0 + c.warp * 2048, 16384, held + O);
  stage_commit(c);
}

__device__ __forceinline__ void gemm_seg(float (&acc)[128], uint32_t (&held)[64], Cons& c, const Params& p, Shadow& sh, int nsteps, bool hold) {
  const bool elected = lane_id() == 0 && (c.warp & 3) < 2;
  uint32_t rel;
  asm("mapa.shared::cluster.u32 %0, %1, %2;" : "=r"(rel) : "r"(c.sb + OFF_BAR + B_GE), "r"((uint32_t)(c.warp & 1)));
  gemm_step<true>(acc, c);
  ring_adv<4>(c.g);
  int k = 1;
#define G_STEP()                                                                                                       \
  { gemm_step<false>(acc, c);                                                                                          \
    wgmma_wait<1>();                                                                                                   \
    if (elected) asm volatile("mbarrier.arrive.shared::cluster.b64 _, [%0];" :: "r"(rel + 8 * ((c.g.s - 1) & 3)) : "memory"); \
    ring_adv<4>(c.g);                                                                                                  \
    k++; }
  if (sh.act != 0) {
    float u0 = 0.f, u1 = 0.f, s0 = 0.f, s1 = 0.f, q0 = 0.f, q1 = 0.f;
    const float ca = sh.act == 3 ? 0.5f : GELU_A, cb = sh.act == 3 ? 0.f : GELU_B;
#pragma unroll 1
    while (true) {
      act_block<0>(held, ca, cb, k == 1, u0, u1, s0, s1, q0, q1);
      G_STEP()
      act_block<4>(held, ca, cb, false, u0, u1, s0, s1, q0, q1);
      G_STEP()
      act_block<8>(held, ca, cb, false, u0, u1, s0, s1, q0, q1);
      G_STEP()
      act_block<12>(held, ca, cb, false, u0, u1, s0, s1, q0, q1);
      rotate16(held);
      if (k == 16) break;
      G_STEP()
    }
    if (sh.act == 2) {
      const int zi = get_item(p, 0);
      const int ln = lane_id(), row0 = (((zi >> 5) & 31) * 2 + (blockIdx.x & 1)) * 128 + c.warp * 16 + (ln >> 2), ql = ln & 3;
      const float m0 = fmaf(s0, 1.f / 64, u0), m1 = fmaf(s1, 1.f / 64, u1);
      q0 -= s0 * s0 * (1.f / 64); q1 -= s1 * s1 * (1.f / 64);
      const float mu0 = quad_sum(m0) * 0.25f, mu1 = quad_sum(m1) * 0.25f;
      q0 = quad_sum(fmaf(64.f * (m0 - mu0), m0 - mu0, q0)); q1 = quad_sum(fmaf(64.f * (m1 - mu1), m1 - mu1, q1));
      if (ql < 2) st_tagged(&g_stats[(row0 + 8 * ql) * 8 + (zi & 31)], ql ? mu1 : mu0, ql ? q1 : q0, load_tag(c));
      if (ln == 0) mbar_arrive(c.sb + OFF_BAR + B_PUB);
    }
  }
  const int s0 = sh.store == 0 ? -9 : k + (sh.store == 2 ? Z_DELAY : 1), s1 = sh.store == 3 ? -9 : s0 + 3;
  hold = hold && k < nsteps;
#pragma unroll 1
  while (k < nsteps) {
    G_STEP()
    if (k == s0) stage_half<0>(c, held, sh.store);
    else if (k == s1) stage_half<32>(c, held, sh.store);
    else if (hold && k == nsteps - 2 && c.warp >= 4) named_sync(6);
  }
  if (hold && c.warp < 4) asm volatile("bar.arrive 6, 256;" ::: "memory");
  wgmma_wait<0>();
  fence_regs(acc);
  if (elected) asm volatile("mbarrier.arrive.shared::cluster.b64 _, [%0];" :: "r"(rel + 8 * ((c.g.s - 1) & 3)) : "memory");
  sh.store = sh.act == 2 ? 2 : 0;
  sh.act = 0;
}

template <bool SUB> __device__ __forceinline__ void softmax_exp(const float (&S)[64], uint32_t (&P)[32], float m0, float m1, float& s0, float& s1) {
  float a0 = 0.f, a1 = 0.f, b0 = 0.f, b1 = 0.f;
#pragma unroll
  for (int j = 0; j < 16; j++) {
    const float p0 = ex2(SUB ? S[4 * j] - m0 : S[4 * j]), p1 = ex2(SUB ? S[4 * j + 1] - m0 : S[4 * j + 1]);
    const float p2 = ex2(SUB ? S[4 * j + 2] - m1 : S[4 * j + 2]), p3 = ex2(SUB ? S[4 * j + 3] - m1 : S[4 * j + 3]);
    a0 += p0; b0 += p1; a1 += p2; b1 += p3;
    P[2 * j] = pack_bf16(p0, p1); P[2 * j + 1] = pack_bf16(p2, p3);
  }
  s0 = a0 + b0; s1 = a1 + b1;
}
__device__ __forceinline__ void row_max(const float (&S)[64], float& x0, float& x1) {
  float a0 = fmaxf(S[0], S[1]), a1 = fmaxf(S[2], S[3]);
#pragma unroll
  for (int j = 1; j < 16; j++) { a0 = fmaxf(a0, fmaxf(S[4 * j], S[4 * j + 1])); a1 = fmaxf(a1, fmaxf(S[4 * j + 2], S[4 * j + 3])); }
  x0 = quad_max(a0); x1 = quad_max(a1);
}

__device__ __forceinline__ void issue_qk(float (&S)[64], uint32_t da, uint32_t db) {
#pragma unroll
  for (int kk = 0; kk < 8; kk++) {
    const uint32_t o = (kk >> 2) * 1024 + (kk & 3) * 2;
    wgmma_m64n128k16_ss_tb0(S, DESC_HI | (da + o), DESC_HI | (db + o), kk > 0);
  }
}
__device__ __forceinline__ void issue_pv(float (&O)[64], const uint32_t (&P)[32], uint32_t db, int acc) {
#pragma unroll
  for (int kk = 0; kk < 8; kk++) wgmma_m64n128k16_rs_tb1(O, P[4 * kk], P[4 * kk + 1], P[4 * kk + 2], P[4 * kk + 3], DESC_HI | (db + kk * 128), (acc || kk > 0));
}

__device__ __forceinline__ void att_pack(const float (&O)[64], uint32_t (&pk)[32], float i0, float i1) {
#pragma unroll
  for (int j = 0; j < 16; j++) {
    pk[2 * j] = pack_bf16(O[4 * j] * i0, O[4 * j + 1] * i0);
    pk[2 * j + 1] = pack_bf16(O[4 * j + 2] * i1, O[4 * j + 3] * i1);
  }
}
__device__ __forceinline__ void att_stage(Cons& c, const uint32_t (&pk)[32], uint32_t qbuf) {
  stage_chunks<2>(c.sb + (qbuf ? OFF_Q1 : OFF_Q0) + c.warp * 2048, 16384, pk);
  stage_commit(c);
}

#define ATT_ISSUE(PIN, ACC)                                                                                            \
  wgmma_fence();                                                                                                       \
  issue_qk(S, qd, kd); wgmma_commit();                                                                                 \
  if (g > 1) release_slot(c, vrel);                                                                                    \
  vready = mbar_test(vbar, vph);                                                                                       \
  mbar_spin(vbar, vph);                                                                                                \
  wgmma_fence();                                                                                                       \
  issue_pv(O, PIN, vd, ACC); wgmma_commit();                                                                           \
  krel = kbar + (B_KE - B_KF); vrel = vbar + (B_KE - B_KF);                                                            \
  g++;                                                                                                                 \
  if (g < total) { kd = kd0 + kv.s * (KV_SLOT >> 4); kbar = bars + B_KF + 8 * kv.s; kph = kv.ph; ring_adv<5>(kv); }    \
  vd = vd0 + kv.s * (KV_SLOT >> 4); vbar = bars + B_KF + 8 * kv.s; vph = kv.ph; ring_adv<5>(kv);

#define ATT_WAIT_S()                                                                                                   \
  wgmma_wait<1>();                                                                                                     \
  fence_regs(S);                                                                                                       \
  release_slot(c, krel);                                                                                               \
  if (c.warp == 2) asm volatile("st.volatile.shared.u32 [%0], %1;" :: "r"(bars + B_PROG), "r"(g) : "memory");

#define ATT_SOFTMAX(POUT, FIRST)                                                                                       \
  fresh = false;                                                                                                       \
  _Pragma("unroll 1")                                                                                                  \
  while (true) {                                                                                                       \
    if (__builtin_expect(fresh, 0)) {                                                                                  \
      float x0, x1;                                                                                                    \
      row_max(S, x0, x1);                                                                                              \
      if (FIRST) m0 = m1 = -1e38f;                                                                                     \
      x0 = fmaxf(x0, m0); x1 = fmaxf(x1, m1);                                                                          \
      f0 = ex2(m0 - x0); f1 = ex2(m1 - x1);                                                                            \
      m0 = x0; m1 = x1; l0 *= f0; l1 *= f1;                                                                            \
      zero = false;                                                                                                    \
    }                                                                                                                  \
    if (zero) {                                                                                                        \
      softmax_exp<false>(S, POUT, m0, m1, s0, s1);                                                                     \
      bad = !(s0 <= SM_HI && s1 <= SM_HI) || ((FIRST) && (s0 < SM_LO || s1 < SM_LO));                                  \
    } else {                                                                                                           \
      softmax_exp<true>(S, POUT, m0, m1, s0, s1);                                                                      \
      bad = !(s0 <= SM_THR && s1 <= SM_THR);                                                                           \
    }                                                                                                                  \
    kready = mbar_test(kbar, kph) && vready;                                                                           \
    slow = fresh || __any_sync(0xffffffffu, bad || !kready);                                                           \
    if (__builtin_expect(!slow, 1)) break;                                                                             \
    if (fresh || !__any_sync(0xffffffffu, bad)) break;                                                                 \
    fresh = true;                                                                                                      \
  }                                                                                                                    \
  l0 += s0; l1 += s1;                                                                                                  \
  wgmma_wait<0>(); fence_regs(O);

#define ATT_RESCALE()                                                                                                  \
  { _Pragma("unroll")                                                                                                  \
    for (int i = 0; i < 16; i++) { O[4 * i] *= f0; O[4 * i + 1] *= f0; O[4 * i + 2] *= f1; O[4 * i + 3] *= f1; } }

__device__ __forceinline__ void att_stagger(const Cons& c, int g) {
  if (c.warp >= 4)
    asm volatile("{\n.reg .pred p;\n.reg .s32 v;\nLOOP:\nld.volatile.shared.s32 v, [%0];\nsetp.le.s32 p, v, %1;\n@p bra LOOP;\n}" :: "r"(c.sb + OFF_BAR + B_PROG), "r"(g) : "memory");
}

__device__ __forceinline__ void att_run(Cons& c, const Params& p, int it, int n) {
  const uint32_t bars = c.sb + OFF_BAR;
  float S[64], O[64];
  uint32_t P0[32], P1[32];
#pragma unroll
  for (int i = 0; i < 64; i++) O[i] = 0.f;
#pragma unroll
  for (int i = 0; i < 32; i++) P0[i] = P1[i] = 0u;
  fence_regs(O); fence_regs(P0); fence_regs(P1);
  float m0 = 0.f, m1 = 0.f, l0 = 0.f, l1 = 0.f, f0 = 1.f, f1 = 1.f, s0, s1, pl0 = 0.f, pl1 = 0.f;
  const int total = 16 * n;
  int g = 0;
  Ring kv = {1, 0};
  uint32_t kbar = bars + B_KF, kph = 0, vbar = bars + B_KF, vph = 0, krel, vrel = 0;
  const uint32_t kd0 = (uint32_t)make_desc(c.sb, 16, 1024), vd0 = (uint32_t)make_desc(c.sb, 16384, 1024);
  uint32_t qd = kd0 + ((OFF_Q0 + (c.warp >> 2) * 8192) >> 4), kd = kd0, vd = vd0;
  bool fresh, kready, vready, bad, slow, zero = false;
  mbar_spin(bars + B_QF, 0);
  mbar_spin(bars + B_KF, 0);
  att_stagger(c, 0);
#pragma unroll 1
  while (true) {
    ATT_ISSUE(P1, 1)
    const bool first = ((g - 1) & 15) == 0;
    if (first) { pl0 = l0; pl1 = l1; m0 = m1 = l0 = l1 = 0.f; zero = true; }
    ATT_WAIT_S()
    ATT_SOFTMAX(P0, first)
    if (__builtin_expect(slow || first, 0)) {
      if (first) {
        if (g > 1) {
          att_pack(O, P1, __fdividef(1.f, quad_sum(pl0)), __fdividef(1.f, quad_sum(pl1)));
          att_stage(c, P1, ((g >> 4) & 1) ^ 1);
        }
      } else if (fresh) ATT_RESCALE();
      mbar_spin(kbar, kph);
      if (__any_sync(0xffffffffu, !kready)) att_stagger(c, g);
    }
    ATT_ISSUE(P0, !first)
    ATT_WAIT_S()
    ATT_SOFTMAX(P1, false)
    if (__builtin_expect(slow || (g & 15) == 0, 0)) {
      if (fresh) ATT_RESCALE();
      if (g == total) break;
      mbar_spin(kbar, kph);
      if (__any_sync(0xffffffffu, !kready)) att_stagger(c, g);
      if ((g & 15) == 0) {
        const int t = g >> 4;
        const uint32_t qb = t & 1;
        mbar_spin(bars + B_QF + 8 * qb, (t >> 1) & 1);
        qd = kd0 + (((qb ? OFF_Q1 : OFF_Q0) + (c.warp >> 2) * 8192) >> 4);
      }
    }
  }
  release_slot(c, vrel);
  mbar_spin(vbar, vph);
  wgmma_fence();
  issue_pv(O, P1, vd, 1); wgmma_commit();
  pl0 = __fdividef(1.f, quad_sum(l0)); pl1 = __fdividef(1.f, quad_sum(l1));
  wgmma_wait<0>();
  fence_regs(O);
  release_slot(c, vbar + (B_KE - B_KF));
  att_pack(O, P0, pl0, pl1);
  if ((get_item(p, it + n) >> 12) == T_END) {
    const uint32_t buf = c.sb + (((n - 1) & 1) ? OFF_Q1 : OFF_Q0) + c.warp * 2048;
    stage_chunks<2>(buf, 16384, P0);
    fence_async_smem();
    __syncwarp();
    if (elect_one()) {
      const int im = get_item(p, it + n - 1), col = ((im >> 5) & 31) * 128, row = ((im & 31) * 2 + (blockIdx.x & 1)) * 128 + c.warp * 16;
      tma_store_2d(&p.tm[TS_O], buf, col, row); tma_store_2d(&p.tm[TS_O], buf + 16384, col + 64, row);
      bulk_commit();
      bulk_wait<0>();
      mbar_arrive(bars + B_STG);
    }
    __syncwarp();
  } else {
    att_stage(c, P0, (n - 1) & 1);
  }
}

__global__ void __cluster_dims__(2, 1, 1) __launch_bounds__(384, 1) fused_kernel(const __grid_constant__ Params p) {
  const uint32_t sb = smem_base();
  const uint32_t bars = sb + OFF_BAR;
  const int tid = threadIdx.x, lane = tid & 31;
  const int warp_id = __shfl_sync(0xffffffffu, tid >> 5, 0), wg = warp_id >> 2;
  const uint32_t rank = blockIdx.x & 1;
  const uint16_t* items = p.items[blockIdx.x >> 1];
  const int gw = blockIdx.x * 8 + warp_id - 4;
  uint4 xv[2][4];
  if (wg != 0 && gw < SEQ / 2) {
#pragma unroll
    for (int rr = 0; rr < 2; rr++)
#pragma unroll
      for (int i = 0; i < 4; i++) xv[rr][i] = __ldg(reinterpret_cast<const uint4*>(p.x + (size_t)(gw * 2 + rr) * DM) + i * 32 + lane);
  }
  if (warp_id == 1 && lane < TM_COUNT) asm volatile("prefetch.tensormap [%0];" :: "l"(&p.tm[lane]) : "memory");
  if (tid == 0) {
    for (int i = 0; i < 4; i++) { mbar_init(bars + B_GF + 8 * i, 1); mbar_init(bars + B_GE + 8 * i, 4); }
    for (int i = 0; i < 5; i++) { mbar_init(bars + B_KF + 8 * i, 1); mbar_init(bars + B_KE + 8 * i, 4); }
    for (int i = 0; i < 2; i++) { mbar_init(bars + B_QF + 8 * i, 1); mbar_init(bars + B_QE + 8 * i, 1); }
    mbar_init(bars + B_XF, 2); mbar_init(bars + B_XR, 2); mbar_init(bars + B_STG, 8); mbar_init(bars + B_FREE, 1); mbar_init(bars + B_GO, 1); mbar_init(bars + B_LN, 2); mbar_init(bars + B_PUB, 8);
    asm volatile("fence.mbarrier_init.release.cluster;" ::: "memory");
  }
  asm volatile("barrier.cluster.arrive.relaxed.aligned;" ::: "memory");

  if (wg == 0) {
    asm volatile("setmaxnreg.dec.sync.aligned.u32 40;");
    asm volatile("barrier.cluster.wait.acquire.aligned;" ::: "memory");
    if (warp_id >= 2 && (items[0] >> 12) == T_Z2) {
      if (lane == 0) mbar_wait_sleep(bars + B_PUB, 0, 100);
      __syncwarp();
      uint32_t tag;
      asm volatile("ld.volatile.shared.u32 %0, [%1];" : "=r"(tag) : "r"(bars + B_TAG));
      const int r = (warp_id - 2) * 64 + lane;
      const uint2* ps = &g_stats[((((items[0] >> 5) & 31) * 2 + rank) * 128 + r) * 8];
      uint4 t[2][4];
      uint32_t cnt = 0;
      while (true) {
        bool ok = true;
#pragma unroll
        for (int i = 0; i < 8; i++) t[i >> 2][i & 3] = ld_tagged2(ps + (i >> 2) * 256 + (i & 3) * 2);
#pragma unroll
        for (int i = 0; i < 8; i++) { const uint4 v = t[i >> 2][i & 3]; ok = ok && tag_ok(v.x, v.y, tag) && ((i & 3) == 3 || tag_ok(v.z, v.w, tag)); }
        if (__all_sync(0xffffffffu, ok)) break;
        trap_if(++cnt > SPIN_LIMIT);
        __nanosleep(100);
      }
#pragma unroll
      for (int y = 0; y < 2; y++) {
        float u = 0.f, v = 0.f;
#pragma unroll
        for (int i = 0; i < 7; i++) u += __uint_as_float((i & 1) ? t[y][i >> 1].z : t[y][i >> 1].x);
        u *= 1.f / 7;
#pragma unroll
        for (int i = 0; i < 7; i++) {
          const float d = __uint_as_float((i & 1) ? t[y][i >> 1].z : t[y][i >> 1].x) - u;
          v += fmaf(256.f * d, d, __uint_as_float((i & 1) ? t[y][i >> 1].w : t[y][i >> 1].y));
        }
        const float rs = rsqrtf(fmaxf(v, 0.f) * (1.f / FH) + 4e-5f);
        asm volatile("st.shared.v2.b32 [%0], {%1, %2};" :: "r"(sb + OFF_LN + (r + 32 * y) * 8), "r"(pack_bf16(rs, rs)), "r"(pack_bf16(-u, -u)) : "memory");
      }
      __syncwarp();
      if (lane == 0) mbar_arrive(bars + B_LN);
      __syncwarp();
    }
    if (warp_id == 0) {
      trap_if(sb & 1023);
      Ring g = {0, 1};
      int it = 0;
      uint32_t xph = 0;
      if (elect_one()) {
#pragma unroll 1
        for (;; it++) {
          const int item = items[it], type = item >> 12, b = item & 31, row = (((item >> 5) & 31) * 2 + rank) * 128;
          if (type >= T_ATT) break;
#pragma unroll 1
          for (int seg = 0; seg < (type == T_U ? 2 : 1); seg++) {
            const CUtensorMap* tA = &p.tm[seg ? TM_WSP : TM_XN];
            const CUtensorMap* tB = &p.tm[seg ? TM_Z2 : (type == T_Q ? TM_WQ : TM_WIN)];
            const int bchunk = b * 4 + (type == T_Z2 ? 28 : 0) + rank * 2;
            const unsigned* fl = seg ? &g_flags[F_Z2 + b * 32] : &g_flags[F_XN + (row >> 2)];
            const unsigned tgt = seg ? 16 : 128;
            int k = 0;
            if (it == 0 && seg == 0) {
              for (; k < 4; k++) {
                mbar_expect_tx(bars + B_GF + 8 * k, G_STAGE);
                tma_load_3d_mc(sb + k * G_STAGE + G_A + rank * 16384, tB, k * 64, bchunk, bars + B_GF + 8 * k);
              }
              g.ph ^= 1;
              asm volatile("st.volatile.shared.v4.u32 [%0], {%1, %2, %2, %2};" :: "r"(bars + B_TAG), "r"(__ldcg(&g_epoch) % 4095u + 1), "r"(0) : "memory");
            }
            if (seg || type != T_U) { flag_wait(fl, tgt); fence_async_global(); }
            for (int x = 0; x < k; x++) tma_load_2d(sb + x * G_STAGE, tA, x * 64, row, bars + B_GF + 8 * x);
#pragma unroll 1
            for (; k < (seg ? 32 : 16); k++) {
              if (k == 3 && type == T_U && seg == 0) { mbar_wait(bars + B_XF, xph); xph ^= 1; }
              mbar_wait(bars + B_GE + 8 * g.s, g.ph);
              const uint32_t st = sb + g.s * G_STAGE, fb = bars + B_GF + 8 * g.s;
              mbar_expect_tx(fb, G_STAGE);
              tma_load_2d(st, tA, k * 64, row, fb);
              tma_load_3d_mc(st + G_A + rank * 16384, tB, k * 64, bchunk, fb);
              ring_adv<4>(g);
            }
          }
        }
      }
      { const int e = __ffs(__ballot_sync(0xffffffffu, elect_one())) - 1; it = __shfl_sync(0xffffffffu, it, e); g.ph = __shfl_sync(0xffffffffu, g.ph, e); }
      const int n = ((items[it] >> 10) & 3) + 3;
      Ring kv = {0, 1};
      if (elect_one()) {
        int prow = 0;
        {
          const int im = items[it];
          tma_prefetch_2d(&p.tm[(im & 1) ? TM_V : TM_K], rank * 64, ((im >> 5) & 31) * SEQ + ((im & 7) >> 1) * 128);
        }
#pragma unroll 1
        for (int x = 0; x <= 32 * n; x++) {
          const int gb = x >> 1, t = gb >> 4;
          const int hrow = ((items[it + t] >> 5) & 31) * SEQ;
          const bool isv = (x & 1) || x == 32 * n;
          if (x != 1) {
            if (x == 0 || x == 2) mbar_wait(bars + B_GE + 4 * x, g.ph);
            if (x == 4) { mbar_wait(bars + B_XF, xph); xph ^= 1; }
            mbar_wait(bars + B_KE + 8 * kv.s, kv.ph);
            mbar_expect_tx(bars + B_KF + 8 * kv.s, KV_SLOT);
            tma_load_2d_mc(sb + kv.s * KV_SLOT + rank * 16384, &p.tm[isv ? TM_V : TM_K], rank * 64, isv ? prow : hrow + (gb & 15) * 128, bars + B_KF + 8 * kv.s);
            ring_adv<5>(kv);
          }
          {
            const int gp = gb + KV_PF, ip = items[it + (gp >> 4)];
            if (gp < 16 * n && ((gp ^ ip) & 7) == 0) tma_prefetch_2d(&p.tm[(x & 1) ? TM_V : TM_K], rank * 64, ((ip >> 5) & 31) * SEQ + (gp & 15) * 128);
          }
          if (x == 32 * n - 8) mbar_arrive(bars + B_GO);
          if (x & 1) prow = hrow + (gb & 15) * 128;
          if ((x & 31) == 11 && t + 1 < n) {
            const int tq = t + 1;
            const int im = items[it + tq], h = (im >> 5) & 31, m = (im & 31) * 2 + rank;
            const uint32_t qb = tq & 1;
            flag_wait(&g_flags[F_Q + m * 16 + (h >> 1)], 1);
            fence_async_global();
            mbar_wait(bars + B_QE + 8 * qb, ((tq - 1) >> 1) & 1);
            const uint32_t dst = sb + (qb ? OFF_Q1 : OFF_Q0), fb = bars + B_QF + 8 * qb;
            mbar_expect_tx(fb, 32768);
            tma_load_2d(dst, &p.tm[TM_Q], h * 128, m * 128, fb);
            tma_load_2d(dst + 16384, &p.tm[TM_Q], h * 128 + 64, m * 128, fb);
          }
        }
      }
      __syncwarp();
      it += n;
      uint32_t ready = 0;
      auto wait_head = [&](int h) {
        if ((ready >> h) & 1) return;
        uint32_t cnt = 0;
        while (true) {
          asm volatile("ld.acquire.cta.shared.u32 %0, [%1];" : "=r"(ready) : "r"(bars + B_RDY) : "memory");
          if ((ready >> h) & 1) break;
          trap_if(++cnt > SPIN_LIMIT * 8);
          __nanosleep(20);
        }
        fence_async_global();
      };
      int item = items[it];
      if ((item >> 12) == T_SA) {
        const int m = ((item >> 5) & 31) * 2 + rank, b = item & 31;
        Ring dr = kv;
        wait_head(0);
#pragma unroll 1
        for (int i = 0; i < 28 + 2 * SA_HEADS; i++) {
          {
            const bool so = i >= 28;
            const int k = so ? i - 28 : i;
            if (so) wait_head(k >> 1);
            if (elect_one()) {
              if (i < 4) { for (int x = 0; x < ((0x1022 >> (4 * i)) & 3); x++) { mbar_wait(bars + B_KE + 8 * dr.s, dr.ph); ring_adv<5>(dr); } }
              if (i == 2) { mbar_wait(bars + B_XF, xph); xph ^= 1; }
              mbar_wait(bars + B_GE + 8 * g.s, g.ph);
              const uint32_t st = sb + ((g.s + SA_ROT) & 3) * G_STAGE, fb = bars + B_GF + 8 * g.s;
              mbar_expect_tx(fb, G_STAGE);
              tma_load_2d(st, &p.tm[so ? TM_O : TM_U], k * 64, m * 128, fb);
              tma_load_3d_mc(st + G_A + rank * 16384, &p.tm[so ? TM_WO : TM_WOUT], k * 64, b * 4 + rank * 2, fb);
            }
            ring_adv<4>(g);
          }
          const int ip = i + OUT_PF;
          if (ip < 28 + 2 * SA_HEADS && elect_one()) {
            const bool so = ip >= 28;
            const int k = so ? ip - 28 : ip;
            if ((ip & 3) == b && (!so || ((ready >> (k >> 1)) & 1))) tma_prefetch_2d(&p.tm[so ? TM_O : TM_U], k * 64, m * 128);
            if ((ip & 7) == (m >> 1)) tma_prefetch_3d(&p.tm[so ? TM_WO : TM_WOUT], k * 64, b * 4 + rank * 2);
          }
          __syncwarp();
        }
        item = items[++it];
      }
      if ((item >> 12) == T_FIN) {
        const bool own = item & 4;
        const int m = ((item >> 5) & 31) * 2 + rank, col = (item & 3) * 256 + (own ? 128 : 0);
        uint32_t ps = own ? FIN_SLOT0 : kv.s;
#pragma unroll 1
        for (int i = 2 * SA_HEADS; i <= 2 * NH; i++) {
          const bool extra = i == 2 * NH - FIN_PREP;
          if (extra && own) continue;
          const int k = i > 2 * NH - FIN_PREP ? i - 1 : i;
          if (!extra) wait_head(k >> 1);
          if (elect_one()) {
            if (i == 2 * SA_HEADS) {
              for (int y = k; y < k + 4; y++) if ((ready >> (y >> 1)) & 1) tma_prefetch_2d(&p.tm[TM_O], y * 64, m * 128);
            }
            if (own && i < 2 * SA_HEADS + 5) {
              const uint32_t s0 = ((0x22100u >> (4 * ps)) - SA_ROT) & 3, s1 = ((0x32110u >> (4 * ps)) - SA_ROT) & 3;
              mbar_wait(bars + B_GE + 8 * s0, g.ph ^ (s0 < g.s)); mbar_wait(bars + B_GE + 8 * s1, g.ph ^ (s1 < g.s));
            }
            if (extra) { flag_wait(&g_flags[F_S + m * 4 + (item & 3)], 2); fence_async_global(); }
            mbar_wait(bars + B_KE + 8 * kv.s, kv.ph);
            const uint32_t dst = sb + ps * KV_SLOT, fb = bars + B_KF + 8 * kv.s;
            if (++ps == 5) ps = 0;
            mbar_expect_tx(fb, KV_SLOT);
            if (!extra) {
              tma_load_2d(dst, &p.tm[TM_O], k * 64, m * 128, fb);
              tma_load_2d_mc(dst + 16384 + rank * 8192, &p.tm[TM_WO64], col + rank * 64, k * 64, fb);
            } else {
              tma_load_2d(dst, &p.tm[TM_SA], col, m * 128, fb);
              tma_load_2d(dst + 16384, &p.tm[TM_SA], col + 64, m * 128, fb);
            }
            ring_adv<5>(kv);
          }
          __syncwarp();
        }
      }
      unsigned last = 0;
      if (lane == 0 && (item >> 12) == T_FIN) mbar_wait_sleep(bars + B_XR, 0, 100);
      if (lane == 0) { __threadfence(); last = atomicInc(&g_done, gridDim.x - 1) == gridDim.x - 1; }
      last = __shfl_sync(0xffffffffu, last, 0);
      if (last) {
        for (int i = lane; i < F_TOTAL / 4; i += 32) reinterpret_cast<uint4*>(g_flags)[i] = make_uint4(0, 0, 0, 0);
        if (lane == 0) g_epoch = g_epoch + 1;
      }
    } else if (warp_id == 1) {
      if (elect_one()) {
        uint32_t ph = 0;
        int t = 0;
        unsigned* fq = nullptr;
        const bool z = (items[0] >> 12) == T_Z2;
#pragma unroll 1
        for (int it = 0;; it++) {
          const int ii = (z && it < 2) ? it ^ 1 : it;
          const int item = items[ii], type = item >> 12, a = (item >> 5) & 31, b = item & 31;
          if (type == T_END) break;
          const int nt = items[ii + 1] >> 12;
          int row = (a * 2 + rank) * 128, col = b * 256;
          unsigned* f = &g_flags[F_S + (a * 2 + rank) * 4 + b];
          int tm = TS_G, npair = 2;
          bool quad = false;
          uint32_t src = sb + OFF_Q0;
          if (type == T_Z2) { tm = TS_Z2; f = &g_flags[F_Z2 + b * 32]; }
          else if (type == T_Q) { tm = TS_Q; f = &g_flags[F_Q + (a * 2 + rank) * 16 + b]; if (z || nt >= T_ATT) { npair = 0; quad = true; } }
          else if (type == T_U) { tm = TS_U; f = &g_flags[F_U + (a * 2 + rank) * 32]; npair = 0; quad = true; }
          else if (type == T_ATT) { tm = TS_O; f = &g_flags[F_O + (b * 2 + rank) * 32 + a]; npair = 1; row = (b * 2 + rank) * 128; col = a * 128; if (t & 1) src = sb + OFF_Q1; }
          else if (type == T_FIN) npair = 1;
          auto load_fin = [&](int fi, int tmi, uint32_t qb) {
            const int fc = (fi & 3) * 256 + ((fi & 4) ? 128 : 0), fr = (((fi >> 5) & 31) * 2 + rank) * 128;
            mbar_expect_tx(bars + B_QF + 8 * qb, 32768);
            tma_load_2d(sb + (qb ? OFF_Q1 : OFF_Q0), &p.tm[tmi], fc, fr, bars + B_QF + 8 * qb);
            tma_load_2d(sb + (qb ? OFF_Q1 : OFF_Q0) + 16384, &p.tm[tmi], fc + 64, fr, bars + B_QF + 8 * qb);
          };
          if (type == T_ATT && nt == T_FIN) load_fin(items[ii + 1], TM_X, (t & 1) ^ 1);
          if (type == T_FIN) {
            if (!(item & 4)) { flag_wait(&g_flags[F_S + (a * 2 + rank) * 4 + (b & 3)], 1); fence_async_global(); load_fin(item, TM_G, (t & 1) ^ 1); }
            mbar_arrive(bars + B_XR);
          }
#pragma unroll 1
          for (int op = 0; op < npair + quad; op++) {
            const bool q = op == npair;
            const int c0 = (q || type == T_SA) ? col : col + op * 128;
            mbar_wait_sleep(bars + B_STG, ph, (type == T_ATT && nt == T_ATT) ? SW_ATT : SW_NS);
            if (type == T_FIN) break;
            ph ^= 1;
            fence_async_smem();
            if (type == T_SA && op == 1) { tm = TS_SA; load_fin(items[ii + 1], TM_X, 1); }
            int c1 = c0;
            if (q) {
              const CUtensorMap* tb = &p.tm[type == T_U ? TM_U : TM_Q];
              const bool pre = nt == T_ATT;
              tma_store_2d(tb, sb + (pre ? 2 * G_STAGE : OFF_Q1), c0 + (pre ? 0 : 128), row);
              tma_store_2d(tb, sb + (pre ? 3 * G_STAGE : OFF_Q1 + 16384), c0 + (pre ? 64 : 192), row);
              bulk_commit();
              bulk_wait_read<0>();
              mbar_arrive_cta(bars + B_XF, 0); mbar_arrive_cta(bars + B_XF, 1);
              if (pre) { src = sb + OFF_Q1; c1 += 128; }
            }
            if (nt != T_END) {
#pragma unroll 1
              for (int r = 0; r < 256; r += ST_ROWS) {
                tma_store_2d(&p.tm[tm], src + r * 128, c1 + (r >> 7) * 64, row + (r & 127));
                bulk_commit();
                bulk_wait_read<ST_FLY>();
              }
            }
            bulk_wait_read<0>();
            mbar_arrive(bars + B_FREE);
            if (type == T_ATT && (t & 1) && (nt == T_SA || (items[ii + 2] >> 12) == T_SA)) { mbar_arrive_cta(bars + B_XF, 0); mbar_arrive_cta(bars + B_XF, 1); }
            if (type == T_ATT) mbar_arrive(bars + B_QE + 8 * (t & 1));
            else if (nt == T_ATT) mbar_arrive(bars + B_QE + 8);
            if (z && it == 0) { fq = f; continue; }
            if (op + 1 >= npair || type == T_SA) {
              bulk_wait<0>();
              red_release(f, 1);
              if (type == T_Z2) red_release(fq, 1);
            }
          }
          if (type == T_ATT) t++;
          else if (t == 0 && (items[it + 1] >> 12) < T_ATT && (items[it + 2] >> 12) == T_ATT) {
            const int im = items[it + 2], h = (im >> 5) & 31, m = (im & 31) * 2 + rank;
            flag_wait(&g_flags[F_Q + m * 16 + (h >> 1)], 1);
            fence_async_global();
            mbar_expect_tx(bars + B_QF, 32768);
            tma_load_2d(sb + OFF_Q0, &p.tm[TM_Q], h * 128, m * 128, bars + B_QF);
            tma_load_2d(sb + OFF_Q0 + 16384, &p.tm[TM_Q], h * 128 + 64, m * 128, bars + B_QF);
          }
        }
      }
      __syncwarp();
    } else if (warp_id == 2) {
      int it = 0;
      while ((items[it] >> 12) <= T_ATT) it++;
      if ((items[it] >> 12) != T_END) {
        const bool sa = (items[it] >> 12) == T_SA;
        const int m = ((items[it] >> 5) & 31) * 2 + rank;
        if (lane == 0) {
          mbar_wait_sleep(bars + B_GO, 0, 500);
          if (sa) {
            const int b = items[it] & 3;
            flag_wait(&g_flags[F_U + m * 32], 7);
            fence_async_global();
            for (int y = b; y < OUT_PF; y += 4) tma_prefetch_2d(&p.tm[TM_U], y * 64, m * 128);
            tma_prefetch_3d(&p.tm[TM_WOUT], (m >> 1) * 64, b * 4 + rank * 2);
          }
          if (!sa) for (int y = m * 4 + (items[it] & 3); y < 16 * (NH - SA_HEADS); y += 64) tma_prefetch_3d(&p.tm[TM_WO], (2 * SA_HEADS + (y >> 3)) * 64, (y & 7) * 2);
        }
        __syncwarp();
        uint32_t cnt = 0;
        while (true) {
          const uint32_t r = __ballot_sync(0xffffffffu, ld_acquire(&g_flags[F_O + m * 32 + lane]) != 0);
          if (lane == 0) asm volatile("st.release.cta.shared.u32 [%0], %1;" :: "r"(bars + B_RDY), "r"(r) : "memory");
          if (r == ~0u) break;
          trap_if(++cnt > SPIN_LIMIT);
          __nanosleep(r >> 28 ? 20 : 300);
        }
        if (lane == 0) mbar_arrive(bars + B_XR);
      }
      __syncwarp();
    }
    cluster_sync_relaxed();
  } else {
    Cons c;
    c.sb = sb; c.warp = warp_id - 4; c.g = {0, 0}; c.fph = 1; c.rot = 0;
    if (gw < SEQ / 2) {
      float f[2][32], rs[2];
#pragma unroll
      for (int rr = 0; rr < 2; rr++) {
#pragma unroll
        for (int i = 0; i < 4; i++) {
          const uint4 v = xv[rr][i];
          f[rr][8 * i + 0] = bf_lo(v.x); f[rr][8 * i + 1] = bf_hi(v.x); f[rr][8 * i + 2] = bf_lo(v.y); f[rr][8 * i + 3] = bf_hi(v.y);
          f[rr][8 * i + 4] = bf_lo(v.z); f[rr][8 * i + 5] = bf_hi(v.z); f[rr][8 * i + 6] = bf_lo(v.w); f[rr][8 * i + 7] = bf_hi(v.w);
        }
        float s = 0.f;
#pragma unroll
        for (int i = 0; i < 32; i++) s += f[rr][i];
#pragma unroll
        for (int o = 16; o; o >>= 1) s += __shfl_xor_sync(0xffffffffu, s, o);
        const float mean = s * (1.f / DM);
        float q = 0.f;
#pragma unroll
        for (int i = 0; i < 32; i++) { f[rr][i] -= mean; q = fmaf(f[rr][i], f[rr][i], q); }
#pragma unroll
        for (int o = 16; o; o >>= 1) q += __shfl_xor_sync(0xffffffffu, q, o);
        rs[rr] = rsqrtf(q * (1.f / DM) + 1e-5f);
      }
      uint4* dst = reinterpret_cast<uint4*>(g_xn + (size_t)gw * 2 * DM) + lane;
#pragma unroll
      for (int rr = 0; rr < 2; rr++) {
        const float r = rs[rr];
#pragma unroll
        for (int i = 0; i < 4; i++) {
          const float* y = &f[rr][8 * i];
          dst[rr * 128 + i * 32] = make_uint4(pack_bf16(y[0] * r, y[1] * r), pack_bf16(y[2] * r, y[3] * r), pack_bf16(y[4] * r, y[5] * r), pack_bf16(y[6] * r, y[7] * r));
        }
      }
      __syncwarp();
      if (lane == 0) red_release(&g_flags[F_XN + (gw >> 6) * 32], 2);
    }
    asm volatile("setmaxnreg.inc.sync.aligned.u32 232;");
    asm volatile("barrier.cluster.wait.acquire.aligned;" ::: "memory");
    int natt = 0;
    int it = 0;
    uint32_t held[64];
#pragma unroll
    for (int i = 0; i < 64; i++) held[i] = 0u;
    Shadow sh = {0, 0};
    float facc[64];
#pragma unroll 1
    while (true) {
      const int item = get_item(p, it), type = item >> 12, a = (item >> 5) & 31;
      c.warp = fresh_warp();
      if (type == T_ATT) {
        const int n = ((item >> 10) & 3) + 3;
        att_run(c, p, it, n);
#pragma unroll
        for (int i = 0; i < 64; i++) held[i] = 0u;
        natt = n;
        it += n;
        c.rot = SA_ROT;
        if ((get_item(p, it) >> 12) == T_SA) continue;
#pragma unroll
        for (int i = 0; i < 64; i++) facc[i] = 0.f;
        break;
      }
      float acc[128];
      const bool sa = type == T_SA;
      bool more = type >= T_U;
      int nsteps = sa ? 28 : 16;
      const bool direct = sh.act == 2 || (get_item(p, it + 1) >> 12) >= T_ATT;
      uint32_t bias0 = 0, bias1 = 0;
#pragma unroll 1
      while (true) {
        gemm_seg(acc, held, c, p, sh, nsteps, more || !direct || sa);
        if (type == T_Q) {
#pragma unroll
          for (int i = 0; i < 128; i++) acc[i] *= SM_C;
        }
        if (!more && direct) break;
#pragma unroll
        for (int i = 0; i < 64; i++) held[i] = pack_bf16(acc[2 * i], acc[2 * i + 1]);
        if (!more) break;
        more = false;
        nsteps = sa ? 2 * SA_HEADS : 32;
        sh.act = sa ? 3 : 1;
        if (sa) {
          sh.store = 3;
        } else {
          const int row0 = (a * 2 + rank) * 128 + c.warp * 16 + (lane_id() >> 2);
          asm volatile("ld.global.nc.u16 %0, [%1];" : "=r"(bias0) : "l"(p.b_sp + row0));
          asm volatile("ld.global.nc.u16 %0, [%1];" : "=r"(bias1) : "l"(p.b_sp + row0 + 8));
        }
      }
      c.warp = fresh_warp();
      if (direct) {
        const bool pre = !sa && sh.store != 2;
        const uint32_t hb0 = bf2_mul(bias0 * 0x10001u, BF2_HALF), hb1 = bf2_mul(bias1 * 0x10001u, BF2_HALF);
        stage_acquire(c);
#pragma unroll
        for (int h = 0; h < 2; h++) {
          uint32_t pk[32];
#pragma unroll
          for (int i = 0; i < 32; i++) pk[i] = pack_bf16(acc[64 * h + 2 * i], acc[64 * h + 2 * i + 1]);
          if (type == T_U) {
#pragma unroll
            for (int i = 0; i < 32; i++) pk[i] = bf2_mul(bf2_fma(pk[i], BF2_HALF, (i & 1) ? hb1 : hb0), held[32 * h + i]);
          }
          if (h) named_sync(5);
          stage_chunks<2>(sb + (h ? OFF_Q1 : (pre ? 2 * G_STAGE : OFF_Q0)) + c.warp * 2048, (!h && pre) ? G_STAGE : 16384, pk);
          if (sa) break;
        }
        stage_commit(c);
        if (sa) {
#pragma unroll
          for (int i = 0; i < 64; i++) facc[i] = acc[64 + i];
          it++;
          break;
        }
      } else if (type == T_Q) {
        sh.store = 1;
      } else {
        sh.act = 2;
      }
      it++;
    }
    const int fin = get_item(p, it);
    if ((fin >> 12) == T_FIN) {
      c.warp = fresh_warp();
      const bool own = fin & 4;
      Ring kv = {(uint32_t)(32 * natt) % 5, ((uint32_t)(32 * natt) / 5) & 1};
      uint32_t prev = 0, ps = own ? FIN_SLOT0 : kv.s;
      fence_regs(facc);
      auto fin_steps = [&](int k0, int k1) {
#pragma unroll 1
        for (int k = k0; k < k1; k++) {
          mbar_spin(bars + B_KF + 8 * kv.s, kv.ph);
          const uint32_t st = ((c.sb & 0x3FFFF) >> 4) + ps * (KV_SLOT >> 4);
          if (++ps == 5) ps = 0;
          const uint32_t da = st + (c.warp >> 2) * 512 + (1u << 16), db = st + 1024 + ((8192u >> 4) << 16);
          wgmma_fence();
#pragma unroll
          for (int kk = 0; kk < 4; kk++) wgmma_m64n128k16_ss_tb1(facc, DESC_HI | (da + kk * 2), DESC_HI | (db + kk * 128), 1);
          wgmma_commit();
          wgmma_wait<1>();
          if (k > 2 * SA_HEADS) release_slot(c, prev);
          prev = bars + B_KE + 8 * kv.s;
          ring_adv<5>(kv);
        }
      };
      const int kp = (own && ((fin >> 5) & 31) == 7) ? 2 * SA_HEADS + 5 : 2 * NH - FIN_PREP - (own ? OWN_OFF : 0);
      fin_steps(2 * SA_HEADS, kp);
      const uint32_t ln = lane_id(), xb = own ? 1 : natt & 1;
      const uint32_t lo = c.warp * 2048 + ((ln & 15) << 7);
      uint32_t xs[32], ss[32];
      auto load_tile = [&](uint32_t base, uint32_t* d) {
#pragma unroll
        for (int i = 0; i < 8; i++) ldmatrix_x4(base + lo + (i >> 2) * 16384 + (((2 * (i & 3) + (ln >> 4)) ^ (ln & 7)) << 4), d[4 * i], d[4 * i + 1], d[4 * i + 2], d[4 * i + 3]);
      };
      const uint32_t xa = sb + (xb ? OFF_Q1 : OFF_Q0);
      mbar_spin(bars + B_QF + 8 * xb, ((natt + 1 - xb) >> 1) & 1);
      load_tile(xa, xs);
#pragma unroll
      for (int i = 0; i < 32; i++) ss[i] = 0u;
      if (!own) {
        mbar_spin(bars + B_QF + 8 * (xb ^ 1), ((natt + xb) >> 1) & 1);
        load_tile(sb + (xb ? OFF_Q0 : OFF_Q1), held + 32);
        mbar_spin(bars + B_KF + 8 * kv.s, kv.ph);
        load_tile(sb + ps * KV_SLOT, ss);
        wg_any(c.warp >= 4, false);
        release_slot(c, bars + B_KE + 8 * kv.s);
        if (++ps == 5) ps = 0;
        ring_adv<5>(kv);
      }
      float gf[64], rf[64];
#pragma unroll
      for (int i = 0; i < 32; i++) {
        const uint32_t gt = bf2_mul(held[32 + i], BF2_HALF);
        gf[2 * i] = bf_lo(gt); gf[2 * i + 1] = bf_hi(gt);
        rf[2 * i] = fmaf(bf_lo(ss[i]), gf[2 * i], bf_lo(xs[i])); rf[2 * i + 1] = fmaf(bf_hi(ss[i]), gf[2 * i + 1], bf_hi(xs[i]));
      }
      fence_regs(gf); fence_regs(rf);
      fin_steps(kp, 2 * NH);
      wgmma_wait<0>();
      fence_regs(facc);
#pragma unroll
      for (int i = 0; i < 32; i++) xs[i] = pack_bf16(fmaf(facc[2 * i], gf[2 * i], rf[2 * i]), fmaf(facc[2 * i + 1], gf[2 * i + 1], rf[2 * i + 1]));
      __syncwarp();
      stage_chunks<2>(xa + c.warp * 2048, 16384, xs);
      fence_async_smem();
      __syncwarp();
      if (elect_one()) {
        const int col = (fin & 3) * 256 + (own ? 128 : 0), row = (((fin >> 5) & 31) * 2 + rank) * 128 + c.warp * 16;
        tma_store_2d(&p.tm[TS_OUT], xa + c.warp * 2048, col, row);
        tma_store_2d(&p.tm[TS_OUT], xa + c.warp * 2048 + 16384, col + 64, row);
        bulk_commit();
        mbar_arrive(bars + B_STG);
        bulk_wait_read<0>();
      }
    }
    __syncwarp();
    cluster_sync_relaxed();
  }
}

typedef CUresult (*PFN_encodeTiled)(CUtensorMap*, CUtensorMapDataType, cuuint32_t, void*, const cuuint64_t*, const cuuint64_t*, const cuuint32_t*, const cuuint32_t*,
                                    CUtensorMapInterleave, CUtensorMapSwizzle, CUtensorMapL2promotion, CUtensorMapFloatOOBfill);
static PFN_encodeTiled s_encode = nullptr;
static void tm_2d(CUtensorMap* tm, const void* ptr, uint64_t rows, uint64_t cols, uint32_t box_rows) {
  cuuint64_t dims[2] = {cols, rows}; cuuint64_t strides[1] = {cols * 2}; cuuint32_t box[2] = {64, box_rows}; cuuint32_t es[2] = {1, 1};
  CUresult r = s_encode(tm, CU_TENSOR_MAP_DATA_TYPE_BFLOAT16, 2, (void*)ptr, dims, strides, box, es, CU_TENSOR_MAP_INTERLEAVE_NONE,
                        CU_TENSOR_MAP_SWIZZLE_128B, CU_TENSOR_MAP_L2_PROMOTION_L2_128B, CU_TENSOR_MAP_FLOAT_OOB_FILL_NONE);
  if (r != CUDA_SUCCESS) fprintf(stderr, "tensor map encode failed (%d)\n", (int)r);
}
static void tm_3d(CUtensorMap* tm, const void* ptr, uint64_t rows, uint64_t cols) {
  cuuint64_t dims[3] = {64, rows, cols / 64}; cuuint64_t strides[2] = {cols * 2, 128}; cuuint32_t box[3] = {64, 64, 2}; cuuint32_t es[3] = {1, 1, 1};
  CUresult r = s_encode(tm, CU_TENSOR_MAP_DATA_TYPE_BFLOAT16, 3, (void*)ptr, dims, strides, box, es, CU_TENSOR_MAP_INTERLEAVE_NONE,
                        CU_TENSOR_MAP_SWIZZLE_128B, CU_TENSOR_MAP_L2_PROMOTION_L2_128B, CU_TENSOR_MAP_FLOAT_OOB_FILL_NONE);
  if (r != CUDA_SUCCESS) fprintf(stderr, "tensor map encode failed (%d)\n", (int)r);
}
static inline uint16_t mk(int type, int a, int b) { return (uint16_t)(type << 12 | a << 5 | b); }

static void build_schedule(Params& P) {
  int cnt[NCLUSTER];
  for (int c = 0; c < NCLUSTER; c++) { cnt[c] = 0; for (int i = 0; i < MAXI; i++) P.items[c][i] = mk(T_END, 0, 0); }
  auto phys = [](int c) { return c == 64 ? 9 : c == 65 ? 17 : c == 9 ? 64 : c == 17 ? 65 : c; };
  auto push = [&](int c, uint16_t v) { P.items[phys(c)][cnt[c]++] = v; };
  int natt[NCLUSTER], nq[NCLUSTER];
  for (int c = 0; c < NCLUSTER; c++) { natt[c] = c < 32 ? 3 : (c < 56 ? 5 : (c < 62 ? 4 : (c < 64 ? 3 : 5))); nq[c] = c < 56 ? 1 : (c < 62 ? 7 : (c < 64 ? 9 : 6)); }
  for (int c = 0; c < 56; c++) push(c, mk(T_Z2, c % 8, c / 8));
  int qi = 0;
  for (int slot = 0; slot < 9; slot++)
    for (int c = NCLUSTER - 1; c >= 0; c--) {
      const int first = c < 56 ? 1 : 0;
      if (slot >= first && slot < first + nq[c]) { push(c, mk(T_Q, qi % 8, qi / 8)); qi++; }
    }
  for (int c = 0; c < 56; c++) push(c, mk(T_U, c % 8, c / 8));
  int ai = 0;
  for (int slot = 0; slot < 5; slot++)
    for (int c = 0; c < NCLUSTER; c++) {
      const int first = c < 32 ? 0 : 5 - natt[c];
      if (slot >= first && slot < first + natt[c]) { push(c, mk(T_ATT, ai / 8, ai % 8) | (natt[c] - 3) << 10); ai++; }
    }
  for (int c = 0; c < 32; c++) push(c, mk(T_SA, c % 8, c / 8));
  for (int c = 0; c < 64; c++) push(c, mk(T_FIN, c % 8, (c / 8) % 4 | (c < 32 ? 4 : 0)));
  if (qi != 128 || ai != 256) fprintf(stderr, "bad schedule %d %d\n", qi, ai);
}

static Params s_params;
extern "C" void kernel_launch(void* const* d_in, const int* in_sizes, int n_in, void* d_out, int out_size) {
  (void)in_sizes; (void)n_in; (void)out_size;
  if (!s_encode) {
    void* fn = nullptr; cudaDriverEntryPointQueryResult qr;
    cudaGetDriverEntryPoint("cuTensorMapEncodeTiled", &fn, cudaEnableDefault, &qr);
    s_encode = (PFN_encodeTiled)fn;
    cudaFuncSetAttribute(fused_kernel, cudaFuncAttributeMaxDynamicSharedMemorySize, SMEM_BYTES);
    build_schedule(s_params);
  }
  Params& P = s_params;
  void *xn, *q, *o, *z2, *u, *gg, *sa;
  cudaGetSymbolAddress(&gg, g_g); cudaGetSymbolAddress(&sa, g_sa);
  cudaGetSymbolAddress(&xn, g_xn); cudaGetSymbolAddress(&q, g_q); cudaGetSymbolAddress(&o, g_o);
  cudaGetSymbolAddress(&z2, g_z2); cudaGetSymbolAddress(&u, g_u);
  tm_2d(&P.tm[TM_XN], xn, SEQ, DM, 128); tm_2d(&P.tm[TM_WSP], d_in[7], SEQ, SEQ, 128); tm_2d(&P.tm[TM_U], u, SEQ, FH, 128);
  tm_2d(&P.tm[TM_O], o, SEQ, HD, 128); tm_2d(&P.tm[TM_Q], q, SEQ, HD, 128); tm_2d(&P.tm[TM_X], d_in[0], SEQ, DM, 128);
  tm_2d(&P.tm[TM_K], d_in[1], NH * SEQ, 128, 128); tm_2d(&P.tm[TM_V], d_in[2], NH * SEQ, 128, 128);
  tm_2d(&P.tm[TM_SA], sa, SEQ, DM, 128); tm_2d(&P.tm[TM_G], gg, SEQ, DM, 128); tm_2d(&P.tm[TM_WO64], d_in[4], HD, DM, 64);
  tm_3d(&P.tm[TM_WIN], d_in[6], DM, FF); tm_3d(&P.tm[TM_WQ], d_in[3], DM, HD); tm_3d(&P.tm[TM_Z2], z2, SEQ, FH);
  tm_3d(&P.tm[TM_WOUT], d_in[9], FH, DM); tm_3d(&P.tm[TM_WO], d_in[4], HD, DM);
  tm_2d(&P.tm[TS_Q], q, SEQ, HD, ST_ROWS); tm_2d(&P.tm[TS_O], o, SEQ, HD, ST_ROWS); tm_2d(&P.tm[TS_Z2], z2, SEQ, FH, ST_ROWS); tm_2d(&P.tm[TS_U], u, SEQ, FH, ST_ROWS);
  tm_2d(&P.tm[TS_SA], sa, SEQ, DM, ST_ROWS); tm_2d(&P.tm[TS_G], gg, SEQ, DM, ST_ROWS); tm_2d(&P.tm[TS_OUT], d_out, SEQ, DM, 16);
  P.x = (const bf16*)d_in[0]; P.b_sp = (const bf16*)d_in[8];
  fused_kernel<<<2 * NCLUSTER, 384, SMEM_BYTES, cudaStreamPerThread>>>(P);
}
```

```cpp
#include <cuda_runtime.h>
#include <cuda_bf16.h>
#include <cuda.h>
#include <stdint.h>
#include <stdio.h>

typedef __nv_bfloat16 bf16;

constexpr int SEQ = 2048, DM = 1024, NH = 32, HD = 4096, FF = 3584, FH = 1792;

__device__ __align__(1024) bf16 g_xn[SEQ * DM];
__device__ __align__(1024) bf16 g_q[SEQ * HD];
__device__ __align__(1024) bf16 g_o[SEQ * HD];
__device__ __align__(1024) bf16 g_z2[SEQ * FH];
__device__ __align__(1024) bf16 g_u[SEQ * FH];
__device__ __align__(1024) uint2 g_stats[SEQ * 8];
__device__ __align__(1024) bf16 g_g[SEQ * DM];
__device__ __align__(1024) bf16 g_sa[SEQ * DM];
constexpr int F_XN = 0;
constexpr int F_Z2 = 512;
constexpr int F_Q = 768;
constexpr int F_U = 1024;
constexpr int F_O = 1536;
constexpr int F_S = 2048;
constexpr int F_TOTAL = 2112;
__device__ __align__(1024) unsigned g_flags[F_TOTAL];
__device__ unsigned g_done;
__device__ unsigned g_epoch;

__device__ __forceinline__ uint32_t smem_u32(const void* p) { return (uint32_t)__cvta_generic_to_shared(p); }
__device__ __forceinline__ void mbar_init(uint32_t bar, uint32_t cnt) { asm volatile("mbarrier.init.shared::cta.b64 [%0], %1;" :: "r"(bar), "r"(cnt)); }
__device__ __forceinline__ void mbar_expect_tx(uint32_t bar, uint32_t bytes) { asm volatile("mbarrier.arrive.expect_tx.shared::cta.b64 _, [%0], %1;" :: "r"(bar), "r"(bytes) : "memory"); }
__device__ __forceinline__ void mbar_arrive(uint32_t bar) { asm volatile("mbarrier.arrive.shared::cta.b64 _, [%0];" :: "r"(bar) : "memory"); }
__device__ __forceinline__ void mbar_arrive_cta(uint32_t bar, uint32_t cta) {
  asm volatile("{\n.reg .b32 ra;\nmapa.shared::cluster.u32 ra, %0, %1;\nmbarrier.arrive.shared::cluster.b64 _, [ra];\n}" :: "r"(bar), "r"(cta) : "memory");
}
__device__ __forceinline__ bool mbar_test(uint32_t bar, uint32_t parity) {
  uint32_t ok;
  asm volatile("{\n.reg .pred P1;\nmbarrier.test_wait.parity.shared::cta.b64 P1, [%1], %2;\nselp.u32 %0, 1, 0, P1;\n}" : "=r"(ok) : "r"(bar), "r"(parity) : "memory");
  return ok;
}
constexpr uint32_t SPIN_LIMIT = 1u << 22;
__device__ __forceinline__ void trap_if(bool c) { asm volatile("{\n.reg .pred P;\nsetp.ne.u32 P, %0, 0;\n@P trap;\n}" :: "r"((uint32_t)c)); }
__device__ __forceinline__ void mbar_wait(uint32_t bar, uint32_t parity) {
  asm volatile("{\n.reg .pred P1;\n.reg .u32 n;\nmbarrier.try_wait.parity.shared::cta.b64 P1, [%0], %1;\n@P1 bra DONE;\nmov.u32 n, 0;\n"
               "LOOP:\nmbarrier.try_wait.parity.shared::cta.b64 P1, [%0], %1;\n@P1 bra DONE;\nadd.u32 n, n, 1;\nsetp.gt.u32 P1, n, %2;\n@P1 trap;\nbra LOOP;\nDONE:\n}"
               :: "r"(bar), "r"(parity), "n"(SPIN_LIMIT) : "memory");
}
__device__ __forceinline__ void mbar_spin(uint32_t bar, uint32_t parity) {
  asm volatile("{\n.reg .pred P1;\nLOOP:\nmbarrier.try_wait.parity.shared::cta.b64 P1, [%0], %1;\n@!P1 bra LOOP;\n}" :: "r"(bar), "r"(parity) : "memory");
}
__device__ __forceinline__ void mbar_wait_sleep(uint32_t bar, uint32_t parity, uint32_t ns) {
  uint32_t n = 0;
  while (!mbar_test(bar, parity)) { trap_if(++n > SPIN_LIMIT * 4); __nanosleep(ns); }
}
__device__ __forceinline__ void tma_load_2d(uint32_t dst, const CUtensorMap* tm, int c0, int c1, uint32_t bar) {
  asm volatile("cp.async.bulk.tensor.2d.shared::cluster.global.mbarrier::complete_tx::bytes [%0], [%1, {%3, %4}], [%2];"
    :: "r"(dst), "l"(tm), "r"(bar), "r"(c0), "r"(c1) : "memory");
}
__device__ __forceinline__ void tma_load_2d_mc(uint32_t dst, const CUtensorMap* tm, int c0, int c1, uint32_t bar) {
  asm volatile("cp.async.bulk.tensor.2d.shared::cluster.global.mbarrier::complete_tx::bytes.multicast::cluster [%0], [%1, {%3, %4}], [%2], %5;"
    :: "r"(dst), "l"(tm), "r"(bar), "r"(c0), "r"(c1), "h"((uint16_t)3) : "memory");
}
__device__ __forceinline__ void tma_prefetch_2d(const CUtensorMap* tm, int c0, int c1) {
  asm volatile("cp.async.bulk.prefetch.tensor.2d.L2.global [%0, {%1, %2}];" :: "l"(tm), "r"(c0), "r"(c1) : "memory");
}
__device__ __forceinline__ void tma_prefetch_3d(const CUtensorMap* tm, int c1, int c2) {
  asm volatile("cp.async.bulk.prefetch.tensor.3d.L2.global [%0, {%1, %2, %3}];" :: "l"(tm), "r"(0), "r"(c1), "r"(c2) : "memory");
}
__device__ __forceinline__ void tma_load_3d_mc(uint32_t dst, const CUtensorMap* tm, int c1, int c2, uint32_t bar) {
  asm volatile("cp.async.bulk.tensor.3d.shared::cluster.global.mbarrier::complete_tx::bytes.multicast::cluster [%0], [%1, {%3, %4, %5}], [%2], %6;"
    :: "r"(dst), "l"(tm), "r"(bar), "r"(0), "r"(c1), "r"(c2), "h"((uint16_t)3) : "memory");
}
__device__ __forceinline__ void tma_store_2d(const CUtensorMap* tm, uint32_t src, int c0, int c1) {
  asm volatile("cp.async.bulk.tensor.2d.global.shared::cta.bulk_group [%0, {%2, %3}], [%1];" :: "l"(tm), "r"(src), "r"(c0), "r"(c1) : "memory");
}
__device__ __forceinline__ void bulk_commit() { asm volatile("cp.async.bulk.commit_group;" ::: "memory"); }
template <int N> __device__ __forceinline__ void bulk_wait_read() { asm volatile("cp.async.bulk.wait_group.read %0;" :: "n"(N) : "memory"); }
template <int N> __device__ __forceinline__ void bulk_wait() { asm volatile("cp.async.bulk.wait_group %0;" :: "n"(N) : "memory"); }
__device__ __forceinline__ void fence_async_smem() { asm volatile("fence.proxy.async.shared::cta;" ::: "memory"); }
__device__ __forceinline__ void fence_async_global() { asm volatile("fence.proxy.async.global;" ::: "memory"); }
__device__ __forceinline__ void wgmma_fence() { asm volatile("wgmma.fence.sync.aligned;" ::: "memory"); }
__device__ __forceinline__ void wgmma_commit() { asm volatile("wgmma.commit_group.sync.aligned;" ::: "memory"); }
template <int N> __device__ __forceinline__ void wgmma_wait() { asm volatile("wgmma.wait_group.sync.aligned %0;" :: "n"(N) : "memory"); }
__device__ __forceinline__ uint64_t make_desc(uint32_t addr, uint32_t lbo, uint32_t sbo) {
  return (uint64_t)((addr & 0x3FFFF) >> 4) | ((uint64_t)(lbo >> 4) << 16) | ((uint64_t)(sbo >> 4) << 32) | (1ull << 62);
}
template <int N> __device__ __forceinline__ void fence_regs(float (&d)[N]) {
#pragma unroll
  for (int i = 0; i < N; i++) asm volatile("" : "+f"(d[i]) :: "memory");
}
template <int N> __device__ __forceinline__ void fence_regs(uint32_t (&d)[N]) {
#pragma unroll
  for (int i = 0; i < N; i++) asm volatile("" : "+r"(d[i]) :: "memory");
}
__device__ __forceinline__ void named_sync(int id) { asm volatile("bar.sync %0, 256;" :: "r"(id) : "memory"); }
__device__ __forceinline__ bool wg_any(bool w, bool v) {
  uint32_t r;
  asm volatile("{\n.reg .pred p, q;\nsetp.ne.u32 p, %1, 0;\nbar.red.or.pred q, %2, 128, p;\nselp.u32 %0, 1, 0, q;\n}" : "=r"(r) : "r"((uint32_t)v), "r"(w ? 4 : 3) : "memory");
  return __any_sync(0xffffffffu, r);
}
__device__ __forceinline__ int fresh_warp() { uint32_t t; asm volatile("mov.u32 %0, %%tid.x;" : "=r"(t)); return __shfl_sync(0xffffffffu, (int)(t >> 5) - 4, 0); }
__device__ __forceinline__ void cluster_sync_relaxed() { asm volatile("barrier.cluster.arrive.relaxed.aligned;\nbarrier.cluster.wait.aligned;" ::: "memory"); }
__device__ __forceinline__ unsigned ld_acquire(const unsigned* p) { unsigned v; asm volatile("ld.acquire.gpu.global.u32 %0, [%1];" : "=r"(v) : "l"(p) : "memory"); return v; }
__device__ __forceinline__ void red_release(unsigned* p, unsigned v) { asm volatile("red.release.gpu.global.add.u32 [%0], %1;" :: "l"(p), "r"(v) : "memory"); }
__device__ __forceinline__ void flag_wait(const unsigned* p, unsigned target) {
  uint32_t n = 0;
  while (ld_acquire(p) < target) { trap_if(++n > SPIN_LIMIT); __nanosleep(20); }
}
__device__ __forceinline__ void st_tagged(uint2* p, float a, float b, uint32_t tag) {
  asm volatile("{\n.reg .b64 x;\nmov.b64 x, {%1, %2};\nst.relaxed.gpu.global.b64 [%0], x;\n}" :: "l"(p),
               "r"((__float_as_uint(a) & ~63u) | (tag & 63u)), "r"((__float_as_uint(b) & ~63u) | (tag >> 6)) : "memory");
}
__device__ __forceinline__ uint4 ld_tagged2(const uint2* p) {
  uint4 v;
  asm volatile("{\n.reg .b64 x, y;\nld.relaxed.gpu.global.v2.b64 {x, y}, [%4];\nmov.b64 {%0, %1}, x;\nmov.b64 {%2, %3}, y;\n}" : "=r"(v.x), "=r"(v.y), "=r"(v.z), "=r"(v.w) : "l"(p) : "memory");
  return v;
}
__device__ __forceinline__ bool tag_ok(uint32_t a, uint32_t b, uint32_t tag) { return ((a & 63u) | ((b & 63u) << 6)) == tag; }
__device__ __forceinline__ uint32_t pack_bf16(float lo, float hi) { uint32_t r; asm("cvt.rn.bf16x2.f32 %0, %1, %2;" : "=r"(r) : "f"(hi), "f"(lo)); return r; }
__device__ __forceinline__ uint32_t bf2_fma(uint32_t a, uint32_t b, uint32_t c) { uint32_t r; asm("fma.rn.bf16x2 %0, %1, %2, %3;" : "=r"(r) : "r"(a), "r"(b), "r"(c)); return r; }
__device__ __forceinline__ uint32_t bf2_mul(uint32_t a, uint32_t b) { uint32_t r; asm("mul.rn.bf16x2 %0, %1, %2;" : "=r"(r) : "r"(a), "r"(b)); return r; }
__device__ __forceinline__ uint32_t bf2_add(uint32_t a, uint32_t b) { uint32_t r; asm("add.rn.bf16x2 %0, %1, %2;" : "=r"(r) : "r"(a), "r"(b)); return r; }
constexpr uint32_t BF2_HALF = 0x3f003f00u;
__device__ __forceinline__ float bf_lo(uint32_t v) { return __uint_as_float(v << 16); }
__device__ __forceinline__ float bf_hi(uint32_t v) { return __uint_as_float(v & 0xffff0000u); }
__device__ __forceinline__ float ex2(float x) { float y; asm("ex2.approx.ftz.f32 %0, %1;" : "=f"(y) : "f"(x)); return y; }
__device__ __forceinline__ float tanh_fast(float x) { float y; asm("tanh.approx.f32 %0, %1;" : "=f"(y) : "f"(x)); return y; }
__device__ __forceinline__ void stmatrix_x4(uint32_t addr, uint32_t a, uint32_t b, uint32_t c, uint32_t d) {
  asm volatile("stmatrix.sync.aligned.m8n8.x4.shared.b16 [%0], {%1, %2, %3, %4};" :: "r"(addr), "r"(a), "r"(b), "r"(c), "r"(d) : "memory");
}
__device__ __forceinline__ void ldmatrix_x4(uint32_t addr, uint32_t& a, uint32_t& b, uint32_t& c, uint32_t& d) {
  asm volatile("ldmatrix.sync.aligned.m8n8.x4.shared.b16 {%0, %1, %2, %3}, [%4];" : "=r"(a), "=r"(b), "=r"(c), "=r"(d) : "r"(addr) : "memory");
}
__device__ __forceinline__ uint32_t lane_id() { uint32_t l; asm volatile("mov.u32 %0, %%laneid;" : "=r"(l)); return l; }
__device__ __forceinline__ bool elect_one() {
  uint32_t r;
  asm volatile("{\n.reg .pred P;\nelect.sync _|P, 0xffffffff;\nselp.u32 %0, 1, 0, P;\n}" : "=r"(r));
  return r;
}

__device__ __forceinline__ void wgmma_m64n128k16_ss_tb0(float (&d)[64], uint64_t da, uint64_t db, int scale_d) {
  asm volatile("{\n.reg .pred p;\nsetp.ne.b32 p, %66, 0;\n"
    "wgmma.mma_async.sync.aligned.m64n128k16.f32.bf16.bf16 "
    "{%0, %1, %2, %3, %4, %5, %6, %7, %8, %9, %10, %11, %12, %13, %14, %15, %16, %17, %18, %19, %20, %21, %22, %23, %24, %25, %26, %27, %28, %29, %30, %31, %32, %33, %34, %35, %36, %37, %38, %39, %40, %41, %42, %43, %44, %45, %46, %47, %48, %49, %50, %51, %52, %53, %54, %55, %56, %57, %58, %59, %60, %61, %62, %63}, "
    "%64, %65, p, 1, 1, 0, 0;\n}\n"
    : "+f"(d[0]), "+f"(d[1]), "+f"(d[2]), "+f"(d[3]), "+f"(d[4]), "+f"(d[5]), "+f"(d[6]), "+f"(d[7]), "+f"(d[8]), "+f"(d[9]), "+f"(d[10]), "+f"(d[11]), "+f"(d[12]), "+f"(d[13]), "+f"(d[14]), "+f"(d[15]), "+f"(d[16]), "+f"(d[17]), "+f"(d[18]), "+f"(d[19]), "+f"(d[20]), "+f"(d[21]), "+f"(d[22]), "+f"(d[23]), "+f"(d[24]), "+f"(d[25]), "+f"(d[26]), "+f"(d[27]), "+f"(d[28]), "+f"(d[29]), "+f"(d[30]), "+f"(d[31]), "+f"(d[32]), "+f"(d[33]), "+f"(d[34]), "+f"(d[35]), "+f"(d[36]), "+f"(d[37]), "+f"(d[38]), "+f"(d[39]), "+f"(d[40]), "+f"(d[41]), "+f"(d[42]), "+f"(d[43]), "+f"(d[44]), "+f"(d[45]), "+f"(d[46]), "+f"(d[47]), "+f"(d[48]), "+f"(d[49]), "+f"(d[50]), "+f"(d[51]), "+f"(d[52]), "+f"(d[53]), "+f"(d[54]), "+f"(d[55]), "+f"(d[56]), "+f"(d[57]), "+f"(d[58]), "+f"(d[59]), "+f"(d[60]), "+f"(d[61]), "+f"(d[62]), "+f"(d[63])
    : "l"(da), "l"(db), "r"(scale_d));
}
__device__ __forceinline__ void wgmma_m64n256k16_ss_tb1(float (&d)[128], uint64_t da, uint64_t db, int scale_d) {
  asm volatile("{\n.reg .pred p;\nsetp.ne.b32 p, %130, 0;\n"
    "wgmma.mma_async.sync.aligned.m64n256k16.f32.bf16.bf16 "
    "{%0, %1, %2, %3, %4, %5, %6, %7, %8, %9, %10, %11, %12, %13, %14, %15, %16, %17, %18, %19, %20, %21, %22, %23, %24, %25, %26, %27, %28, %29, %30, %31, %32, %33, %34, %35, %36, %37, %38, %39, %40, %41, %42, %43, %44, %45, %46, %47, %48, %49, %50, %51, %52, %53, %54, %55, %56, %57, %58, %59, %60, %61, %62, %63, %64, %65, %66, %67, %68, %69, %70, %71, %72, %73, %74, %75, %76, %77, %78, %79, %80, %81, %82, %83, %84, %85, %86, %87, %88, %89, %90, %91, %92, %93, %94, %95, %96, %97, %98, %99, %100, %101, %102, %103, %104, %105, %106, %107, %108, %109, %110, %111, %112, %113, %114, %115, %116, %117, %118, %119, %120, %121, %122, %123, %124, %125, %126, %127}, "
    "%128, %129, p, 1, 1, 0, 1;\n}\n"
    : "+f"(d[0]), "+f"(d[1]), "+f"(d[2]), "+f"(d[3]), "+f"(d[4]), "+f"(d[5]), "+f"(d[6]), "+f"(d[7]), "+f"(d[8]), "+f"(d[9]), "+f"(d[10]), "+f"(d[11]), "+f"(d[12]), "+f"(d[13]), "+f"(d[14]), "+f"(d[15]), "+f"(d[16]), "+f"(d[17]), "+f"(d[18]), "+f"(d[19]), "+f"(d[20]), "+f"(d[21]), "+f"(d[22]), "+f"(d[23]), "+f"(d[24]), "+f"(d[25]), "+f"(d[26]), "+f"(d[27]), "+f"(d[28]), "+f"(d[29]), "+f"(d[30]), "+f"(d[31]), "+f"(d[32]), "+f"(d[33]), "+f"(d[34]), "+f"(d[35]), "+f"(d[36]), "+f"(d[37]), "+f"(d[38]), "+f"(d[39]), "+f"(d[40]), "+f"(d[41]), "+f"(d[42]), "+f"(d[43]), "+f"(d[44]), "+f"(d[45]), "+f"(d[46]), "+f"(d[47]), "+f"(d[48]), "+f"(d[49]), "+f"(d[50]), "+f"(d[51]), "+f"(d[52]), "+f"(d[53]), "+f"(d[54]), "+f"(d[55]), "+f"(d[56]), "+f"(d[57]), "+f"(d[58]), "+f"(d[59]), "+f"(d[60]), "+f"(d[61]), "+f"(d[62]), "+f"(d[63]), "+f"(d[64]), "+f"(d[65]), "+f"(d[66]), "+f"(d[67]), "+f"(d[68]), "+f"(d[69]), "+f"(d[70]), "+f"(d[71]), "+f"(d[72]), "+f"(d[73]), "+f"(d[74]), "+f"(d[75]), "+f"(d[76]), "+f"(d[77]), "+f"(d[78]), "+f"(d[79]), "+f"(d[80]), "+f"(d[81]), "+f"(d[82]), "+f"(d[83]), "+f"(d[84]), "+f"(d[85]), "+f"(d[86]), "+f"(d[87]), "+f"(d[88]), "+f"(d[89]), "+f"(d[90]), "+f"(d[91]), "+f"(d[92]), "+f"(d[93]), "+f"(d[94]), "+f"(d[95]), "+f"(d[96]), "+f"(d[97]), "+f"(d[98]), "+f"(d[99]), "+f"(d[100]), "+f"(d[101]), "+f"(d[102]), "+f"(d[103]), "+f"(d[104]), "+f"(d[105]), "+f"(d[106]), "+f"(d[107]), "+f"(d[108]), "+f"(d[109]), "+f"(d[110]), "+f"(d[111]), "+f"(d[112]), "+f"(d[113]), "+f"(d[114]), "+f"(d[115]), "+f"(d[116]), "+f"(d[117]), "+f"(d[118]), "+f"(d[119]), "+f"(d[120]), "+f"(d[121]), "+f"(d[122]), "+f"(d[123]), "+f"(d[124]), "+f"(d[125]), "+f"(d[126]), "+f"(d[127])
    : "l"(da), "l"(db), "r"(scale_d));
}
__device__ __forceinline__ void wgmma_m64n128k16_rs_tb1(float (&d)[64], uint32_t a0, uint32_t a1, uint32_t a2, uint32_t a3, uint64_t db, int scale_d) {
  asm volatile("{\n.reg .pred p;\nsetp.ne.b32 p, %69, 0;\n"
    "wgmma.mma_async.sync.aligned.m64n128k16.f32.bf16.bf16 "
    "{%0, %1, %2, %3, %4, %5, %6, %7, %8, %9, %10, %11, %12, %13, %14, %15, %16, %17, %18, %19, %20, %21, %22, %23, %24, %25, %26, %27, %28, %29, %30, %31, %32, %33, %34, %35, %36, %37, %38, %39, %40, %41, %42, %43, %44, %45, %46, %47, %48, %49, %50, %51, %52, %53, %54, %55, %56, %57, %58, %59, %60, %61, %62, %63}, "
    "{%64, %65, %66, %67}, %68, p, 1, 1, 1;\n}\n"
    : "+f"(d[0]), "+f"(d[1]), "+f"(d[2]), "+f"(d[3]), "+f"(d[4]), "+f"(d[5]), "+f"(d[6]), "+f"(d[7]), "+f"(d[8]), "+f"(d[9]), "+f"(d[10]), "+f"(d[11]), "+f"(d[12]), "+f"(d[13]), "+f"(d[14]), "+f"(d[15]), "+f"(d[16]), "+f"(d[17]), "+f"(d[18]), "+f"(d[19]), "+f"(d[20]), "+f"(d[21]), "+f"(d[22]), "+f"(d[23]), "+f"(d[24]), "+f"(d[25]), "+f"(d[26]), "+f"(d[27]), "+f"(d[28]), "+f"(d[29]), "+f"(d[30]), "+f"(d[31]), "+f"(d[32]), "+f"(d[33]), "+f"(d[34]), "+f"(d[35]), "+f"(d[36]), "+f"(d[37]), "+f"(d[38]), "+f"(d[39]), "+f"(d[40]), "+f"(d[41]), "+f"(d[42]), "+f"(d[43]), "+f"(d[44]), "+f"(d[45]), "+f"(d[46]), "+f"(d[47]), "+f"(d[48]), "+f"(d[49]), "+f"(d[50]), "+f"(d[51]), "+f"(d[52]), "+f"(d[53]), "+f"(d[54]), "+f"(d[55]), "+f"(d[56]), "+f"(d[57]), "+f"(d[58]), "+f"(d[59]), "+f"(d[60]), "+f"(d[61]), "+f"(d[62]), "+f"(d[63])
    : "r"(a0), "r"(a1), "r"(a2), "r"(a3), "l"(db), "r"(scale_d));
}
__device__ __forceinline__ void wgmma_m64n128k16_ss_tb1(float (&d)[64], uint64_t da, uint64_t db, int scale_d) {
  asm volatile("{\n.reg .pred p;\nsetp.ne.b32 p, %66, 0;\n"
    "wgmma.mma_async.sync.aligned.m64n128k16.f32.bf16.bf16 "
    "{%0, %1, %2, %3, %4, %5, %6, %7, %8, %9, %10, %11, %12, %13, %14, %15, %16, %17, %18, %19, %20, %21, %22, %23, %24, %25, %26, %27, %28, %29, %30, %31, %32, %33, %34, %35, %36, %37, %38, %39, %40, %41, %42, %43, %44, %45, %46, %47, %48, %49, %50, %51, %52, %53, %54, %55, %56, %57, %58, %59, %60, %61, %62, %63}, "
    "%64, %65, p, 1, 1, 0, 1;\n}\n"
    : "+f"(d[0]), "+f"(d[1]), "+f"(d[2]), "+f"(d[3]), "+f"(d[4]), "+f"(d[5]), "+f"(d[6]), "+f"(d[7]), "+f"(d[8]), "+f"(d[9]), "+f"(d[10]), "+f"(d[11]), "+f"(d[12]), "+f"(d[13]), "+f"(d[14]), "+f"(d[15]), "+f"(d[16]), "+f"(d[17]), "+f"(d[18]), "+f"(d[19]), "+f"(d[20]), "+f"(d[21]), "+f"(d[22]), "+f"(d[23]), "+f"(d[24]), "+f"(d[25]), "+f"(d[26]), "+f"(d[27]), "+f"(d[28]), "+f"(d[29]), "+f"(d[30]), "+f"(d[31]), "+f"(d[32]), "+f"(d[33]), "+f"(d[34]), "+f"(d[35]), "+f"(d[36]), "+f"(d[37]), "+f"(d[38]), "+f"(d[39]), "+f"(d[40]), "+f"(d[41]), "+f"(d[42]), "+f"(d[43]), "+f"(d[44]), "+f"(d[45]), "+f"(d[46]), "+f"(d[47]), "+f"(d[48]), "+f"(d[49]), "+f"(d[50]), "+f"(d[51]), "+f"(d[52]), "+f"(d[53]), "+f"(d[54]), "+f"(d[55]), "+f"(d[56]), "+f"(d[57]), "+f"(d[58]), "+f"(d[59]), "+f"(d[60]), "+f"(d[61]), "+f"(d[62]), "+f"(d[63])
    : "l"(da), "l"(db), "r"(scale_d));
}


enum { TM_XN, TM_WSP, TM_U, TM_O, TM_Q, TM_X, TM_SA, TM_G, TM_K, TM_V, TM_WO64,
       TM_WIN, TM_WQ, TM_Z2, TM_WOUT, TM_WO, TS_Q, TS_O, TS_Z2, TS_U, TS_SA, TS_G, TS_OUT, TM_COUNT };
enum { T_Z2 = 0, T_Q = 1, T_U = 2, T_ATT = 3, T_SA = 4, T_FIN = 5, T_END = 7 };
constexpr int NCLUSTER = 66, MAXI = 14;
struct alignas(64) Params {
  const bf16* x;
  const bf16* b_sp;
  CUtensorMap tm[TM_COUNT];
  uint16_t items[NCLUSTER][MAXI];
};

constexpr uint32_t G_STAGE = 49152, G_A = 16384, KV_SLOT = 32768;
constexpr uint32_t OFF_Q1 = 163840, OFF_Q0 = 196608, OFF_BAR = 229376, OFF_LN = OFF_BAR + 256, SMEM_BYTES = OFF_LN + 1024;
constexpr uint32_t B_GF = 0, B_GE = 32, B_KF = 64, B_KE = 104, B_QF = 144, B_QE = 160, B_XF = 176, B_XR = 184, B_STG = 192, B_FREE = 200, B_GO = 208, B_LN = 216, B_TAG = 224, B_RDY = 228, B_PROG = 232, B_PUB = 248;
constexpr int SA_HEADS = 18;
constexpr int SW_NS = 40;
constexpr int ST_ROWS = 16;
constexpr int ST_FLY = 2;
constexpr int KV_PF = 4;
constexpr int FIN_PREP = 8;
constexpr int OWN_OFF = 8;
constexpr int Z_DELAY = 3;
constexpr int SW_ATT = 800;
constexpr int OUT_PF = 8;
constexpr int SA_ROT = 1;
constexpr uint32_t FIN_SLOT0 = (0x0320u >> (4 * ((28 + 2 * SA_HEADS + SA_ROT) & 3))) & 15;
constexpr float SM_C = 0.08838834764831845f * 1.4426950408889634f;
constexpr float GELU_A = 0.7978845608028654f, GELU_B = 0.7978845608028654f * 0.044715f;
constexpr float SM_LO = 1e-7f, SM_HI = 1e12f;
constexpr float SM_THR = 1024.f;


extern __shared__ __align__(1024) uint8_t smem_raw[];
__device__ __forceinline__ uint32_t smem_base() { return smem_u32(smem_raw); }

struct Ring { uint32_t s, ph; };
template <int N> __device__ __forceinline__ void ring_adv(Ring& r) { if (++r.s == N) { r.s = 0; r.ph ^= 1; } }

__device__ __forceinline__ int get_item(const Params& p, int i) {
  uint32_t b; asm volatile("mov.u32 %0, %%ctaid.x;" : "=r"(b));
  return p.items[b >> 1][i];
}
struct Cons {
  uint32_t sb;
  int warp;
  Ring g;
  uint32_t rot;
  uint32_t fph;
};

__device__ __forceinline__ void stage_acquire(const Cons& c) { mbar_spin(c.sb + OFF_BAR + B_FREE, c.fph); }
__device__ __forceinline__ void stage_commit(Cons& c) {
  __syncwarp();
  if (lane_id() == 0) mbar_arrive(c.sb + OFF_BAR + B_STG);
  c.fph ^= 1;
}

__device__ __forceinline__ void release_slot(const Cons& c, uint32_t bar) {
  if (lane_id() == 0 && (c.warp & 3) < 2) mbar_arrive_cta(bar, c.warp & 1);
}
constexpr uint64_t DESC_HI = (uint64_t)0x40000040u << 32;

template <bool FIRST> __device__ __forceinline__ void gemm_step(float (&acc)[128], Cons& c) {
  mbar_spin(c.sb + OFF_BAR + B_GF + 8 * c.g.s, c.g.ph);
  const uint32_t st = ((c.sb & 0x3FFFF) >> 4) + ((c.g.s + c.rot) & 3) * (G_STAGE >> 4);
  const uint32_t da = st + (c.warp >> 2) * 512 + (1u << 16), db = st + (G_A >> 4) + ((8192u >> 4) << 16);
  wgmma_fence();
#pragma unroll
  for (int kk = 0; kk < 4; kk++) wgmma_m64n256k16_ss_tb1(acc, DESC_HI | (da + kk * 2), DESC_HI | (db + kk * 128), !(FIRST && kk == 0));
  wgmma_commit();
}

template <int N> __device__ __forceinline__ void stage_chunks(uint32_t buf, uint32_t stride, const uint32_t* pk) {
  const uint32_t ln = lane_id();
  const uint32_t a = buf + ((ln & 15) << 7);
  const uint32_t x = ln & 7, hi = ln >> 4;
#pragma unroll
  for (int i = 0; i < 4 * N; i++) stmatrix_x4(a + (i >> 2) * stride + (((2 * (i & 3) + hi) ^ x) << 4), pk[4 * i], pk[4 * i + 1], pk[4 * i + 2], pk[4 * i + 3]);
}

__device__ __forceinline__ float act2_fn(float x, float a, float b) {
  return fmaf(x, tanh_fast(x * fmaf(x * x, b, a)), x);
}
__device__ __forceinline__ float quad_sum(float v) { v += __shfl_xor_sync(0xffffffffu, v, 1); v += __shfl_xor_sync(0xffffffffu, v, 2); return v; }
__device__ __forceinline__ float quad_max(float v) { v = fmaxf(v, __shfl_xor_sync(0xffffffffu, v, 1)); v = fmaxf(v, __shfl_xor_sync(0xffffffffu, v, 2)); return v; }

__device__ __forceinline__ uint32_t load_tag(const Cons& c) { uint32_t t; asm volatile("ld.volatile.shared.u32 %0, [%1];" : "=r"(t) : "r"(c.sb + OFF_BAR + B_TAG)); return t; }

struct Shadow {
  int act;
  int store;
};
__device__ __forceinline__ void rotate16(uint32_t (&h)[64]) {
#pragma unroll
  for (int i = 0; i < 16; i++)
    asm volatile("{\n.reg .b32 t;\nmov.b32 t, %0;\nmov.b32 %0, %1;\nmov.b32 %1, %2;\nmov.b32 %2, %3;\nmov.b32 %3, t;\n}" : "+r"(h[i]), "+r"(h[i + 16]), "+r"(h[i + 32]), "+r"(h[i + 48]));
}

template <int O>
__device__ __forceinline__ void act_block(uint32_t (&held)[64], float ca, float cb, bool first, float& u0, float& u1, float& s0, float& s1, float& q0, float& q1) {
#pragma unroll
  for (int i = O; i < O + 4; i += 2) {
    const float a0 = act2_fn(bf_lo(held[i]), ca, cb), a1 = act2_fn(bf_hi(held[i]), ca, cb);
    const float b0 = act2_fn(bf_lo(held[i + 1]), ca, cb), b1 = act2_fn(bf_hi(held[i + 1]), ca, cb);
    if (i == 0 && first) { u0 = a0; u1 = b0; }
    float d;
    d = a0 - u0; s0 += d; q0 = fmaf(d, d, q0); d = a1 - u0; s0 += d; q0 = fmaf(d, d, q0);
    d = b0 - u1; s1 += d; q1 = fmaf(d, d, q1); d = b1 - u1; s1 += d; q1 = fmaf(d, d, q1);
    held[i] = pack_bf16(a0, a1); held[i + 1] = pack_bf16(b0, b1);
  }
}

template <int O> __device__ __forceinline__ void stage_half(Cons& c, uint32_t (&held)[64], int mode) {
  if (mode == 2) {
    uint32_t a0, a1, r0, r1;
    const uint32_t la = c.sb + OFF_LN + (c.warp * 16 + (lane_id() >> 2)) * 8;
    mbar_spin(c.sb + OFF_BAR + B_LN, 0);
    asm volatile("ld.shared.v2.b32 {%0, %1}, [%2];" : "=r"(r0), "=r"(a0) : "r"(la));
    asm volatile("ld.shared.v2.b32 {%0, %1}, [%2];" : "=r"(r1), "=r"(a1) : "r"(la + 64));
#pragma unroll
    for (int i = O; i < O + 32; i += 2) { held[i] = bf2_mul(bf2_add(held[i], a0), r0); held[i + 1] = bf2_mul(bf2_add(held[i + 1], a1), r1); }
  }
  if (O == 0 && mode == 3) {
#pragma unroll
    for (int i = 0; i < 64; i++) held[i] = bf2_mul(held[i], BF2_HALF);
  }
  stage_acquire(c);
  stage_chunks<2>(c.sb + OFF_Q0 + c.warp * 2048, 16384, held + O);
  stage_commit(c);
}

__device__ __forceinline__ void gemm_seg(float (&acc)[128], uint32_t (&held)[64], Cons& c, const Params& p, Shadow& sh, int nsteps, bool hold) {
  const bool elected = lane_id() == 0 && (c.warp & 3) < 2;
  uint32_t rel;
  asm("mapa.shared::cluster.u32 %0, %1, %2;" : "=r"(rel) : "r"(c.sb + OFF_BAR + B_GE), "r"((uint32_t)(c.warp & 1)));
  gemm_step<true>(acc, c);
  ring_adv<4>(c.g);
  int k = 1;
#define G_STEP()                                                                                                       \
  { gemm_step<false>(acc, c);                                                                                          \
    wgmma_wait<1>();                                                                                                   \
    if (elected) asm volatile("mbarrier.arrive.shared::cluster.b64 _, [%0];" :: "r"(rel + 8 * ((c.g.s - 1) & 3)) : "memory"); \
    ring_adv<4>(c.g);                                                                                                  \
    k++; }
  if (sh.act != 0) {
    float u0 = 0.f, u1 = 0.f, s0 = 0.f, s1 = 0.f, q0 = 0.f, q1 = 0.f;
    const float ca = sh.act == 3 ? 0.5f : GELU_A, cb = sh.act == 3 ? 0.f : GELU_B;
#pragma unroll 1
    while (true) {
      act_block<0>(held, ca, cb, k == 1, u0, u1, s0, s1, q0, q1);
      G_STEP()
      act_block<4>(held, ca, cb, false, u0, u1, s0, s1, q0, q1);
      G_STEP()
      act_block<8>(held, ca, cb, false, u0, u1, s0, s1, q0, q1);
      G_STEP()
      act_block<12>(held, ca, cb, false, u0, u1, s0, s1, q0, q1);
      rotate16(held);
      if (k == 16) break;
      G_STEP()
    }
    if (sh.act == 2) {
      const int zi = get_item(p, 0);
      const int ln = lane_id(), row0 = (((zi >> 5) & 31) * 2 + (blockIdx.x & 1)) * 128 + c.warp * 16 + (ln >> 2), ql = ln & 3;
      const float m0 = fmaf(s0, 1.f / 64, u0), m1 = fmaf(s1, 1.f / 64, u1);
      q0 -= s0 * s0 * (1.f / 64); q1 -= s1 * s1 * (1.f / 64);
      const float mu0 = quad_sum(m0) * 0.25f, mu1 = quad_sum(m1) * 0.25f;
      q0 = quad_sum(fmaf(64.f * (m0 - mu0), m0 - mu0, q0)); q1 = quad_sum(fmaf(64.f * (m1 - mu1), m1 - mu1, q1));
      if (ql < 2) st_tagged(&g_stats[(row0 + 8 * ql) * 8 + (zi & 31)], ql ? mu1 : mu0, ql ? q1 : q0, load_tag(c));
      if (ln == 0) mbar_arrive(c.sb + OFF_BAR + B_PUB);
    }
  }
  const int s0 = sh.store == 0 ? -9 : k + (sh.store == 2 ? Z_DELAY : 1), s1 = sh.store == 3 ? -9 : s0 + 3;
  hold = hold && k < nsteps;
#pragma unroll 1
  while (k < nsteps) {
    G_STEP()
    if (k == s0) stage_half<0>(c, held, sh.store);
    else if (k == s1) stage_half<32>(c, held, sh.store);
    else if (hold && k == nsteps - 2 && c.warp >= 4) named_sync(6);
  }
  if (hold && c.warp < 4) asm volatile("bar.arrive 6, 256;" ::: "memory");
  wgmma_wait<0>();
  fence_regs(acc);
  if (elected) asm volatile("mbarrier.arrive.shared::cluster.b64 _, [%0];" :: "r"(rel + 8 * ((c.g.s - 1) & 3)) : "memory");
  sh.store = sh.act == 2 ? 2 : 0;
  sh.act = 0;
}

template <bool SUB> __device__ __forceinline__ void softmax_exp(const float (&S)[64], uint32_t (&P)[32], float m0, float m1, float& s0, float& s1) {
  float a0 = 0.f, a1 = 0.f, b0 = 0.f, b1 = 0.f;
#pragma unroll
  for (int j = 0; j < 16; j++) {
    const float p0 = ex2(SUB ? S[4 * j] - m0 : S[4 * j]), p1 = ex2(SUB ? S[4 * j + 1] - m0 : S[4 * j + 1]);
    const float p2 = ex2(SUB ? S[4 * j + 2] - m1 : S[4 * j + 2]), p3 = ex2(SUB ? S[4 * j + 3] - m1 : S[4 * j + 3]);
    a0 += p0; b0 += p1; a1 += p2; b1 += p3;
    P[2 * j] = pack_bf16(p0, p1); P[2 * j + 1] = pack_bf16(p2, p3);
  }
  s0 = a0 + b0; s1 = a1 + b1;
}
__device__ __forceinline__ void row_max(const float (&S)[64], float& x0, float& x1) {
  float a0 = fmaxf(S[0], S[1]), a1 = fmaxf(S[2], S[3]);
#pragma unroll
  for (int j = 1; j < 16; j++) { a0 = fmaxf(a0, fmaxf(S[4 * j], S[4 * j + 1])); a1 = fmaxf(a1, fmaxf(S[4 * j + 2], S[4 * j + 3])); }
  x0 = quad_max(a0); x1 = quad_max(a1);
}

__device__ __forceinline__ void issue_qk(float (&S)[64], uint32_t da, uint32_t db) {
#pragma unroll
  for (int kk = 0; kk < 8; kk++) {
    const uint32_t o = (kk >> 2) * 1024 + (kk & 3) * 2;
    wgmma_m64n128k16_ss_tb0(S, DESC_HI | (da + o), DESC_HI | (db + o), kk > 0);
  }
}
__device__ __forceinline__ void issue_pv(float (&O)[64], const uint32_t (&P)[32], uint32_t db, int acc) {
#pragma unroll
  for (int kk = 0; kk < 8; kk++) wgmma_m64n128k16_rs_tb1(O, P[4 * kk], P[4 * kk + 1], P[4 * kk + 2], P[4 * kk + 3], DESC_HI | (db + kk * 128), (acc || kk > 0));
}

__device__ __forceinline__ void att_pack(const float (&O)[64], uint32_t (&pk)[32], float i0, float i1) {
#pragma unroll
  for (int j = 0; j < 16; j++) {
    pk[2 * j] = pack_bf16(O[4 * j] * i0, O[4 * j + 1] * i0);
    pk[2 * j + 1] = pack_bf16(O[4 * j + 2] * i1, O[4 * j + 3] * i1);
  }
}
__device__ __forceinline__ void att_stage(Cons& c, const uint32_t (&pk)[32], uint32_t qbuf) {
  stage_chunks<2>(c.sb + (qbuf ? OFF_Q1 : OFF_Q0) + c.warp * 2048, 16384, pk);
  stage_commit(c);
}

#define ATT_ISSUE(PIN, ACC)                                                                                            \
  wgmma_fence();                                                                                                       \
  issue_qk(S, qd, kd); wgmma_commit();                                                                                 \
  if (g > 1) release_slot(c, vrel);                                                                                    \
  vready = mbar_test(vbar, vph);                                                                                       \
  mbar_spin(vbar, vph);                                                                                                \
  wgmma_fence();                                                                                                       \
  issue_pv(O, PIN, vd, ACC); wgmma_commit();                                                                           \
  krel = kbar + (B_KE - B_KF); vrel = vbar + (B_KE - B_KF);                                                            \
  g++;                                                                                                                 \
  if (g < total) { kd = kd0 + kv.s * (KV_SLOT >> 4); kbar = bars + B_KF + 8 * kv.s; kph = kv.ph; ring_adv<5>(kv); }    \
  vd = vd0 + kv.s * (KV_SLOT >> 4); vbar = bars + B_KF + 8 * kv.s; vph = kv.ph; ring_adv<5>(kv);

#define ATT_WAIT_S()                                                                                                   \
  wgmma_wait<1>();                                                                                                     \
  fence_regs(S);                                                                                                       \
  release_slot(c, krel);                                                                                               \
  if (c.warp == 2) asm volatile("st.volatile.shared.u32 [%0], %1;" :: "r"(bars + B_PROG), "r"(g) : "memory");

#define ATT_SOFTMAX(POUT, FIRST)                                                                                       \
  fresh = false;                                                                                                       \
  _Pragma("unroll 1")                                                                                                  \
  while (true) {                                                                                                       \
    if (__builtin_expect(fresh, 0)) {                                                                                  \
      float x0, x1;                                                                                                    \
      row_max(S, x0, x1);                                                                                              \
      if (FIRST) m0 = m1 = -1e38f;                                                                                     \
      x0 = fmaxf(x0, m0); x1 = fmaxf(x1, m1);                                                                          \
      f0 = ex2(m0 - x0); f1 = ex2(m1 - x1);                                                                            \
      m0 = x0; m1 = x1; l0 *= f0; l1 *= f1;                                                                            \
      zero = false;                                                                                                    \
    }                                                                                                                  \
    if (zero) {                                                                                                        \
      softmax_exp<false>(S, POUT, m0, m1, s0, s1);                                                                     \
      bad = !(s0 <= SM_HI && s1 <= SM_HI) || ((FIRST) && (s0 < SM_LO || s1 < SM_LO));                                  \
    } else {                                                                                                           \
      softmax_exp<true>(S, POUT, m0, m1, s0, s1);                                                                      \
      bad = !(s0 <= SM_THR && s1 <= SM_THR);                                                                           \
    }                                                                                                                  \
    kready = mbar_test(kbar, kph) && vready;                                                                           \
    slow = fresh || __any_sync(0xffffffffu, bad || !kready);                                                           \
    if (__builtin_expect(!slow, 1)) break;                                                                             \
    if (fresh || !__any_sync(0xffffffffu, bad)) break;                                                                 \
    fresh = true;                                                                                                      \
  }                                                                                                                    \
  l0 += s0; l1 += s1;                                                                                                  \
  wgmma_wait<0>(); fence_regs(O);

#define ATT_RESCALE()                                                                                                  \
  { _Pragma("unroll")                                                                                                  \
    for (int i = 0; i < 16; i++) { O[4 * i] *= f0; O[4 * i + 1] *= f0; O[4 * i + 2] *= f1; O[4 * i + 3] *= f1; } }

__device__ __forceinline__ void att_stagger(const Cons& c, int g) {
  if (c.warp >= 4)
    asm volatile("{\n.reg .pred p;\n.reg .s32 v;\nLOOP:\nld.volatile.shared.s32 v, [%0];\nsetp.le.s32 p, v, %1;\n@p bra LOOP;\n}" :: "r"(c.sb + OFF_BAR + B_PROG), "r"(g) : "memory");
}

__device__ __forceinline__ void att_run(Cons& c, const Params& p, int it, int n) {
  const uint32_t bars = c.sb + OFF_BAR;
  float S[64], O[64];
  uint32_t P0[32], P1[32];
#pragma unroll
  for (int i = 0; i < 64; i++) O[i] = 0.f;
#pragma unroll
  for (int i = 0; i < 32; i++) P0[i] = P1[i] = 0u;
  fence_regs(O); fence_regs(P0); fence_regs(P1);
  float m0 = 0.f, m1 = 0.f, l0 = 0.f, l1 = 0.f, f0 = 1.f, f1 = 1.f, s0, s1, pl0 = 0.f, pl1 = 0.f;
  const int total = 16 * n;
  int g = 0;
  Ring kv = {1, 0};
  uint32_t kbar = bars + B_KF, kph = 0, vbar = bars + B_KF, vph = 0, krel, vrel = 0;
  const uint32_t kd0 = (uint32_t)make_desc(c.sb, 16, 1024), vd0 = (uint32_t)make_desc(c.sb, 16384, 1024);
  uint32_t qd = kd0 + ((OFF_Q0 + (c.warp >> 2) * 8192) >> 4), kd = kd0, vd = vd0;
  bool fresh, kready, vready, bad, slow, zero = false;
  mbar_spin(bars + B_QF, 0);
  mbar_spin(bars + B_KF, 0);
  att_stagger(c, 0);
#pragma unroll 1
  while (true) {
    ATT_ISSUE(P1, 1)
    const bool first = ((g - 1) & 15) == 0;
    if (first) { pl0 = l0; pl1 = l1; m0 = m1 = l0 = l1 = 0.f; zero = true; }
    ATT_WAIT_S()
    ATT_SOFTMAX(P0, first)
    if (__builtin_expect(slow || first, 0)) {
      if (first) {
        if (g > 1) {
          att_pack(O, P1, __fdividef(1.f, quad_sum(pl0)), __fdividef(1.f, quad_sum(pl1)));
          att_stage(c, P1, ((g >> 4) & 1) ^ 1);
        }
      } else if (fresh) ATT_RESCALE();
      mbar_spin(kbar, kph);
      if (__any_sync(0xffffffffu, !kready)) att_stagger(c, g);
    }
    ATT_ISSUE(P0, !first)
    ATT_WAIT_S()
    ATT_SOFTMAX(P1, false)
    if (__builtin_expect(slow || (g & 15) == 0, 0)) {
      if (fresh) ATT_RESCALE();
      if (g == total) break;
      mbar_spin(kbar, kph);
      if (__any_sync(0xffffffffu, !kready)) att_stagger(c, g);
      if ((g & 15) == 0) {
        const int t = g >> 4;
        const uint32_t qb = t & 1;
        mbar_spin(bars + B_QF + 8 * qb, (t >> 1) & 1);
        qd = kd0 + (((qb ? OFF_Q1 : OFF_Q0) + (c.warp >> 2) * 8192) >> 4);
      }
    }
  }
  release_slot(c, vrel);
  mbar_spin(vbar, vph);
  wgmma_fence();
  issue_pv(O, P1, vd, 1); wgmma_commit();
  pl0 = __fdividef(1.f, quad_sum(l0)); pl1 = __fdividef(1.f, quad_sum(l1));
  wgmma_wait<0>();
  fence_regs(O);
  release_slot(c, vbar + (B_KE - B_KF));
  att_pack(O, P0, pl0, pl1);
  if ((get_item(p, it + n) >> 12) == T_END) {
    const uint32_t buf = c.sb + (((n - 1) & 1) ? OFF_Q1 : OFF_Q0) + c.warp * 2048;
    stage_chunks<2>(buf, 16384, P0);
    fence_async_smem();
    __syncwarp();
    if (elect_one()) {
      const int im = get_item(p, it + n - 1), col = ((im >> 5) & 31) * 128, row = ((im & 31) * 2 + (blockIdx.x & 1)) * 128 + c.warp * 16;
      tma_store_2d(&p.tm[TS_O], buf, col, row); tma_store_2d(&p.tm[TS_O], buf + 16384, col + 64, row);
      bulk_commit();
      bulk_wait<0>();
      mbar_arrive(bars + B_STG);
    }
    __syncwarp();
  } else {
    att_stage(c, P0, (n - 1) & 1);
  }
}

__global__ void __cluster_dims__(2, 1, 1) __launch_bounds__(384, 1) fused_kernel(const __grid_constant__ Params p) {
  const uint32_t sb = smem_base();
  const uint32_t bars = sb + OFF_BAR;
  const int tid = threadIdx.x, lane = tid & 31;
  const int warp_id = __shfl_sync(0xffffffffu, tid >> 5, 0), wg = warp_id >> 2;
  const uint32_t rank = blockIdx.x & 1;
  const uint16_t* items = p.items[blockIdx.x >> 1];
  const int gw = blockIdx.x * 8 + warp_id - 4;
  uint4 xv[2][4];
  if (wg != 0 && gw < SEQ / 2) {
#pragma unroll
    for (int rr = 0; rr < 2; rr++)
#pragma unroll
      for (int i = 0; i < 4; i++) xv[rr][i] = __ldg(reinterpret_cast<const uint4*>(p.x + (size_t)(gw * 2 + rr) * DM) + i * 32 + lane);
  }
  if (warp_id == 1 && lane < TM_COUNT) asm volatile("prefetch.tensormap [%0];" :: "l"(&p.tm[lane]) : "memory");
  if (tid == 0) {
    for (int i = 0; i < 4; i++) { mbar_init(bars + B_GF + 8 * i, 1); mbar_init(bars + B_GE + 8 * i, 4); }
    for (int i = 0; i < 5; i++) { mbar_init(bars + B_KF + 8 * i, 1); mbar_init(bars + B_KE + 8 * i, 4); }
    for (int i = 0; i < 2; i++) { mbar_init(bars + B_QF + 8 * i, 1); mbar_init(bars + B_QE + 8 * i, 1); }
    mbar_init(bars + B_XF, 2); mbar_init(bars + B_XR, 2); mbar_init(bars + B_STG, 8); mbar_init(bars + B_FREE, 1); mbar_init(bars + B_GO, 1); mbar_init(bars + B_LN, 2); mbar_init(bars + B_PUB, 8);
    asm volatile("fence.mbarrier_init.release.cluster;" ::: "memory");
  }
  asm volatile("barrier.cluster.arrive.relaxed.aligned;" ::: "memory");

  if (wg == 0) {
    asm volatile("setmaxnreg.dec.sync.aligned.u32 40;");
    asm volatile("barrier.cluster.wait.acquire.aligned;" ::: "memory");
    if (warp_id >= 2 && (items[0] >> 12) == T_Z2) {
      if (lane == 0) mbar_wait_sleep(bars + B_PUB, 0, 100);
      __syncwarp();
      uint32_t tag;
      asm volatile("ld.volatile.shared.u32 %0, [%1];" : "=r"(tag) : "r"(bars + B_TAG));
      const int r = (warp_id - 2) * 64 + lane;
      const uint2* ps = &g_stats[((((items[0] >> 5) & 31) * 2 + rank) * 128 + r) * 8];
      uint4 t[2][4];
      uint32_t cnt = 0;
      while (true) {
        bool ok = true;
#pragma unroll
        for (int i = 0; i < 8; i++) t[i >> 2][i & 3] = ld_tagged2(ps + (i >> 2) * 256 + (i & 3) * 2);
#pragma unroll
        for (int i = 0; i < 8; i++) { const uint4 v = t[i >> 2][i & 3]; ok = ok && tag_ok(v.x, v.y, tag) && ((i & 3) == 3 || tag_ok(v.z, v.w, tag)); }
        if (__all_sync(0xffffffffu, ok)) break;
        trap_if(++cnt > SPIN_LIMIT);
        __nanosleep(100);
      }
#pragma unroll
      for (int y = 0; y < 2; y++) {
        float u = 0.f, v = 0.f;
#pragma unroll
        for (int i = 0; i < 7; i++) u += __uint_as_float((i & 1) ? t[y][i >> 1].z : t[y][i >> 1].x);
        u *= 1.f / 7;
#pragma unroll
        for (int i = 0; i < 7; i++) {
          const float d = __uint_as_float((i & 1) ? t[y][i >> 1].z : t[y][i >> 1].x) - u;
          v += fmaf(256.f * d, d, __uint_as_float((i & 1) ? t[y][i >> 1].w : t[y][i >> 1].y));
        }
        const float rs = rsqrtf(fmaxf(v, 0.f) * (1.f / FH) + 4e-5f);
        asm volatile("st.shared.v2.b32 [%0], {%1, %2};" :: "r"(sb + OFF_LN + (r + 32 * y) * 8), "r"(pack_bf16(rs, rs)), "r"(pack_bf16(-u, -u)) : "memory");
      }
      __syncwarp();
      if (lane == 0) mbar_arrive(bars + B_LN);
      __syncwarp();
    }
    if (warp_id == 0) {
      trap_if(sb & 1023);
      Ring g = {0, 1};
      int it = 0;
      uint32_t xph = 0;
      if (elect_one()) {
#pragma unroll 1
        for (;; it++) {
          const int item = items[it], type = item >> 12, b = item & 31, row = (((item >> 5) & 31) * 2 + rank) * 128;
          if (type >= T_ATT) break;
#pragma unroll 1
          for (int seg = 0; seg < (type == T_U ? 2 : 1); seg++) {
            const CUtensorMap* tA = &p.tm[seg ? TM_WSP : TM_XN];
            const CUtensorMap* tB = &p.tm[seg ? TM_Z2 : (type == T_Q ? TM_WQ : TM_WIN)];
            const int bchunk = b * 4 + (type == T_Z2 ? 28 : 0) + rank * 2;
            const unsigned* fl = seg ? &g_flags[F_Z2 + b * 32] : &g_flags[F_XN + (row >> 2)];
            const unsigned tgt = seg ? 16 : 128;
            int k = 0;
            if (it == 0 && seg == 0) {
              for (; k < 4; k++) {
                mbar_expect_tx(bars + B_GF + 8 * k, G_STAGE);
                tma_load_3d_mc(sb + k * G_STAGE + G_A + rank * 16384, tB, k * 64, bchunk, bars + B_GF + 8 * k);
              }
              g.ph ^= 1;
            }
            if (seg || type != T_U) { flag_wait(fl, tgt); fence_async_global(); }
            for (int x = 0; x < k; x++) tma_load_2d(sb + x * G_STAGE, tA, x * 64, row, bars + B_GF + 8 * x);
            if (it == 0) asm volatile("st.volatile.shared.v4.u32 [%0], {%1, %2, %2, %2};" :: "r"(bars + B_TAG), "r"(__ldcg(&g_epoch) % 4095u + 1), "r"(0) : "memory");
#pragma unroll 1
            for (; k < (seg ? 32 : 16); k++) {
              if (k == 3 && type == T_U && seg == 0) { mbar_wait(bars + B_XF, xph); xph ^= 1; }
              mbar_wait(bars + B_GE + 8 * g.s, g.ph);
              const uint32_t st = sb + g.s * G_STAGE, fb = bars + B_GF + 8 * g.s;
              mbar_expect_tx(fb, G_STAGE);
              tma_load_2d(st, tA, k * 64, row, fb);
              tma_load_3d_mc(st + G_A + rank * 16384, tB, k * 64, bchunk, fb);
              ring_adv<4>(g);
            }
          }
        }
      }
      { const int e = __ffs(__ballot_sync(0xffffffffu, elect_one())) - 1; it = __shfl_sync(0xffffffffu, it, e); g.ph = __shfl_sync(0xffffffffu, g.ph, e); }
      const int n = ((items[it] >> 10) & 3) + 3;
      Ring kv = {0, 1};
      if (elect_one()) {
        int prow = 0;
        {
          const int im = items[it];
          tma_prefetch_2d(&p.tm[(im & 1) ? TM_V : TM_K], rank * 64, ((im >> 5) & 31) * SEQ + ((im & 7) >> 1) * 128);
        }
#pragma unroll 1
        for (int x = 0; x <= 32 * n; x++) {
          const int gb = x >> 1, t = gb >> 4;
          const int hrow = ((items[it + t] >> 5) & 31) * SEQ;
          const bool isv = (x & 1) || x == 32 * n;
          if (x != 1) {
            if (x == 0 || x == 2) mbar_wait(bars + B_GE + 4 * x, g.ph);
            if (x == 4) { mbar_wait(bars + B_XF, xph); xph ^= 1; }
            mbar_wait(bars + B_KE + 8 * kv.s, kv.ph);
            mbar_expect_tx(bars + B_KF + 8 * kv.s, KV_SLOT);
            tma_load_2d_mc(sb + kv.s * KV_SLOT + rank * 16384, &p.tm[isv ? TM_V : TM_K], rank * 64, isv ? prow : hrow + (gb & 15) * 128, bars + B_KF + 8 * kv.s);
            ring_adv<5>(kv);
          }
          {
            const int gp = gb + KV_PF, ip = items[it + (gp >> 4)];
            if (gp < 16 * n && ((gp ^ ip) & 7) == 0) tma_prefetch_2d(&p.tm[(x & 1) ? TM_V : TM_K], rank * 64, ((ip >> 5) & 31) * SEQ + (gp & 15) * 128);
          }
          if (x == 32 * n - 8) mbar_arrive(bars + B_GO);
          if (x & 1) prow = hrow + (gb & 15) * 128;
          if ((x & 31) == 11 && t + 1 < n) {
            const int tq = t + 1;
            const int im = items[it + tq], h = (im >> 5) & 31, m = (im & 31) * 2 + rank;
            const uint32_t qb = tq & 1;
            flag_wait(&g_flags[F_Q + m * 16 + (h >> 1)], 1);
            fence_async_global();
            mbar_wait(bars + B_QE + 8 * qb, ((tq - 1) >> 1) & 1);
            const uint32_t dst = sb + (qb ? OFF_Q1 : OFF_Q0), fb = bars + B_QF + 8 * qb;
            mbar_expect_tx(fb, 32768);
            tma_load_2d(dst, &p.tm[TM_Q], h * 128, m * 128, fb);
            tma_load_2d(dst + 16384, &p.tm[TM_Q], h * 128 + 64, m * 128, fb);
          }
        }
      }
      __syncwarp();
      it += n;
      uint32_t ready = 0;
      auto wait_head = [&](int h) {
        if ((ready >> h) & 1) return;
        uint32_t cnt = 0;
        while (true) {
          asm volatile("ld.acquire.cta.shared.u32 %0, [%1];" : "=r"(ready) : "r"(bars + B_RDY) : "memory");
          if ((ready >> h) & 1) break;
          trap_if(++cnt > SPIN_LIMIT * 8);
          __nanosleep(20);
        }
        fence_async_global();
      };
      int item = items[it];
      if ((item >> 12) == T_SA) {
        const int m = ((item >> 5) & 31) * 2 + rank, b = item & 31;
        Ring dr = kv;
        wait_head(0);
#pragma unroll 1
        for (int i = 0; i < 28 + 2 * SA_HEADS; i++) {
          {
            const bool so = i >= 28;
            const int k = so ? i - 28 : i;
            if (so) wait_head(k >> 1);
            if (elect_one()) {
              if (i < 4) { for (int x = 0; x < ((0x1022 >> (4 * i)) & 3); x++) { mbar_wait(bars + B_KE + 8 * dr.s, dr.ph); ring_adv<5>(dr); } }
              if (i == 2) { mbar_wait(bars + B_XF, xph); xph ^= 1; }
              mbar_wait(bars + B_GE + 8 * g.s, g.ph);
              const uint32_t st = sb + ((g.s + SA_ROT) & 3) * G_STAGE, fb = bars + B_GF + 8 * g.s;
              mbar_expect_tx(fb, G_STAGE);
              tma_load_2d(st, &p.tm[so ? TM_O : TM_U], k * 64, m * 128, fb);
              tma_load_3d_mc(st + G_A + rank * 16384, &p.tm[so ? TM_WO : TM_WOUT], k * 64, b * 4 + rank * 2, fb);
            }
            ring_adv<4>(g);
          }
          const int ip = i + OUT_PF;
          if (ip < 28 + 2 * SA_HEADS && elect_one()) {
            const bool so = ip >= 28;
            const int k = so ? ip - 28 : ip;
            if ((ip & 3) == b && (!so || ((ready >> (k >> 1)) & 1))) tma_prefetch_2d(&p.tm[so ? TM_O : TM_U], k * 64, m * 128);
            if ((ip & 7) == (m >> 1)) tma_prefetch_3d(&p.tm[so ? TM_WO : TM_WOUT], k * 64, b * 4 + rank * 2);
          }
          __syncwarp();
        }
        item = items[++it];
      }
      if ((item >> 12) == T_FIN) {
        const bool own = item & 4;
        const int m = ((item >> 5) & 31) * 2 + rank, col = (item & 3) * 256 + (own ? 128 : 0);
        uint32_t ps = own ? FIN_SLOT0 : kv.s;
#pragma unroll 1
        for (int i = 2 * SA_HEADS; i <= 2 * NH; i++) {
          const bool extra = i == 2 * NH - FIN_PREP;
          if (extra && own) continue;
          const int k = i > 2 * NH - FIN_PREP ? i - 1 : i;
          if (!extra) wait_head(k >> 1);
          if (elect_one()) {
            if (i == 2 * SA_HEADS) {
              for (int y = k; y < k + 4; y++) if ((ready >> (y >> 1)) & 1) tma_prefetch_2d(&p.tm[TM_O], y * 64, m * 128);
            }
            if (own && i < 2 * SA_HEADS + 5) {
              const uint32_t s0 = ((0x22100u >> (4 * ps)) - SA_ROT) & 3, s1 = ((0x32110u >> (4 * ps)) - SA_ROT) & 3;
              mbar_wait(bars + B_GE + 8 * s0, g.ph ^ (s0 < g.s)); mbar_wait(bars + B_GE + 8 * s1, g.ph ^ (s1 < g.s));
            }
            if (extra) { flag_wait(&g_flags[F_S + m * 4 + (item & 3)], 2); fence_async_global(); }
            mbar_wait(bars + B_KE + 8 * kv.s, kv.ph);
            const uint32_t dst = sb + ps * KV_SLOT, fb = bars + B_KF + 8 * kv.s;
            if (++ps == 5) ps = 0;
            mbar_expect_tx(fb, KV_SLOT);
            if (!extra) {
              tma_load_2d(dst, &p.tm[TM_O], k * 64, m * 128, fb);
              tma_load_2d_mc(dst + 16384 + rank * 8192, &p.tm[TM_WO64], col + rank * 64, k * 64, fb);
            } else {
              tma_load_2d(dst, &p.tm[TM_SA], col, m * 128, fb);
              tma_load_2d(dst + 16384, &p.tm[TM_SA], col + 64, m * 128, fb);
            }
            ring_adv<5>(kv);
          }
          __syncwarp();
        }
      }
      unsigned last = 0;
      if (lane == 0 && (item >> 12) == T_FIN) mbar_wait_sleep(bars + B_XR, 0, 100);
      if (lane == 0) { __threadfence(); last = atomicInc(&g_done, gridDim.x - 1) == gridDim.x - 1; }
      last = __shfl_sync(0xffffffffu, last, 0);
      if (last) {
        for (int i = lane; i < F_TOTAL / 4; i += 32) reinterpret_cast<uint4*>(g_flags)[i] = make_uint4(0, 0, 0, 0);
        if (lane == 0) g_epoch = g_epoch + 1;
      }
    } else if (warp_id == 1) {
      if (elect_one()) {
        uint32_t ph = 0;
        int t = 0;
        unsigned* fq = nullptr;
        const bool z = (items[0] >> 12) == T_Z2;
#pragma unroll 1
        for (int it = 0;; it++) {
          const int ii = (z && it < 2) ? it ^ 1 : it;
          const int item = items[ii], type = item >> 12, a = (item >> 5) & 31, b = item & 31;
          if (type == T_END) break;
          const int nt = items[ii + 1] >> 12;
          int row = (a * 2 + rank) * 128, col = b * 256;
          unsigned* f = &g_flags[F_S + (a * 2 + rank) * 4 + b];
          int tm = TS_G, npair = 2;
          bool quad = false;
          uint32_t src = sb + OFF_Q0;
          if (type == T_Z2) { tm = TS_Z2; f = &g_flags[F_Z2 + b * 32]; }
          else if (type == T_Q) { tm = TS_Q; f = &g_flags[F_Q + (a * 2 + rank) * 16 + b]; if (z || nt >= T_ATT) { npair = 0; quad = true; } }
          else if (type == T_U) { tm = TS_U; f = &g_flags[F_U + (a * 2 + rank) * 32]; npair = 0; quad = true; }
          else if (type == T_ATT) { tm = TS_O; f = &g_flags[F_O + (b * 2 + rank) * 32 + a]; npair = 1; row = (b * 2 + rank) * 128; col = a * 128; if (t & 1) src = sb + OFF_Q1; }
          else if (type == T_FIN) npair = 1;
          auto load_fin = [&](int fi, int tmi, uint32_t qb) {
            const int fc = (fi & 3) * 256 + ((fi & 4) ? 128 : 0), fr = (((fi >> 5) & 31) * 2 + rank) * 128;
            mbar_expect_tx(bars + B_QF + 8 * qb, 32768);
            tma_load_2d(sb + (qb ? OFF_Q1 : OFF_Q0), &p.tm[tmi], fc, fr, bars + B_QF + 8 * qb);
            tma_load_2d(sb + (qb ? OFF_Q1 : OFF_Q0) + 16384, &p.tm[tmi], fc + 64, fr, bars + B_QF + 8 * qb);
          };
          if (type == T_ATT && nt == T_FIN) load_fin(items[ii + 1], TM_X, (t & 1) ^ 1);
          if (type == T_FIN) {
            if (!(item & 4)) { flag_wait(&g_flags[F_S + (a * 2 + rank) * 4 + (b & 3)], 1); fence_async_global(); load_fin(item, TM_G, (t & 1) ^ 1); }
            mbar_arrive(bars + B_XR);
          }
#pragma unroll 1
          for (int op = 0; op < npair + quad; op++) {
            const bool q = op == npair;
            const int c0 = (q || type == T_SA) ? col : col + op * 128;
            mbar_wait_sleep(bars + B_STG, ph, (type == T_ATT && nt == T_ATT) ? SW_ATT : SW_NS);
            if (type == T_FIN) break;
            ph ^= 1;
            fence_async_smem();
            if (type == T_SA && op == 1) { tm = TS_SA; load_fin(items[ii + 1], TM_X, 1); }
            int c1 = c0;
            if (q) {
              const CUtensorMap* tb = &p.tm[type == T_U ? TM_U : TM_Q];
              const bool pre = nt == T_ATT;
              tma_store_2d(tb, sb + (pre ? 2 * G_STAGE : OFF_Q1), c0 + (pre ? 0 : 128), row);
              tma_store_2d(tb, sb + (pre ? 3 * G_STAGE : OFF_Q1 + 16384), c0 + (pre ? 64 : 192), row);
              bulk_commit();
              bulk_wait_read<0>();
              mbar_arrive_cta(bars + B_XF, 0); mbar_arrive_cta(bars + B_XF, 1);
              if (pre) { src = sb + OFF_Q1; c1 += 128; }
            }
            if (nt != T_END) {
#pragma unroll 1
              for (int r = 0; r < 256; r += ST_ROWS) {
                tma_store_2d(&p.tm[tm], src + r * 128, c1 + (r >> 7) * 64, row + (r & 127));
                bulk_commit();
                bulk_wait_read<ST_FLY>();
              }
            }
            bulk_wait_read<0>();
            mbar_arrive(bars + B_FREE);
            if (type == T_ATT && (t & 1) && (nt == T_SA || (items[ii + 2] >> 12) == T_SA)) { mbar_arrive_cta(bars + B_XF, 0); mbar_arrive_cta(bars + B_XF, 1); }
            if (type == T_ATT) mbar_arrive(bars + B_QE + 8 * (t & 1));
            else if (nt == T_ATT) mbar_arrive(bars + B_QE + 8);
            if (z && it == 0) { fq = f; continue; }
            if (op + 1 >= npair || type == T_SA) {
              bulk_wait<0>();
              red_release(f, 1);
              if (type == T_Z2) red_release(fq, 1);
            }
          }
          if (type == T_ATT) t++;
          else if (t == 0 && (items[it + 1] >> 12) < T_ATT && (items[it + 2] >> 12) == T_ATT) {
            const int im = items[it + 2], h = (im >> 5) & 31, m = (im & 31) * 2 + rank;
            flag_wait(&g_flags[F_Q + m * 16 + (h >> 1)], 1);
            fence_async_global();
            mbar_expect_tx(bars + B_QF, 32768);
            tma_load_2d(sb + OFF_Q0, &p.tm[TM_Q], h * 128, m * 128, bars + B_QF);
            tma_load_2d(sb + OFF_Q0 + 16384, &p.tm[TM_Q], h * 128 + 64, m * 128, bars + B_QF);
          }
        }
      }
      __syncwarp();
    } else if (warp_id == 2) {
      int it = 0;
      while ((items[it] >> 12) <= T_ATT) it++;
      if ((items[it] >> 12) != T_END) {
        const bool sa = (items[it] >> 12) == T_SA;
        const int m = ((items[it] >> 5) & 31) * 2 + rank;
        if (lane == 0) {
          mbar_wait_sleep(bars + B_GO, 0, 500);
          if (sa) {
            const int b = items[it] & 3;
            flag_wait(&g_flags[F_U + m * 32], 7);
            fence_async_global();
            for (int y = b; y < OUT_PF; y += 4) tma_prefetch_2d(&p.tm[TM_U], y * 64, m * 128);
            tma_prefetch_3d(&p.tm[TM_WOUT], (m >> 1) * 64, b * 4 + rank * 2);
          }
          if (!sa) for (int y = m * 4 + (items[it] & 3); y < 16 * (NH - SA_HEADS); y += 64) tma_prefetch_3d(&p.tm[TM_WO], (2 * SA_HEADS + (y >> 3)) * 64, (y & 7) * 2);
        }
        __syncwarp();
        uint32_t cnt = 0;
        while (true) {
          const uint32_t r = __ballot_sync(0xffffffffu, ld_acquire(&g_flags[F_O + m * 32 + lane]) != 0);
          if (lane == 0) asm volatile("st.release.cta.shared.u32 [%0], %1;" :: "r"(bars + B_RDY), "r"(r) : "memory");
          if (r == ~0u) break;
          trap_if(++cnt > SPIN_LIMIT);
          __nanosleep(r >> 28 ? 20 : 300);
        }
        if (lane == 0) mbar_arrive(bars + B_XR);
      }
      __syncwarp();
    }
    cluster_sync_relaxed();
  } else {
    Cons c;
    c.sb = sb; c.warp = warp_id - 4; c.g = {0, 0}; c.fph = 1; c.rot = 0;
    if (gw < SEQ / 2) {
      float f[2][32], rs[2];
#pragma unroll
      for (int rr = 0; rr < 2; rr++) {
#pragma unroll
        for (int i = 0; i < 4; i++) {
          const uint4 v = xv[rr][i];
          f[rr][8 * i + 0] = bf_lo(v.x); f[rr][8 * i + 1] = bf_hi(v.x); f[rr][8 * i + 2] = bf_lo(v.y); f[rr][8 * i + 3] = bf_hi(v.y);
          f[rr][8 * i + 4] = bf_lo(v.z); f[rr][8 * i + 5] = bf_hi(v.z); f[rr][8 * i + 6] = bf_lo(v.w); f[rr][8 * i + 7] = bf_hi(v.w);
        }
        float s = 0.f;
#pragma unroll
        for (int i = 0; i < 32; i++) s += f[rr][i];
#pragma unroll
        for (int o = 16; o; o >>= 1) s += __shfl_xor_sync(0xffffffffu, s, o);
        const float mean = s * (1.f / DM);
        float q = 0.f;
#pragma unroll
        for (int i = 0; i < 32; i++) { f[rr][i] -= mean; q = fmaf(f[rr][i], f[rr][i], q); }
#pragma unroll
        for (int o = 16; o; o >>= 1) q += __shfl_xor_sync(0xffffffffu, q, o);
        rs[rr] = rsqrtf(q * (1.f / DM) + 1e-5f);
      }
      uint4* dst = reinterpret_cast<uint4*>(g_xn + (size_t)gw * 2 * DM) + lane;
#pragma unroll
      for (int rr = 0; rr < 2; rr++) {
        const float r = rs[rr];
#pragma unroll
        for (int i = 0; i < 4; i++) {
          const float* y = &f[rr][8 * i];
          dst[rr * 128 + i * 32] = make_uint4(pack_bf16(y[0] * r, y[1] * r), pack_bf16(y[2] * r, y[3] * r), pack_bf16(y[4] * r, y[5] * r), pack_bf16(y[6] * r, y[7] * r));
        }
      }
      named_sync(7);
      if (tid == 128) red_release(&g_flags[F_XN + (gw >> 6) * 32], 16);
    }
    asm volatile("setmaxnreg.inc.sync.aligned.u32 232;");
    asm volatile("barrier.cluster.wait.acquire.aligned;" ::: "memory");
    int natt = 0;
    int it = 0;
    uint32_t held[64];
#pragma unroll
    for (int i = 0; i < 64; i++) held[i] = 0u;
    Shadow sh = {0, 0};
    float facc[64];
#pragma unroll 1
    while (true) {
      const int item = get_item(p, it), type = item >> 12, a = (item >> 5) & 31;
      c.warp = fresh_warp();
      if (type == T_ATT) {
        const int n = ((item >> 10) & 3) + 3;
        att_run(c, p, it, n);
#pragma unroll
        for (int i = 0; i < 64; i++) held[i] = 0u;
        natt = n;
        it += n;
        c.rot = SA_ROT;
        if ((get_item(p, it) >> 12) == T_SA) continue;
#pragma unroll
        for (int i = 0; i < 64; i++) facc[i] = 0.f;
        break;
      }
      float acc[128];
      const bool sa = type == T_SA;
      bool more = type >= T_U;
      int nsteps = sa ? 28 : 16;
      const bool direct = sh.act == 2 || (get_item(p, it + 1) >> 12) >= T_ATT;
      uint32_t bias0 = 0, bias1 = 0;
#pragma unroll 1
      while (true) {
        gemm_seg(acc, held, c, p, sh, nsteps, more || !direct || sa);
        if (type == T_Q) {
#pragma unroll
          for (int i = 0; i < 128; i++) acc[i] *= SM_C;
        }
        if (!more && direct) break;
#pragma unroll
        for (int i = 0; i < 64; i++) held[i] = pack_bf16(acc[2 * i], acc[2 * i + 1]);
        if (!more) break;
        more = false;
        nsteps = sa ? 2 * SA_HEADS : 32;
        sh.act = sa ? 3 : 1;
        if (sa) {
          sh.store = 3;
        } else {
          const int row0 = (a * 2 + rank) * 128 + c.warp * 16 + (lane_id() >> 2);
          asm volatile("ld.global.nc.u16 %0, [%1];" : "=r"(bias0) : "l"(p.b_sp + row0));
          asm volatile("ld.global.nc.u16 %0, [%1];" : "=r"(bias1) : "l"(p.b_sp + row0 + 8));
        }
      }
      c.warp = fresh_warp();
      if (direct) {
        const bool pre = !sa && sh.store != 2;
        const uint32_t hb0 = bf2_mul(bias0 * 0x10001u, BF2_HALF), hb1 = bf2_mul(bias1 * 0x10001u, BF2_HALF);
        stage_acquire(c);
#pragma unroll
        for (int h = 0; h < 2; h++) {
          uint32_t pk[32];
#pragma unroll
          for (int i = 0; i < 32; i++) pk[i] = pack_bf16(acc[64 * h + 2 * i], acc[64 * h + 2 * i + 1]);
          if (type == T_U) {
#pragma unroll
            for (int i = 0; i < 32; i++) pk[i] = bf2_mul(bf2_fma(pk[i], BF2_HALF, (i & 1) ? hb1 : hb0), held[32 * h + i]);
          }
          if (h) named_sync(5);
          stage_chunks<2>(sb + (h ? OFF_Q1 : (pre ? 2 * G_STAGE : OFF_Q0)) + c.warp * 2048, (!h && pre) ? G_STAGE : 16384, pk);
          if (sa) break;
        }
        stage_commit(c);
        if (sa) {
#pragma unroll
          for (int i = 0; i < 64; i++) facc[i] = acc[64 + i];
          it++;
          break;
        }
      } else if (type == T_Q) {
        sh.store = 1;
      } else {
        sh.act = 2;
      }
      it++;
    }
    const int fin = get_item(p, it);
    if ((fin >> 12) == T_FIN) {
      c.warp = fresh_warp();
      const bool own = fin & 4;
      Ring kv = {(uint32_t)(32 * natt) % 5, ((uint32_t)(32 * natt) / 5) & 1};
      uint32_t prev = 0, ps = own ? FIN_SLOT0 : kv.s;
      fence_regs(facc);
      auto fin_steps = [&](int k0, int k1) {
#pragma unroll 1
        for (int k = k0; k < k1; k++) {
          mbar_spin(bars + B_KF + 8 * kv.s, kv.ph);
          const uint32_t st = ((c.sb & 0x3FFFF) >> 4) + ps * (KV_SLOT >> 4);
          if (++ps == 5) ps = 0;
          const uint32_t da = st + (c.warp >> 2) * 512 + (1u << 16), db = st + 1024 + ((8192u >> 4) << 16);
          wgmma_fence();
#pragma unroll
          for (int kk = 0; kk < 4; kk++) wgmma_m64n128k16_ss_tb1(facc, DESC_HI | (da + kk * 2), DESC_HI | (db + kk * 128), 1);
          wgmma_commit();
          wgmma_wait<1>();
          if (k > 2 * SA_HEADS) release_slot(c, prev);
          prev = bars + B_KE + 8 * kv.s;
          ring_adv<5>(kv);
        }
      };
      const int kp = (own && ((fin >> 5) & 31) == 7) ? 2 * SA_HEADS + 5 : 2 * NH - FIN_PREP - (own ? OWN_OFF : 0);
      fin_steps(2 * SA_HEADS, kp);
      const uint32_t ln = lane_id(), xb = own ? 1 : natt & 1;
      const uint32_t lo = c.warp * 2048 + ((ln & 15) << 7);
      uint32_t xs[32];
      auto load_tile = [&](uint32_t base, uint32_t* d) {
#pragma unroll
        for (int i = 0; i < 8; i++) ldmatrix_x4(base + lo + (i >> 2) * 16384 + (((2 * (i & 3) + (ln >> 4)) ^ (ln & 7)) << 4), d[4 * i], d[4 * i + 1], d[4 * i + 2], d[4 * i + 3]);
      };
      const uint32_t xa = sb + (xb ? OFF_Q1 : OFF_Q0);
      mbar_spin(bars + B_QF + 8 * xb, ((natt + 1 - xb) >> 1) & 1);
      load_tile(xa, xs);
      if (!own) {
        mbar_spin(bars + B_QF + 8 * (xb ^ 1), ((natt + xb) >> 1) & 1);
        load_tile(sb + (xb ? OFF_Q0 : OFF_Q1), held + 32);
      }
      float gf[64], rf[64];
#pragma unroll
      for (int i = 0; i < 32; i++) { gf[2 * i] = bf_lo(held[32 + i]); gf[2 * i + 1] = bf_hi(held[32 + i]); rf[2 * i] = bf_lo(xs[i]); rf[2 * i + 1] = bf_hi(xs[i]); }
      if (!own) {
        mbar_spin(bars + B_KF + 8 * kv.s, kv.ph);
#pragma unroll
        for (int i = 0; i < 8; i++) {
          uint32_t t[4];
          ldmatrix_x4(sb + ps * KV_SLOT + lo + (i >> 2) * 16384 + (((2 * (i & 3) + (ln >> 4)) ^ (ln & 7)) << 4), t[0], t[1], t[2], t[3]);
#pragma unroll
          for (int y = 0; y < 4; y++) {
            rf[8 * i + 2 * y] = fmaf(bf_lo(t[y]), gf[8 * i + 2 * y], rf[8 * i + 2 * y]);
            rf[8 * i + 2 * y + 1] = fmaf(bf_hi(t[y]), gf[8 * i + 2 * y + 1], rf[8 * i + 2 * y + 1]);
          }
        }
        wg_any(c.warp >= 4, false);
        release_slot(c, bars + B_KE + 8 * kv.s);
        if (++ps == 5) ps = 0;
        ring_adv<5>(kv);
      }
      fence_regs(gf); fence_regs(rf);
      fin_steps(kp, 2 * NH);
      wgmma_wait<0>();
      fence_regs(facc);
#pragma unroll
      for (int i = 0; i < 32; i++) xs[i] = pack_bf16(fmaf(facc[2 * i], gf[2 * i], rf[2 * i]), fmaf(facc[2 * i + 1], gf[2 * i + 1], rf[2 * i + 1]));
      __syncwarp();
      stage_chunks<2>(xa + c.warp * 2048, 16384, xs);
      fence_async_smem();
      __syncwarp();
      if (elect_one()) {
        const int col = (fin & 3) * 256 + (own ? 128 : 0), row = (((fin >> 5) & 31) * 2 + rank) * 128 + c.warp * 16;
        tma_store_2d(&p.tm[TS_OUT], xa + c.warp * 2048, col, row);
        tma_store_2d(&p.tm[TS_OUT], xa + c.warp * 2048 + 16384, col + 64, row);
        bulk_commit();
        mbar_arrive(bars + B_STG);
        bulk_wait_read<0>();
      }
    }
    __syncwarp();
    cluster_sync_relaxed();
  }
}

typedef CUresult (*PFN_encodeTiled)(CUtensorMap*, CUtensorMapDataType, cuuint32_t, void*, const cuuint64_t*, const cuuint64_t*, const cuuint32_t*, const cuuint32_t*,
                                    CUtensorMapInterleave, CUtensorMapSwizzle, CUtensorMapL2promotion, CUtensorMapFloatOOBfill);
static PFN_encodeTiled s_encode = nullptr;
static void tm_2d(CUtensorMap* tm, const void* ptr, uint64_t rows, uint64_t cols, uint32_t box_rows) {
  cuuint64_t dims[2] = {cols, rows}; cuuint64_t strides[1] = {cols * 2}; cuuint32_t box[2] = {64, box_rows}; cuuint32_t es[2] = {1, 1};
  CUresult r = s_encode(tm, CU_TENSOR_MAP_DATA_TYPE_BFLOAT16, 2, (void*)ptr, dims, strides, box, es, CU_TENSOR_MAP_INTERLEAVE_NONE,
                        CU_TENSOR_MAP_SWIZZLE_128B, CU_TENSOR_MAP_L2_PROMOTION_L2_128B, CU_TENSOR_MAP_FLOAT_OOB_FILL_NONE);
  if (r != CUDA_SUCCESS) fprintf(stderr, "tensor map encode failed (%d)\n", (int)r);
}
static void tm_3d(CUtensorMap* tm, const void* ptr, uint64_t rows, uint64_t cols) {
  cuuint64_t dims[3] = {64, rows, cols / 64}; cuuint64_t strides[2] = {cols * 2, 128}; cuuint32_t box[3] = {64, 64, 2}; cuuint32_t es[3] = {1, 1, 1};
  CUresult r = s_encode(tm, CU_TENSOR_MAP_DATA_TYPE_BFLOAT16, 3, (void*)ptr, dims, strides, box, es, CU_TENSOR_MAP_INTERLEAVE_NONE,
                        CU_TENSOR_MAP_SWIZZLE_128B, CU_TENSOR_MAP_L2_PROMOTION_L2_128B, CU_TENSOR_MAP_FLOAT_OOB_FILL_NONE);
  if (r != CUDA_SUCCESS) fprintf(stderr, "tensor map encode failed (%d)\n", (int)r);
}
static inline uint16_t mk(int type, int a, int b) { return (uint16_t)(type << 12 | a << 5 | b); }

static void build_schedule(Params& P) {
  int cnt[NCLUSTER];
  for (int c = 0; c < NCLUSTER; c++) { cnt[c] = 0; for (int i = 0; i < MAXI; i++) P.items[c][i] = mk(T_END, 0, 0); }
  auto phys = [](int c) { return c == 64 ? 9 : c == 65 ? 17 : c == 9 ? 64 : c == 17 ? 65 : c; };
  auto push = [&](int c, uint16_t v) { P.items[phys(c)][cnt[c]++] = v; };
  int natt[NCLUSTER], nq[NCLUSTER];
  for (int c = 0; c < NCLUSTER; c++) { natt[c] = c < 32 ? 3 : (c < 56 ? 5 : (c < 62 ? 4 : (c < 64 ? 3 : 5))); nq[c] = c < 56 ? 1 : (c < 62 ? 7 : (c < 64 ? 9 : 6)); }
  for (int c = 0; c < 56; c++) push(c, mk(T_Z2, c % 8, c / 8));
  int qi = 0;
  for (int slot = 0; slot < 9; slot++)
    for (int c = NCLUSTER - 1; c >= 0; c--) {
      const int first = c < 56 ? 1 : 0;
      if (slot >= first && slot < first + nq[c]) { push(c, mk(T_Q, qi % 8, qi / 8)); qi++; }
    }
  for (int c = 0; c < 56; c++) push(c, mk(T_U, c % 8, c / 8));
  int ai = 0;
  for (int slot = 0; slot < 5; slot++)
    for (int c = 0; c < NCLUSTER; c++) {
      const int first = c < 32 ? 0 : 5 - natt[c];
      if (slot >= first && slot < first + natt[c]) { push(c, mk(T_ATT, ai / 8, ai % 8) | (natt[c] - 3) << 10); ai++; }
    }
  for (int c = 0; c < 32; c++) push(c, mk(T_SA, c % 8, c / 8));
  for (int c = 0; c < 64; c++) push(c, mk(T_FIN, c % 8, (c / 8) % 4 | (c < 32 ? 4 : 0)));
  if (qi != 128 || ai != 256) fprintf(stderr, "bad schedule %d %d\n", qi, ai);
}

static Params s_params;
extern "C" void kernel_launch(void* const* d_in, const int* in_sizes, int n_in, void* d_out, int out_size) {
  (void)in_sizes; (void)n_in; (void)out_size;
  if (!s_encode) {
    void* fn = nullptr; cudaDriverEntryPointQueryResult qr;
    cudaGetDriverEntryPoint("cuTensorMapEncodeTiled", &fn, cudaEnableDefault, &qr);
    s_encode = (PFN_encodeTiled)fn;
    cudaFuncSetAttribute(fused_kernel, cudaFuncAttributeMaxDynamicSharedMemorySize, SMEM_BYTES);
    build_schedule(s_params);
  }
  Params& P = s_params;
  void *xn, *q, *o, *z2, *u, *gg, *sa;
  cudaGetSymbolAddress(&gg, g_g); cudaGetSymbolAddress(&sa, g_sa);
  cudaGetSymbolAddress(&xn, g_xn); cudaGetSymbolAddress(&q, g_q); cudaGetSymbolAddress(&o, g_o);
  cudaGetSymbolAddress(&z2, g_z2); cudaGetSymbolAddress(&u, g_u);
  tm_2d(&P.tm[TM_XN], xn, SEQ, DM, 128); tm_2d(&P.tm[TM_WSP], d_in[7], SEQ, SEQ, 128); tm_2d(&P.tm[TM_U], u, SEQ, FH, 128);
  tm_2d(&P.tm[TM_O], o, SEQ, HD, 128); tm_2d(&P.tm[TM_Q], q, SEQ, HD, 128); tm_2d(&P.tm[TM_X], d_in[0], SEQ, DM, 128);
  tm_2d(&P.tm[TM_K], d_in[1], NH * SEQ, 128, 128); tm_2d(&P.tm[TM_V], d_in[2], NH * SEQ, 128, 128);
  tm_2d(&P.tm[TM_SA], sa, SEQ, DM, 128); tm_2d(&P.tm[TM_G], gg, SEQ, DM, 128); tm_2d(&P.tm[TM_WO64], d_in[4], HD, DM, 64);
  tm_3d(&P.tm[TM_WIN], d_in[6], DM, FF); tm_3d(&P.tm[TM_WQ], d_in[3], DM, HD); tm_3d(&P.tm[TM_Z2], z2, SEQ, FH);
  tm_3d(&P.tm[TM_WOUT], d_in[9], FH, DM); tm_3d(&P.tm[TM_WO], d_in[4], HD, DM);
  tm_2d(&P.tm[TS_Q], q, SEQ, HD, ST_ROWS); tm_2d(&P.tm[TS_O], o, SEQ, HD, ST_ROWS); tm_2d(&P.tm[TS_Z2], z2, SEQ, FH, ST_ROWS); tm_2d(&P.tm[TS_U], u, SEQ, FH, ST_ROWS);
  tm_2d(&P.tm[TS_SA], sa, SEQ, DM, ST_ROWS); tm_2d(&P.tm[TS_G], gg, SEQ, DM, ST_ROWS); tm_2d(&P.tm[TS_OUT], d_out, SEQ, DM, 16);
  P.x = (const bf16*)d_in[0]; P.b_sp = (const bf16*)d_in[8];
  fused_kernel<<<2 * NCLUSTER, 384, SMEM_BYTES, cudaStreamPerThread>>>(P);
}
```

```cpp
#include <cuda_runtime.h>
#include <cuda_bf16.h>
#include <cuda.h>
#include <stdint.h>
#include <stdio.h>

typedef __nv_bfloat16 bf16;

constexpr int SEQ = 2048, DM = 1024, NH = 32, HD = 4096, FF = 3584, FH = 1792;

__device__ __align__(1024) bf16 g_xn[SEQ * DM];
__device__ __align__(1024) bf16 g_q[SEQ * HD];
__device__ __align__(1024) bf16 g_o[SEQ * HD];
__device__ __align__(1024) bf16 g_z2[SEQ * FH];
__device__ __align__(1024) bf16 g_u[SEQ * FH];
__device__ __align__(1024) uint2 g_stats[SEQ * 8];
__device__ __align__(1024) bf16 g_g[SEQ * DM];
__device__ __align__(1024) bf16 g_sa[SEQ * DM];
constexpr int F_XN = 0;
constexpr int F_Z2 = 512;
constexpr int F_Q = 768;
constexpr int F_U = 1024;
constexpr int F_O = 1536;
constexpr int F_S = 2048;
constexpr int F_TOTAL = 2112;
__device__ __align__(1024) unsigned g_flags[F_TOTAL];
__device__ unsigned g_done;
__device__ unsigned g_epoch;

__device__ __forceinline__ uint32_t smem_u32(const void* p) { return (uint32_t)__cvta_generic_to_shared(p); }
__device__ __forceinline__ void mbar_init(uint32_t bar, uint32_t cnt) { asm volatile("mbarrier.init.shared::cta.b64 [%0], %1;" :: "r"(bar), "r"(cnt)); }
__device__ __forceinline__ void mbar_expect_tx(uint32_t bar, uint32_t bytes) { asm volatile("mbarrier.arrive.expect_tx.shared::cta.b64 _, [%0], %1;" :: "r"(bar), "r"(bytes) : "memory"); }
__device__ __forceinline__ void mbar_arrive(uint32_t bar) { asm volatile("mbarrier.arrive.shared::cta.b64 _, [%0];" :: "r"(bar) : "memory"); }
__device__ __forceinline__ void mbar_arrive_cta(uint32_t bar, uint32_t cta) {
  asm volatile("{\n.reg .b32 ra;\nmapa.shared::cluster.u32 ra, %0, %1;\nmbarrier.arrive.shared::cluster.b64 _, [ra];\n}" :: "r"(bar), "r"(cta) : "memory");
}
__device__ __forceinline__ bool mbar_test(uint32_t bar, uint32_t parity) {
  uint32_t ok;
  asm volatile("{\n.reg .pred P1;\nmbarrier.test_wait.parity.shared::cta.b64 P1, [%1], %2;\nselp.u32 %0, 1, 0, P1;\n}" : "=r"(ok) : "r"(bar), "r"(parity) : "memory");
  return ok;
}
constexpr uint32_t SPIN_LIMIT = 1u << 22;
__device__ __forceinline__ void trap_if(bool c) { asm volatile("{\n.reg .pred P;\nsetp.ne.u32 P, %0, 0;\n@P trap;\n}" :: "r"((uint32_t)c)); }
__device__ __forceinline__ void mbar_wait(uint32_t bar, uint32_t parity) {
  asm volatile("{\n.reg .pred P1;\n.reg .u32 n;\nmbarrier.try_wait.parity.shared::cta.b64 P1, [%0], %1;\n@P1 bra DONE;\nmov.u32 n, 0;\n"
               "LOOP:\nmbarrier.try_wait.parity.shared::cta.b64 P1, [%0], %1;\n@P1 bra DONE;\nadd.u32 n, n, 1;\nsetp.gt.u32 P1, n, %2;\n@P1 trap;\nbra LOOP;\nDONE:\n}"
               :: "r"(bar), "r"(parity), "n"(SPIN_LIMIT) : "memory");
}
__device__ __forceinline__ void mbar_spin(uint32_t bar, uint32_t parity) {
  asm volatile("{\n.reg .pred P1;\nLOOP:\nmbarrier.try_wait.parity.shared::cta.b64 P1, [%0], %1;\n@!P1 bra LOOP;\n}" :: "r"(bar), "r"(parity) : "memory");
}
__device__ __forceinline__ void mbar_wait_sleep(uint32_t bar, uint32_t parity, uint32_t ns) {
  uint32_t n = 0;
  while (!mbar_test(bar, parity)) { trap_if(++n > SPIN_LIMIT * 4); __nanosleep(ns); }
}
__device__ __forceinline__ void tma_load_2d(uint32_t dst, const CUtensorMap* tm, int c0, int c1, uint32_t bar) {
  asm volatile("cp.async.bulk.tensor.2d.shared::cluster.global.mbarrier::complete_tx::bytes [%0], [%1, {%3, %4}], [%2];"
    :: "r"(dst), "l"(tm), "r"(bar), "r"(c0), "r"(c1) : "memory");
}
__device__ __forceinline__ void tma_load_2d_mc(uint32_t dst, const CUtensorMap* tm, int c0, int c1, uint32_t bar) {
  asm volatile("cp.async.bulk.tensor.2d.shared::cluster.global.mbarrier::complete_tx::bytes.multicast::cluster [%0], [%1, {%3, %4}], [%2], %5;"
    :: "r"(dst), "l"(tm), "r"(bar), "r"(c0), "r"(c1), "h"((uint16_t)3) : "memory");
}
__device__ __forceinline__ void tma_prefetch_2d(const CUtensorMap* tm, int c0, int c1) {
  asm volatile("cp.async.bulk.prefetch.tensor.2d.L2.global [%0, {%1, %2}];" :: "l"(tm), "r"(c0), "r"(c1) : "memory");
}
__device__ __forceinline__ void tma_prefetch_3d(const CUtensorMap* tm, int c1, int c2) {
  asm volatile("cp.async.bulk.prefetch.tensor.3d.L2.global [%0, {%1, %2, %3}];" :: "l"(tm), "r"(0), "r"(c1), "r"(c2) : "memory");
}
__device__ __forceinline__ void tma_load_3d_mc(uint32_t dst, const CUtensorMap* tm, int c1, int c2, uint32_t bar) {
  asm volatile("cp.async.bulk.tensor.3d.shared::cluster.global.mbarrier::complete_tx::bytes.multicast::cluster [%0], [%1, {%3, %4, %5}], [%2], %6;"
    :: "r"(dst), "l"(tm), "r"(bar), "r"(0), "r"(c1), "r"(c2), "h"((uint16_t)3) : "memory");
}
__device__ __forceinline__ void tma_store_2d(const CUtensorMap* tm, uint32_t src, int c0, int c1) {
  asm volatile("cp.async.bulk.tensor.2d.global.shared::cta.bulk_group [%0, {%2, %3}], [%1];" :: "l"(tm), "r"(src), "r"(c0), "r"(c1) : "memory");
}
__device__ __forceinline__ void bulk_commit() { asm volatile("cp.async.bulk.commit_group;" ::: "memory"); }
template <int N> __device__ __forceinline__ void bulk_wait_read() { asm volatile("cp.async.bulk.wait_group.read %0;" :: "n"(N) : "memory"); }
template <int N> __device__ __forceinline__ void bulk_wait() { asm volatile("cp.async.bulk.wait_group %0;" :: "n"(N) : "memory"); }
__device__ __forceinline__ void fence_async_smem() { asm volatile("fence.proxy.async.shared::cta;" ::: "memory"); }
__device__ __forceinline__ void fence_async_global() { asm volatile("fence.proxy.async.global;" ::: "memory"); }
__device__ __forceinline__ void wgmma_fence() { asm volatile("wgmma.fence.sync.aligned;" ::: "memory"); }
__device__ __forceinline__ void wgmma_commit() { asm volatile("wgmma.commit_group.sync.aligned;" ::: "memory"); }
template <int N> __device__ __forceinline__ void wgmma_wait() { asm volatile("wgmma.wait_group.sync.aligned %0;" :: "n"(N) : "memory"); }
__device__ __forceinline__ uint64_t make_desc(uint32_t addr, uint32_t lbo, uint32_t sbo) {
  return (uint64_t)((addr & 0x3FFFF) >> 4) | ((uint64_t)(lbo >> 4) << 16) | ((uint64_t)(sbo >> 4) << 32) | (1ull << 62);
}
template <int N> __device__ __forceinline__ void fence_regs(float (&d)[N]) {
#pragma unroll
  for (int i = 0; i < N; i++) asm volatile("" : "+f"(d[i]) :: "memory");
}
template <int N> __device__ __forceinline__ void fence_regs(uint32_t (&d)[N]) {
#pragma unroll
  for (int i = 0; i < N; i++) asm volatile("" : "+r"(d[i]) :: "memory");
}
__device__ __forceinline__ void named_sync(int id) { asm volatile("bar.sync %0, 256;" :: "r"(id) : "memory"); }
__device__ __forceinline__ bool wg_any(bool w, bool v) {
  uint32_t r;
  asm volatile("{\n.reg .pred p, q;\nsetp.ne.u32 p, %1, 0;\nbar.red.or.pred q, %2, 128, p;\nselp.u32 %0, 1, 0, q;\n}" : "=r"(r) : "r"((uint32_t)v), "r"(w ? 4 : 3) : "memory");
  return __any_sync(0xffffffffu, r);
}
__device__ __forceinline__ int fresh_warp() { uint32_t t; asm volatile("mov.u32 %0, %%tid.x;" : "=r"(t)); return __shfl_sync(0xffffffffu, (int)(t >> 5) - 4, 0); }
__device__ __forceinline__ void cluster_sync_relaxed() { asm volatile("barrier.cluster.arrive.relaxed.aligned;\nbarrier.cluster.wait.aligned;" ::: "memory"); }
__device__ __forceinline__ unsigned ld_acquire(const unsigned* p) { unsigned v; asm volatile("ld.acquire.gpu.global.u32 %0, [%1];" : "=r"(v) : "l"(p) : "memory"); return v; }
__device__ __forceinline__ void red_release(unsigned* p, unsigned v) { asm volatile("red.release.gpu.global.add.u32 [%0], %1;" :: "l"(p), "r"(v) : "memory"); }
__device__ __forceinline__ void flag_wait(const unsigned* p, unsigned target) {
  uint32_t n = 0;
  while (ld_acquire(p) < target) { trap_if(++n > SPIN_LIMIT); __nanosleep(20); }
}
__device__ __forceinline__ void st_tagged(uint2* p, float a, float b, uint32_t tag) {
  asm volatile("{\n.reg .b64 x;\nmov.b64 x, {%1, %2};\nst.relaxed.gpu.global.b64 [%0], x;\n}" :: "l"(p),
               "r"((__float_as_uint(a) & ~63u) | (tag & 63u)), "r"((__float_as_uint(b) & ~63u) | (tag >> 6)) : "memory");
}
__device__ __forceinline__ uint4 ld_tagged2(const uint2* p) {
  uint4 v;
  asm volatile("{\n.reg .b64 x, y;\nld.relaxed.gpu.global.v2.b64 {x, y}, [%4];\nmov.b64 {%0, %1}, x;\nmov.b64 {%2, %3}, y;\n}" : "=r"(v.x), "=r"(v.y), "=r"(v.z), "=r"(v.w) : "l"(p) : "memory");
  return v;
}
__device__ __forceinline__ bool tag_ok(uint32_t a, uint32_t b, uint32_t tag) { return ((a & 63u) | ((b & 63u) << 6)) == tag; }
__device__ __forceinline__ float untag(uint32_t v) { return __uint_as_float(v & ~63u); }
__device__ __forceinline__ uint32_t pack_bf16(float lo, float hi) { uint32_t r; asm("cvt.rn.bf16x2.f32 %0, %1, %2;" : "=r"(r) : "f"(hi), "f"(lo)); return r; }
__device__ __forceinline__ uint32_t bf2_fma(uint32_t a, uint32_t b, uint32_t c) { uint32_t r; asm("fma.rn.bf16x2 %0, %1, %2, %3;" : "=r"(r) : "r"(a), "r"(b), "r"(c)); return r; }
__device__ __forceinline__ uint32_t bf2_mul(uint32_t a, uint32_t b) { uint32_t r; asm("mul.rn.bf16x2 %0, %1, %2;" : "=r"(r) : "r"(a), "r"(b)); return r; }
__device__ __forceinline__ uint32_t bf2_add(uint32_t a, uint32_t b) { uint32_t r; asm("add.rn.bf16x2 %0, %1, %2;" : "=r"(r) : "r"(a), "r"(b)); return r; }
constexpr uint32_t BF2_HALF = 0x3f003f00u;
__device__ __forceinline__ float bf_lo(uint32_t v) { return __uint_as_float(v << 16); }
__device__ __forceinline__ float bf_hi(uint32_t v) { return __uint_as_float(v & 0xffff0000u); }
__device__ __forceinline__ float ex2(float x) { float y; asm("ex2.approx.ftz.f32 %0, %1;" : "=f"(y) : "f"(x)); return y; }
__device__ __forceinline__ float tanh_fast(float x) { float y; asm("tanh.approx.f32 %0, %1;" : "=f"(y) : "f"(x)); return y; }
__device__ __forceinline__ void stmatrix_x4(uint32_t addr, uint32_t a, uint32_t b, uint32_t c, uint32_t d) {
  asm volatile("stmatrix.sync.aligned.m8n8.x4.shared.b16 [%0], {%1, %2, %3, %4};" :: "r"(addr), "r"(a), "r"(b), "r"(c), "r"(d) : "memory");
}
__device__ __forceinline__ void ldmatrix_x4(uint32_t addr, uint32_t& a, uint32_t& b, uint32_t& c, uint32_t& d) {
  asm volatile("ldmatrix.sync.aligned.m8n8.x4.shared.b16 {%0, %1, %2, %3}, [%4];" : "=r"(a), "=r"(b), "=r"(c), "=r"(d) : "r"(addr) : "memory");
}
__device__ __forceinline__ uint32_t lane_id() { uint32_t l; asm volatile("mov.u32 %0, %%laneid;" : "=r"(l)); return l; }
__device__ __forceinline__ bool elect_one() {
  uint32_t r;
  asm volatile("{\n.reg .pred P;\nelect.sync _|P, 0xffffffff;\nselp.u32 %0, 1, 0, P;\n}" : "=r"(r));
  return r;
}

__device__ __forceinline__ void wgmma_m64n128k16_ss_tb0(float (&d)[64], uint64_t da, uint64_t db, int scale_d) {
  asm volatile("{\n.reg .pred p;\nsetp.ne.b32 p, %66, 0;\n"
    "wgmma.mma_async.sync.aligned.m64n128k16.f32.bf16.bf16 "
    "{%0, %1, %2, %3, %4, %5, %6, %7, %8, %9, %10, %11, %12, %13, %14, %15, %16, %17, %18, %19, %20, %21, %22, %23, %24, %25, %26, %27, %28, %29, %30, %31, %32, %33, %34, %35, %36, %37, %38, %39, %40, %41, %42, %43, %44, %45, %46, %47, %48, %49, %50, %51, %52, %53, %54, %55, %56, %57, %58, %59, %60, %61, %62, %63}, "
    "%64, %65, p, 1, 1, 0, 0;\n}\n"
    : "+f"(d[0]), "+f"(d[1]), "+f"(d[2]), "+f"(d[3]), "+f"(d[4]), "+f"(d[5]), "+f"(d[6]), "+f"(d[7]), "+f"(d[8]), "+f"(d[9]), "+f"(d[10]), "+f"(d[11]), "+f"(d[12]), "+f"(d[13]), "+f"(d[14]), "+f"(d[15]), "+f"(d[16]), "+f"(d[17]), "+f"(d[18]), "+f"(d[19]), "+f"(d[20]), "+f"(d[21]), "+f"(d[22]), "+f"(d[23]), "+f"(d[24]), "+f"(d[25]), "+f"(d[26]), "+f"(d[27]), "+f"(d[28]), "+f"(d[29]), "+f"(d[30]), "+f"(d[31]), "+f"(d[32]), "+f"(d[33]), "+f"(d[34]), "+f"(d[35]), "+f"(d[36]), "+f"(d[37]), "+f"(d[38]), "+f"(d[39]), "+f"(d[40]), "+f"(d[41]), "+f"(d[42]), "+f"(d[43]), "+f"(d[44]), "+f"(d[45]), "+f"(d[46]), "+f"(d[47]), "+f"(d[48]), "+f"(d[49]), "+f"(d[50]), "+f"(d[51]), "+f"(d[52]), "+f"(d[53]), "+f"(d[54]), "+f"(d[55]), "+f"(d[56]), "+f"(d[57]), "+f"(d[58]), "+f"(d[59]), "+f"(d[60]), "+f"(d[61]), "+f"(d[62]), "+f"(d[63])
    : "l"(da), "l"(db), "r"(scale_d));
}
__device__ __forceinline__ void wgmma_m64n256k16_ss_tb1(float (&d)[128], uint64_t da, uint64_t db, int scale_d) {
  asm volatile("{\n.reg .pred p;\nsetp.ne.b32 p, %130, 0;\n"
    "wgmma.mma_async.sync.aligned.m64n256k16.f32.bf16.bf16 "
    "{%0, %1, %2, %3, %4, %5, %6, %7, %8, %9, %10, %11, %12, %13, %14, %15, %16, %17, %18, %19, %20, %21, %22, %23, %24, %25, %26, %27, %28, %29, %30, %31, %32, %33, %34, %35, %36, %37, %38, %39, %40, %41, %42, %43, %44, %45, %46, %47, %48, %49, %50, %51, %52, %53, %54, %55, %56, %57, %58, %59, %60, %61, %62, %63, %64, %65, %66, %67, %68, %69, %70, %71, %72, %73, %74, %75, %76, %77, %78, %79, %80, %81, %82, %83, %84, %85, %86, %87, %88, %89, %90, %91, %92, %93, %94, %95, %96, %97, %98, %99, %100, %101, %102, %103, %104, %105, %106, %107, %108, %109, %110, %111, %112, %113, %114, %115, %116, %117, %118, %119, %120, %121, %122, %123, %124, %125, %126, %127}, "
    "%128, %129, p, 1, 1, 0, 1;\n}\n"
    : "+f"(d[0]), "+f"(d[1]), "+f"(d[2]), "+f"(d[3]), "+f"(d[4]), "+f"(d[5]), "+f"(d[6]), "+f"(d[7]), "+f"(d[8]), "+f"(d[9]), "+f"(d[10]), "+f"(d[11]), "+f"(d[12]), "+f"(d[13]), "+f"(d[14]), "+f"(d[15]), "+f"(d[16]), "+f"(d[17]), "+f"(d[18]), "+f"(d[19]), "+f"(d[20]), "+f"(d[21]), "+f"(d[22]), "+f"(d[23]), "+f"(d[24]), "+f"(d[25]), "+f"(d[26]), "+f"(d[27]), "+f"(d[28]), "+f"(d[29]), "+f"(d[30]), "+f"(d[31]), "+f"(d[32]), "+f"(d[33]), "+f"(d[34]), "+f"(d[35]), "+f"(d[36]), "+f"(d[37]), "+f"(d[38]), "+f"(d[39]), "+f"(d[40]), "+f"(d[41]), "+f"(d[42]), "+f"(d[43]), "+f"(d[44]), "+f"(d[45]), "+f"(d[46]), "+f"(d[47]), "+f"(d[48]), "+f"(d[49]), "+f"(d[50]), "+f"(d[51]), "+f"(d[52]), "+f"(d[53]), "+f"(d[54]), "+f"(d[55]), "+f"(d[56]), "+f"(d[57]), "+f"(d[58]), "+f"(d[59]), "+f"(d[60]), "+f"(d[61]), "+f"(d[62]), "+f"(d[63]), "+f"(d[64]), "+f"(d[65]), "+f"(d[66]), "+f"(d[67]), "+f"(d[68]), "+f"(d[69]), "+f"(d[70]), "+f"(d[71]), "+f"(d[72]), "+f"(d[73]), "+f"(d[74]), "+f"(d[75]), "+f"(d[76]), "+f"(d[77]), "+f"(d[78]), "+f"(d[79]), "+f"(d[80]), "+f"(d[81]), "+f"(d[82]), "+f"(d[83]), "+f"(d[84]), "+f"(d[85]), "+f"(d[86]), "+f"(d[87]), "+f"(d[88]), "+f"(d[89]), "+f"(d[90]), "+f"(d[91]), "+f"(d[92]), "+f"(d[93]), "+f"(d[94]), "+f"(d[95]), "+f"(d[96]), "+f"(d[97]), "+f"(d[98]), "+f"(d[99]), "+f"(d[100]), "+f"(d[101]), "+f"(d[102]), "+f"(d[103]), "+f"(d[104]), "+f"(d[105]), "+f"(d[106]), "+f"(d[107]), "+f"(d[108]), "+f"(d[109]), "+f"(d[110]), "+f"(d[111]), "+f"(d[112]), "+f"(d[113]), "+f"(d[114]), "+f"(d[115]), "+f"(d[116]), "+f"(d[117]), "+f"(d[118]), "+f"(d[119]), "+f"(d[120]), "+f"(d[121]), "+f"(d[122]), "+f"(d[123]), "+f"(d[124]), "+f"(d[125]), "+f"(d[126]), "+f"(d[127])
    : "l"(da), "l"(db), "r"(scale_d));
}
__device__ __forceinline__ void wgmma_m64n128k16_rs_tb1(float (&d)[64], uint32_t a0, uint32_t a1, uint32_t a2, uint32_t a3, uint64_t db, int scale_d) {
  asm volatile("{\n.reg .pred p;\nsetp.ne.b32 p, %69, 0;\n"
    "wgmma.mma_async.sync.aligned.m64n128k16.f32.bf16.bf16 "
    "{%0, %1, %2, %3, %4, %5, %6, %7, %8, %9, %10, %11, %12, %13, %14, %15, %16, %17, %18, %19, %20, %21, %22, %23, %24, %25, %26, %27, %28, %29, %30, %31, %32, %33, %34, %35, %36, %37, %38, %39, %40, %41, %42, %43, %44, %45, %46, %47, %48, %49, %50, %51, %52, %53, %54, %55, %56, %57, %58, %59, %60, %61, %62, %63}, "
    "{%64, %65, %66, %67}, %68, p, 1, 1, 1;\n}\n"
    : "+f"(d[0]), "+f"(d[1]), "+f"(d[2]), "+f"(d[3]), "+f"(d[4]), "+f"(d[5]), "+f"(d[6]), "+f"(d[7]), "+f"(d[8]), "+f"(d[9]), "+f"(d[10]), "+f"(d[11]), "+f"(d[12]), "+f"(d[13]), "+f"(d[14]), "+f"(d[15]), "+f"(d[16]), "+f"(d[17]), "+f"(d[18]), "+f"(d[19]), "+f"(d[20]), "+f"(d[21]), "+f"(d[22]), "+f"(d[23]), "+f"(d[24]), "+f"(d[25]), "+f"(d[26]), "+f"(d[27]), "+f"(d[28]), "+f"(d[29]), "+f"(d[30]), "+f"(d[31]), "+f"(d[32]), "+f"(d[33]), "+f"(d[34]), "+f"(d[35]), "+f"(d[36]), "+f"(d[37]), "+f"(d[38]), "+f"(d[39]), "+f"(d[40]), "+f"(d[41]), "+f"(d[42]), "+f"(d[43]), "+f"(d[44]), "+f"(d[45]), "+f"(d[46]), "+f"(d[47]), "+f"(d[48]), "+f"(d[49]), "+f"(d[50]), "+f"(d[51]), "+f"(d[52]), "+f"(d[53]), "+f"(d[54]), "+f"(d[55]), "+f"(d[56]), "+f"(d[57]), "+f"(d[58]), "+f"(d[59]), "+f"(d[60]), "+f"(d[61]), "+f"(d[62]), "+f"(d[63])
    : "r"(a0), "r"(a1), "r"(a2), "r"(a3), "l"(db), "r"(scale_d));
}
__device__ __forceinline__ void wgmma_m64n128k16_ss_tb1(float (&d)[64], uint64_t da, uint64_t db, int scale_d) {
  asm volatile("{\n.reg .pred p;\nsetp.ne.b32 p, %66, 0;\n"
    "wgmma.mma_async.sync.aligned.m64n128k16.f32.bf16.bf16 "
    "{%0, %1, %2, %3, %4, %5, %6, %7, %8, %9, %10, %11, %12, %13, %14, %15, %16, %17, %18, %19, %20, %21, %22, %23, %24, %25, %26, %27, %28, %29, %30, %31, %32, %33, %34, %35, %36, %37, %38, %39, %40, %41, %42, %43, %44, %45, %46, %47, %48, %49, %50, %51, %52, %53, %54, %55, %56, %57, %58, %59, %60, %61, %62, %63}, "
    "%64, %65, p, 1, 1, 0, 1;\n}\n"
    : "+f"(d[0]), "+f"(d[1]), "+f"(d[2]), "+f"(d[3]), "+f"(d[4]), "+f"(d[5]), "+f"(d[6]), "+f"(d[7]), "+f"(d[8]), "+f"(d[9]), "+f"(d[10]), "+f"(d[11]), "+f"(d[12]), "+f"(d[13]), "+f"(d[14]), "+f"(d[15]), "+f"(d[16]), "+f"(d[17]), "+f"(d[18]), "+f"(d[19]), "+f"(d[20]), "+f"(d[21]), "+f"(d[22]), "+f"(d[23]), "+f"(d[24]), "+f"(d[25]), "+f"(d[26]), "+f"(d[27]), "+f"(d[28]), "+f"(d[29]), "+f"(d[30]), "+f"(d[31]), "+f"(d[32]), "+f"(d[33]), "+f"(d[34]), "+f"(d[35]), "+f"(d[36]), "+f"(d[37]), "+f"(d[38]), "+f"(d[39]), "+f"(d[40]), "+f"(d[41]), "+f"(d[42]), "+f"(d[43]), "+f"(d[44]), "+f"(d[45]), "+f"(d[46]), "+f"(d[47]), "+f"(d[48]), "+f"(d[49]), "+f"(d[50]), "+f"(d[51]), "+f"(d[52]), "+f"(d[53]), "+f"(d[54]), "+f"(d[55]), "+f"(d[56]), "+f"(d[57]), "+f"(d[58]), "+f"(d[59]), "+f"(d[60]), "+f"(d[61]), "+f"(d[62]), "+f"(d[63])
    : "l"(da), "l"(db), "r"(scale_d));
}


enum { TM_XN, TM_WSP, TM_U, TM_O, TM_Q, TM_X, TM_SA, TM_G, TM_K, TM_V, TM_WO64,
       TM_WIN, TM_WQ, TM_Z2, TM_WOUT, TM_WO, TS_Q, TS_O, TS_Z2, TS_U, TS_SA, TS_G, TS_OUT, TM_COUNT };
enum { T_Z2 = 0, T_Q = 1, T_U = 2, T_ATT = 3, T_SA = 4, T_FIN = 5, T_END = 7 };
constexpr int NCLUSTER = 66, MAXI = 14;
struct alignas(64) Params {
  const bf16* x;
  const bf16* b_sp;
  CUtensorMap tm[TM_COUNT];
  uint16_t items[NCLUSTER][MAXI];
};

constexpr uint32_t G_STAGE = 49152, G_A = 16384, KV_SLOT = 32768;
constexpr uint32_t OFF_Q1 = 163840, OFF_Q0 = 196608, OFF_BAR = 229376, OFF_LN = OFF_BAR + 256, SMEM_BYTES = OFF_LN + 1024;
constexpr uint32_t B_GF = 0, B_GE = 32, B_KF = 64, B_KE = 104, B_QF = 144, B_QE = 160, B_XF = 176, B_XR = 184, B_STG = 192, B_FREE = 200, B_GO = 208, B_LN = 216, B_TAG = 224, B_RDY = 228, B_PROG = 232, B_PUB = 248;
constexpr int SA_HEADS = 18;
constexpr int SW_NS = 40;
constexpr int ST_ROWS = 16;
constexpr int ST_FLY = 2;
constexpr int KV_PF = 4;
constexpr int FIN_PREP = 8;
constexpr int OWN_OFF = 8;
constexpr int Z_DELAY = 3;
constexpr int SW_ATT = 800;
constexpr int OUT_PF = 8;
constexpr int SA_ROT = 1;
constexpr uint32_t FIN_SLOT0 = (0x0320u >> (4 * ((28 + 2 * SA_HEADS + SA_ROT) & 3))) & 15;
constexpr float SM_C = 0.08838834764831845f * 1.4426950408889634f;
constexpr float GELU_A = 0.7978845608028654f, GELU_B = 0.7978845608028654f * 0.044715f;
constexpr float SM_LO = 1e-7f, SM_HI = 1e12f;
constexpr float SM_THR = 1024.f;


extern __shared__ __align__(1024) uint8_t smem_raw[];
__device__ __forceinline__ uint32_t smem_base() { return smem_u32(smem_raw); }

struct Ring { uint32_t s, ph; };
template <int N> __device__ __forceinline__ void ring_adv(Ring& r) { if (++r.s == N) { r.s = 0; r.ph ^= 1; } }

__device__ __forceinline__ int get_item(const Params& p, int i) {
  uint32_t b; asm volatile("mov.u32 %0, %%ctaid.x;" : "=r"(b));
  return p.items[b >> 1][i];
}
struct Cons {
  uint32_t sb;
  int warp;
  Ring g;
  uint32_t rot;
  uint32_t fph;
};

__device__ __forceinline__ void stage_acquire(const Cons& c) { mbar_spin(c.sb + OFF_BAR + B_FREE, c.fph); }
__device__ __forceinline__ void stage_commit(Cons& c) {
  __syncwarp();
  if (lane_id() == 0) mbar_arrive(c.sb + OFF_BAR + B_STG);
  c.fph ^= 1;
}

__device__ __forceinline__ void release_slot(const Cons& c, uint32_t bar) {
  if (lane_id() == 0 && (c.warp & 3) < 2) mbar_arrive_cta(bar, c.warp & 1);
}
constexpr uint64_t DESC_HI = (uint64_t)0x40000040u << 32;

template <bool FIRST> __device__ __forceinline__ void gemm_step(float (&acc)[128], Cons& c) {
  mbar_spin(c.sb + OFF_BAR + B_GF + 8 * c.g.s, c.g.ph);
  const uint32_t st = ((c.sb & 0x3FFFF) >> 4) + ((c.g.s + c.rot) & 3) * (G_STAGE >> 4);
  const uint32_t da = st + (c.warp >> 2) * 512 + (1u << 16), db = st + (G_A >> 4) + ((8192u >> 4) << 16);
  wgmma_fence();
#pragma unroll
  for (int kk = 0; kk < 4; kk++) wgmma_m64n256k16_ss_tb1(acc, DESC_HI | (da + kk * 2), DESC_HI | (db + kk * 128), !(FIRST && kk == 0));
  wgmma_commit();
}

template <int N> __device__ __forceinline__ void stage_chunks(uint32_t buf, uint32_t stride, const uint32_t* pk) {
  const uint32_t ln = lane_id();
  const uint32_t a = buf + ((ln & 15) << 7);
  const uint32_t x = ln & 7, hi = ln >> 4;
#pragma unroll
  for (int i = 0; i < 4 * N; i++) stmatrix_x4(a + (i >> 2) * stride + (((2 * (i & 3) + hi) ^ x) << 4), pk[4 * i], pk[4 * i + 1], pk[4 * i + 2], pk[4 * i + 3]);
}

__device__ __forceinline__ float act2_fn(float x, float a, float b) {
  return fmaf(x, tanh_fast(x * fmaf(x * x, b, a)), x);
}
__device__ __forceinline__ float quad_sum(float v) { v += __shfl_xor_sync(0xffffffffu, v, 1); v += __shfl_xor_sync(0xffffffffu, v, 2); return v; }
__device__ __forceinline__ float quad_max(float v) { v = fmaxf(v, __shfl_xor_sync(0xffffffffu, v, 1)); v = fmaxf(v, __shfl_xor_sync(0xffffffffu, v, 2)); return v; }

__device__ __forceinline__ uint32_t load_tag(const Cons& c) { uint32_t t; asm volatile("ld.volatile.shared.u32 %0, [%1];" : "=r"(t) : "r"(c.sb + OFF_BAR + B_TAG)); return t; }

struct Shadow {
  int act;
  int store;
};
__device__ __forceinline__ void rotate16(uint32_t (&h)[64]) {
#pragma unroll
  for (int i = 0; i < 16; i++)
    asm volatile("{\n.reg .b32 t;\nmov.b32 t, %0;\nmov.b32 %0, %1;\nmov.b32 %1, %2;\nmov.b32 %2, %3;\nmov.b32 %3, t;\n}" : "+r"(h[i]), "+r"(h[i + 16]), "+r"(h[i + 32]), "+r"(h[i + 48]));
}

template <int O>
__device__ __forceinline__ void act_block(uint32_t (&held)[64], float ca, float cb, bool first, float& u0, float& u1, float& s0, float& s1, float& q0, float& q1) {
#pragma unroll
  for (int i = O; i < O + 4; i += 2) {
    const float a0 = act2_fn(bf_lo(held[i]), ca, cb), a1 = act2_fn(bf_hi(held[i]), ca, cb);
    const float b0 = act2_fn(bf_lo(held[i + 1]), ca, cb), b1 = act2_fn(bf_hi(held[i + 1]), ca, cb);
    if (i == 0 && first) { u0 = a0; u1 = b0; }
    float d;
    d = a0 - u0; s0 += d; q0 = fmaf(d, d, q0); d = a1 - u0; s0 += d; q0 = fmaf(d, d, q0);
    d = b0 - u1; s1 += d; q1 = fmaf(d, d, q1); d = b1 - u1; s1 += d; q1 = fmaf(d, d, q1);
    held[i] = pack_bf16(a0, a1); held[i + 1] = pack_bf16(b0, b1);
  }
}

template <int O> __device__ __forceinline__ void stage_half(Cons& c, uint32_t (&held)[64], int mode) {
  if (mode == 2) {
    uint32_t a0, a1, r0, r1;
    const uint32_t la = c.sb + OFF_LN + (c.warp * 16 + (lane_id() >> 2)) * 8;
    mbar_spin(c.sb + OFF_BAR + B_LN, 0);
    asm volatile("ld.shared.v2.b32 {%0, %1}, [%2];" : "=r"(r0), "=r"(a0) : "r"(la));
    asm volatile("ld.shared.v2.b32 {%0, %1}, [%2];" : "=r"(r1), "=r"(a1) : "r"(la + 64));
#pragma unroll
    for (int i = O; i < O + 32; i += 2) { held[i] = bf2_mul(bf2_add(held[i], a0), r0); held[i + 1] = bf2_mul(bf2_add(held[i + 1], a1), r1); }
  }
  if (O == 0 && mode == 3) {
#pragma unroll
    for (int i = 0; i < 64; i++) held[i] = bf2_mul(held[i], BF2_HALF);
  }
  stage_acquire(c);
  stage_chunks<2>(c.sb + OFF_Q0 + c.warp * 2048, 16384, held + O);
  stage_commit(c);
}

__device__ __forceinline__ void gemm_seg(float (&acc)[128], uint32_t (&held)[64], Cons& c, const Params& p, Shadow& sh, int nsteps, bool hold) {
  const bool elected = lane_id() == 0 && (c.warp & 3) < 2;
  uint32_t rel;
  asm("mapa.shared::cluster.u32 %0, %1, %2;" : "=r"(rel) : "r"(c.sb + OFF_BAR + B_GE), "r"((uint32_t)(c.warp & 1)));
  gemm_step<true>(acc, c);
  ring_adv<4>(c.g);
  int k = 1;
#define G_STEP()                                                                                                       \
  { gemm_step<false>(acc, c);                                                                                          \
    wgmma_wait<1>();                                                                                                   \
    if (elected) asm volatile("mbarrier.arrive.shared::cluster.b64 _, [%0];" :: "r"(rel + 8 * ((c.g.s - 1) & 3)) : "memory"); \
    ring_adv<4>(c.g);                                                                                                  \
    k++; }
  if (sh.act != 0) {
    float u0 = 0.f, u1 = 0.f, s0 = 0.f, s1 = 0.f, q0 = 0.f, q1 = 0.f;
    const float ca = sh.act == 3 ? 0.5f : GELU_A, cb = sh.act == 3 ? 0.f : GELU_B;
#pragma unroll 1
    while (true) {
      act_block<0>(held, ca, cb, k == 1, u0, u1, s0, s1, q0, q1);
      G_STEP()
      act_block<4>(held, ca, cb, false, u0, u1, s0, s1, q0, q1);
      G_STEP()
      act_block<8>(held, ca, cb, false, u0, u1, s0, s1, q0, q1);
      G_STEP()
      act_block<12>(held, ca, cb, false, u0, u1, s0, s1, q0, q1);
      rotate16(held);
      if (k == 16) break;
      G_STEP()
    }
    if (sh.act == 2) {
      const int zi = get_item(p, 0);
      const int ln = lane_id(), row0 = (((zi >> 5) & 31) * 2 + (blockIdx.x & 1)) * 128 + c.warp * 16 + (ln >> 2), ql = ln & 3;
      const float m0 = fmaf(s0, 1.f / 64, u0), m1 = fmaf(s1, 1.f / 64, u1);
      q0 -= s0 * s0 * (1.f / 64); q1 -= s1 * s1 * (1.f / 64);
      const float mu0 = quad_sum(m0) * 0.25f, mu1 = quad_sum(m1) * 0.25f;
      q0 = quad_sum(fmaf(64.f * (m0 - mu0), m0 - mu0, q0)); q1 = quad_sum(fmaf(64.f * (m1 - mu1), m1 - mu1, q1));
      if (ql < 2) st_tagged(&g_stats[(row0 + 8 * ql) * 8 + (zi & 31)], ql ? mu1 : mu0, ql ? q1 : q0, load_tag(c));
      if (ln == 0) mbar_arrive(c.sb + OFF_BAR + B_PUB);
    }
  }
  const int s0 = sh.store == 0 ? -9 : k + (sh.store == 2 ? Z_DELAY : 1), s1 = sh.store == 3 ? -9 : s0 + 3;
  hold = hold && k < nsteps;
#pragma unroll 1
  while (k < nsteps) {
    G_STEP()
    if (k == s0) stage_half<0>(c, held, sh.store);
    else if (k == s1) stage_half<32>(c, held, sh.store);
    else if (hold && k == nsteps - 2 && c.warp >= 4) named_sync(6);
  }
  if (hold && c.warp < 4) asm volatile("bar.arrive 6, 256;" ::: "memory");
  wgmma_wait<0>();
  fence_regs(acc);
  if (elected) asm volatile("mbarrier.arrive.shared::cluster.b64 _, [%0];" :: "r"(rel + 8 * ((c.g.s - 1) & 3)) : "memory");
  sh.store = sh.act == 2 ? 2 : 0;
  sh.act = 0;
}

template <bool SUB> __device__ __forceinline__ void softmax_exp(const float (&S)[64], uint32_t (&P)[32], float m0, float m1, float& s0, float& s1) {
  float a0 = 0.f, a1 = 0.f, b0 = 0.f, b1 = 0.f;
#pragma unroll
  for (int j = 0; j < 16; j++) {
    const float p0 = ex2(SUB ? S[4 * j] - m0 : S[4 * j]), p1 = ex2(SUB ? S[4 * j + 1] - m0 : S[4 * j + 1]);
    const float p2 = ex2(SUB ? S[4 * j + 2] - m1 : S[4 * j + 2]), p3 = ex2(SUB ? S[4 * j + 3] - m1 : S[4 * j + 3]);
    a0 += p0; b0 += p1; a1 += p2; b1 += p3;
    P[2 * j] = pack_bf16(p0, p1); P[2 * j + 1] = pack_bf16(p2, p3);
  }
  s0 = a0 + b0; s1 = a1 + b1;
}
__device__ __forceinline__ void row_max(const float (&S)[64], float& x0, float& x1) {
  float a0 = fmaxf(S[0], S[1]), a1 = fmaxf(S[2], S[3]);
#pragma unroll
  for (int j = 1; j < 16; j++) { a0 = fmaxf(a0, fmaxf(S[4 * j], S[4 * j + 1])); a1 = fmaxf(a1, fmaxf(S[4 * j + 2], S[4 * j + 3])); }
  x0 = quad_max(a0); x1 = quad_max(a1);
}

__device__ __forceinline__ void issue_qk(float (&S)[64], uint32_t da, uint32_t db) {
#pragma unroll
  for (int kk = 0; kk < 8; kk++) {
    const uint32_t o = (kk >> 2) * 1024 + (kk & 3) * 2;
    wgmma_m64n128k16_ss_tb0(S, DESC_HI | (da + o), DESC_HI | (db + o), kk > 0);
  }
}
__device__ __forceinline__ void issue_pv(float (&O)[64], const uint32_t (&P)[32], uint32_t db, int acc) {
#pragma unroll
  for (int kk = 0; kk < 8; kk++) wgmma_m64n128k16_rs_tb1(O, P[4 * kk], P[4 * kk + 1], P[4 * kk + 2], P[4 * kk + 3], DESC_HI | (db + kk * 128), (acc || kk > 0));
}

__device__ __forceinline__ void att_pack(const float (&O)[64], uint32_t (&pk)[32], float i0, float i1) {
#pragma unroll
  for (int j = 0; j < 16; j++) {
    pk[2 * j] = pack_bf16(O[4 * j] * i0, O[4 * j + 1] * i0);
    pk[2 * j + 1] = pack_bf16(O[4 * j + 2] * i1, O[4 * j + 3] * i1);
  }
}
__device__ __forceinline__ void att_stage(Cons& c, const uint32_t (&pk)[32], uint32_t qbuf) {
  stage_chunks<2>(c.sb + (qbuf ? OFF_Q1 : OFF_Q0) + c.warp * 2048, 16384, pk);
  stage_commit(c);
}

#define ATT_ISSUE(PIN, ACC, PV)                                                                                        \
  wgmma_fence();                                                                                                       \
  issue_qk(S, qd, kd); wgmma_commit();                                                                                 \
  if (g > 1) release_slot(c, vrel);                                                                                    \
  vready = mbar_test(vbar, vph);                                                                                       \
  if (PV) {                                                                                                            \
    mbar_spin(vbar, vph);                                                                                              \
    wgmma_fence();                                                                                                     \
    issue_pv(O, PIN, vd, ACC); wgmma_commit();                                                                         \
  } else {                                                                                                             \
    asm volatile("wgmma.commit_group.sync.aligned; // empty" ::: "memory");                                            \
  }                                                                                                                    \
  krel = kbar + (B_KE - B_KF); vrel = vbar + (B_KE - B_KF);                                                            \
  g++;                                                                                                                 \
  if (g < total) { kd = kd0 + kv.s * (KV_SLOT >> 4); kbar = bars + B_KF + 8 * kv.s; kph = kv.ph; ring_adv<5>(kv); }    \
  vd = vd0 + kv.s * (KV_SLOT >> 4); vbar = bars + B_KF + 8 * kv.s; vph = kv.ph; ring_adv<5>(kv);

#define ATT_WAIT_S()                                                                                                   \
  wgmma_wait<1>();                                                                                                     \
  fence_regs(S);                                                                                                       \
  release_slot(c, krel);                                                                                               \
  if (c.warp == 2) asm volatile("st.volatile.shared.u32 [%0], %1;" :: "r"(bars + B_PROG), "r"(g) : "memory");

#define ATT_SOFTMAX(POUT, FIRST)                                                                                       \
  fresh = false;                                                                                                       \
  _Pragma("unroll 1")                                                                                                  \
  while (true) {                                                                                                       \
    if (__builtin_expect(fresh, 0)) {                                                                                  \
      float x0, x1;                                                                                                    \
      row_max(S, x0, x1);                                                                                              \
      if (FIRST) m0 = m1 = -1e38f;                                                                                     \
      x0 = fmaxf(x0, m0); x1 = fmaxf(x1, m1);                                                                          \
      f0 = ex2(m0 - x0); f1 = ex2(m1 - x1);                                                                            \
      m0 = x0; m1 = x1; l0 *= f0; l1 *= f1;                                                                            \
      zero = false;                                                                                                    \
    }                                                                                                                  \
    if (zero) {                                                                                                        \
      softmax_exp<false>(S, POUT, m0, m1, s0, s1);                                                                     \
      bad = !(s0 <= SM_HI && s1 <= SM_HI) || ((FIRST) && (s0 < SM_LO || s1 < SM_LO));                                  \
    } else {                                                                                                           \
      softmax_exp<true>(S, POUT, m0, m1, s0, s1);                                                                      \
      bad = !(s0 <= SM_THR && s1 <= SM_THR);                                                                           \
    }                                                                                                                  \
    kready = mbar_test(kbar, kph) && vready;                                                                           \
    slow = fresh || __any_sync(0xffffffffu, bad || !kready);                                                           \
    if (__builtin_expect(!slow, 1)) break;                                                                             \
    if (fresh || !__any_sync(0xffffffffu, bad)) break;                                                                 \
    fresh = true;                                                                                                      \
  }                                                                                                                    \
  l0 += s0; l1 += s1;                                                                                                  \
  wgmma_wait<0>(); fence_regs(O);

#define ATT_RESCALE()                                                                                                  \
  { _Pragma("unroll")                                                                                                  \
    for (int i = 0; i < 16; i++) { O[4 * i] *= f0; O[4 * i + 1] *= f0; O[4 * i + 2] *= f1; O[4 * i + 3] *= f1; } }

__device__ __forceinline__ void att_stagger(const Cons& c, int g) {
  if (c.warp >= 4)
    asm volatile("{\n.reg .pred p;\n.reg .s32 v;\nLOOP:\nld.volatile.shared.s32 v, [%0];\nsetp.le.s32 p, v, %1;\n@p bra LOOP;\n}" :: "r"(c.sb + OFF_BAR + B_PROG), "r"(g) : "memory");
}

__device__ __forceinline__ void att_run(Cons& c, const Params& p, int it, int n) {
  const uint32_t bars = c.sb + OFF_BAR;
  float S[64], O[64];
  uint32_t P0[32], P1[32];
#pragma unroll
  for (int i = 0; i < 64; i++) O[i] = 0.f;
#pragma unroll
  for (int i = 0; i < 32; i++) P0[i] = P1[i] = 0u;
  fence_regs(O); fence_regs(P0); fence_regs(P1);
  float m0 = 0.f, m1 = 0.f, l0 = 0.f, l1 = 0.f, f0 = 1.f, f1 = 1.f, s0, s1, pl0 = 0.f, pl1 = 0.f;
  const int total = 16 * n;
  int g = 0;
  Ring kv = {1, 0};
  uint32_t kbar = bars + B_KF, kph = 0, vbar = bars + B_KF, vph = 0, krel, vrel = 0;
  const uint32_t kd0 = (uint32_t)make_desc(c.sb, 16, 1024), vd0 = (uint32_t)make_desc(c.sb, 16384, 1024);
  uint32_t qd = kd0 + ((OFF_Q0 + (c.warp >> 2) * 8192) >> 4), kd = kd0, vd = vd0;
  bool fresh, kready, vready, bad, slow, zero = false;
  mbar_spin(bars + B_QF, 0);
  mbar_spin(bars + B_KF, 0);
  att_stagger(c, 0);
#pragma unroll 1
  while (true) {
    ATT_ISSUE(P1, 1, g > 0)
    const bool first = ((g - 1) & 15) == 0;
    if (first) { pl0 = l0; pl1 = l1; m0 = m1 = l0 = l1 = 0.f; zero = true; }
    ATT_WAIT_S()
    ATT_SOFTMAX(P0, first)
    if (__builtin_expect(slow || first, 0)) {
      if (first) {
        if (g > 1) {
          att_pack(O, P1, __fdividef(1.f, quad_sum(pl0)), __fdividef(1.f, quad_sum(pl1)));
          att_stage(c, P1, ((g >> 4) & 1) ^ 1);
        }
      } else if (fresh) ATT_RESCALE();
      mbar_spin(kbar, kph);
      if (__any_sync(0xffffffffu, !kready)) att_stagger(c, g);
    }
    ATT_ISSUE(P0, !first, true)
    ATT_WAIT_S()
    ATT_SOFTMAX(P1, false)
    if (__builtin_expect(slow || (g & 15) == 0, 0)) {
      if (fresh) ATT_RESCALE();
      if (g == total) break;
      mbar_spin(kbar, kph);
      if (__any_sync(0xffffffffu, !kready)) att_stagger(c, g);
      if ((g & 15) == 0) {
        const int t = g >> 4;
        const uint32_t qb = t & 1;
        mbar_spin(bars + B_QF + 8 * qb, (t >> 1) & 1);
        qd = kd0 + (((qb ? OFF_Q1 : OFF_Q0) + (c.warp >> 2) * 8192) >> 4);
      }
    }
  }
  release_slot(c, vrel);
  mbar_spin(vbar, vph);
  wgmma_fence();
  issue_pv(O, P1, vd, 1); wgmma_commit();
  pl0 = __fdividef(1.f, quad_sum(l0)); pl1 = __fdividef(1.f, quad_sum(l1));
  wgmma_wait<0>();
  fence_regs(O);
  release_slot(c, vbar + (B_KE - B_KF));
  att_pack(O, P0, pl0, pl1);
  if ((get_item(p, it + n) >> 12) == T_END) {
    const uint32_t buf = c.sb + (((n - 1) & 1) ? OFF_Q1 : OFF_Q0) + c.warp * 2048;
    stage_chunks<2>(buf, 16384, P0);
    fence_async_smem();
    __syncwarp();
    if (elect_one()) {
      const int im = get_item(p, it + n - 1), col = ((im >> 5) & 31) * 128, row = ((im & 31) * 2 + (blockIdx.x & 1)) * 128 + c.warp * 16;
      tma_store_2d(&p.tm[TS_O], buf, col, row); tma_store_2d(&p.tm[TS_O], buf + 16384, col + 64, row);
      bulk_commit();
      bulk_wait<0>();
      mbar_arrive(bars + B_STG);
    }
    __syncwarp();
  } else {
    att_stage(c, P0, (n - 1) & 1);
  }
}

__global__ void __cluster_dims__(2, 1, 1) __launch_bounds__(384, 1) fused_kernel(const __grid_constant__ Params p) {
  const uint32_t sb = smem_base();
  const uint32_t bars = sb + OFF_BAR;
  const int tid = threadIdx.x, lane = tid & 31;
  const int warp_id = __shfl_sync(0xffffffffu, tid >> 5, 0), wg = warp_id >> 2;
  const uint32_t rank = blockIdx.x & 1;
  const uint16_t* items = p.items[blockIdx.x >> 1];
  const int gw = blockIdx.x * 8 + warp_id - 4;
  uint4 xv[2][4];
  if (wg != 0 && gw < SEQ / 2) {
#pragma unroll
    for (int rr = 0; rr < 2; rr++)
#pragma unroll
      for (int i = 0; i < 4; i++) xv[rr][i] = __ldg(reinterpret_cast<const uint4*>(p.x + (size_t)(gw * 2 + rr) * DM) + i * 32 + lane);
  }
  if (warp_id == 1 && lane < TM_COUNT) asm volatile("prefetch.tensormap [%0];" :: "l"(&p.tm[lane]) : "memory");
  if (tid == 0) {
    for (int i = 0; i < 4; i++) { mbar_init(bars + B_GF + 8 * i, 1); mbar_init(bars + B_GE + 8 * i, 4); }
    for (int i = 0; i < 5; i++) { mbar_init(bars + B_KF + 8 * i, 1); mbar_init(bars + B_KE + 8 * i, 4); }
    for (int i = 0; i < 2; i++) { mbar_init(bars + B_QF + 8 * i, 1); mbar_init(bars + B_QE + 8 * i, 1); }
    mbar_init(bars + B_XF, 2); mbar_init(bars + B_XR, 2); mbar_init(bars + B_STG, 8); mbar_init(bars + B_FREE, 1); mbar_init(bars + B_GO, 1); mbar_init(bars + B_LN, 2); mbar_init(bars + B_PUB, 8);
    asm volatile("fence.mbarrier_init.release.cluster;" ::: "memory");
  }
  asm volatile("barrier.cluster.arrive.relaxed.aligned;" ::: "memory");

  if (wg == 0) {
    asm volatile("setmaxnreg.dec.sync.aligned.u32 40;");
    asm volatile("barrier.cluster.wait.acquire.aligned;" ::: "memory");
    if (warp_id >= 2 && (items[0] >> 12) == T_Z2) {
      if (lane == 0) mbar_wait_sleep(bars + B_PUB, 0, 100);
      __syncwarp();
      uint32_t tag;
      asm volatile("ld.volatile.shared.u32 %0, [%1];" : "=r"(tag) : "r"(bars + B_TAG));
      const int r = (warp_id - 2) * 64 + lane;
      const uint2* ps = &g_stats[((((items[0] >> 5) & 31) * 2 + rank) * 128 + r) * 8];
      uint4 t[2][4];
      uint32_t cnt = 0;
      while (true) {
        bool ok = true;
#pragma unroll
        for (int i = 0; i < 8; i++) t[i >> 2][i & 3] = ld_tagged2(ps + (i >> 2) * 256 + (i & 3) * 2);
#pragma unroll
        for (int i = 0; i < 8; i++) { const uint4 v = t[i >> 2][i & 3]; ok = ok && tag_ok(v.x, v.y, tag) && ((i & 3) == 3 || tag_ok(v.z, v.w, tag)); }
        if (__all_sync(0xffffffffu, ok)) break;
        trap_if(++cnt > SPIN_LIMIT);
        __nanosleep(100);
      }
#pragma unroll
      for (int y = 0; y < 2; y++) {
        float u = 0.f, v = 0.f;
#pragma unroll
        for (int i = 0; i < 7; i++) u += untag((i & 1) ? t[y][i >> 1].z : t[y][i >> 1].x);
        u *= 1.f / 7;
#pragma unroll
        for (int i = 0; i < 7; i++) {
          const float d = untag((i & 1) ? t[y][i >> 1].z : t[y][i >> 1].x) - u;
          v += fmaf(256.f * d, d, untag((i & 1) ? t[y][i >> 1].w : t[y][i >> 1].y));
        }
        const float rs = rsqrtf(fmaxf(v, 0.f) * (1.f / FH) + 4e-5f);
        asm volatile("st.shared.v2.b32 [%0], {%1, %2};" :: "r"(sb + OFF_LN + (r + 32 * y) * 8), "r"(pack_bf16(rs, rs)), "r"(pack_bf16(-u, -u)) : "memory");
      }
      __syncwarp();
      if (lane == 0) mbar_arrive(bars + B_LN);
      __syncwarp();
    }
    if (warp_id == 0) {
      trap_if(sb & 1023);
      Ring g = {0, 1};
      int it = 0;
      uint32_t xph = 0;
      if (elect_one()) {
#pragma unroll 1
        for (;; it++) {
          const int item = items[it], type = item >> 12, b = item & 31, row = (((item >> 5) & 31) * 2 + rank) * 128;
          if (type >= T_ATT) break;
#pragma unroll 1
          for (int seg = 0; seg < (type == T_U ? 2 : 1); seg++) {
            const CUtensorMap* tA = &p.tm[seg ? TM_WSP : TM_XN];
            const CUtensorMap* tB = &p.tm[seg ? TM_Z2 : (type == T_Q ? TM_WQ : TM_WIN)];
            const int bchunk = b * 4 + (type == T_Z2 ? 28 : 0) + rank * 2;
            const unsigned* fl = seg ? &g_flags[F_Z2 + b * 32] : &g_flags[F_XN + (row >> 2)];
            const unsigned tgt = seg ? 16 : 128;
            int k = 0;
            if (it == 0 && seg == 0) {
              for (; k < 4; k++) {
                mbar_expect_tx(bars + B_GF + 8 * k, G_STAGE);
                tma_load_3d_mc(sb + k * G_STAGE + G_A + rank * 16384, tB, k * 64, bchunk, bars + B_GF + 8 * k);
              }
              g.ph ^= 1;
            }
            if (seg || type != T_U) { flag_wait(fl, tgt); fence_async_global(); }
            for (int x = 0; x < k; x++) tma_load_2d(sb + x * G_STAGE, tA, x * 64, row, bars + B_GF + 8 * x);
            if (it == 0) asm volatile("st.volatile.shared.v4.u32 [%0], {%1, %2, %2, %2};" :: "r"(bars + B_TAG), "r"(__ldcg(&g_epoch) % 4095u + 1), "r"(0) : "memory");
#pragma unroll 1
            for (; k < (seg ? 32 : 16); k++) {
              if (k == 3 && type == T_U && seg == 0) { mbar_wait(bars + B_XF, xph); xph ^= 1; }
              mbar_wait(bars + B_GE + 8 * g.s, g.ph);
              const uint32_t st = sb + g.s * G_STAGE, fb = bars + B_GF + 8 * g.s;
              mbar_expect_tx(fb, G_STAGE);
              tma_load_2d(st, tA, k * 64, row, fb);
              tma_load_3d_mc(st + G_A + rank * 16384, tB, k * 64, bchunk, fb);
              ring_adv<4>(g);
            }
          }
        }
      }
      { const int e = __ffs(__ballot_sync(0xffffffffu, elect_one())) - 1; it = __shfl_sync(0xffffffffu, it, e); g.ph = __shfl_sync(0xffffffffu, g.ph, e); }
      const int n = ((items[it] >> 10) & 3) + 3;
      Ring kv = {0, 1};
      if (elect_one()) {
        int prow = 0;
        {
          const int im = items[it];
          tma_prefetch_2d(&p.tm[(im & 1) ? TM_V : TM_K], rank * 64, ((im >> 5) & 31) * SEQ + ((im & 7) >> 1) * 128);
        }
#pragma unroll 1
        for (int x = 0; x <= 32 * n; x++) {
          const int gb = x >> 1, t = gb >> 4;
          const int hrow = ((items[it + t] >> 5) & 31) * SEQ;
          const bool isv = (x & 1) || x == 32 * n;
          if (x != 1) {
            if (x == 0 || x == 2) mbar_wait(bars + B_GE + 4 * x, g.ph);
            if (x == 4) { mbar_wait(bars + B_XF, xph); xph ^= 1; }
            mbar_wait(bars + B_KE + 8 * kv.s, kv.ph);
            mbar_expect_tx(bars + B_KF + 8 * kv.s, KV_SLOT);
            tma_load_2d_mc(sb + kv.s * KV_SLOT + rank * 16384, &p.tm[isv ? TM_V : TM_K], rank * 64, isv ? prow : hrow + (gb & 15) * 128, bars + B_KF + 8 * kv.s);
            ring_adv<5>(kv);
          }
          {
            const int gp = gb + KV_PF, ip = items[it + (gp >> 4)];
            if (gp < 16 * n && ((gp ^ ip) & 7) == 0) tma_prefetch_2d(&p.tm[(x & 1) ? TM_V : TM_K], rank * 64, ((ip >> 5) & 31) * SEQ + (gp & 15) * 128);
          }
          if (x == 32 * n - 8) mbar_arrive(bars + B_GO);
          if (x & 1) prow = hrow + (gb & 15) * 128;
          if ((x & 31) == 11 && t + 1 < n) {
            const int tq = t + 1;
            const int im = items[it + tq], h = (im >> 5) & 31, m = (im & 31) * 2 + rank;
            const uint32_t qb = tq & 1;
            flag_wait(&g_flags[F_Q + m * 16 + (h >> 1)], 1);
            fence_async_global();
            mbar_wait(bars + B_QE + 8 * qb, ((tq - 1) >> 1) & 1);
            const uint32_t dst = sb + (qb ? OFF_Q1 : OFF_Q0), fb = bars + B_QF + 8 * qb;
            mbar_expect_tx(fb, 32768);
            tma_load_2d(dst, &p.tm[TM_Q], h * 128, m * 128, fb);
            tma_load_2d(dst + 16384, &p.tm[TM_Q], h * 128 + 64, m * 128, fb);
          }
        }
      }
      __syncwarp();
      it += n;
      uint32_t ready = 0;
      auto wait_head = [&](int h) {
        if ((ready >> h) & 1) return;
        uint32_t cnt = 0;
        while (true) {
          asm volatile("ld.acquire.cta.shared.u32 %0, [%1];" : "=r"(ready) : "r"(bars + B_RDY) : "memory");
          if ((ready >> h) & 1) break;
          trap_if(++cnt > SPIN_LIMIT * 8);
          __nanosleep(20);
        }
        fence_async_global();
      };
      int item = items[it];
      if ((item >> 12) == T_SA) {
        const int m = ((item >> 5) & 31) * 2 + rank, b = item & 31;
        Ring dr = kv;
        wait_head(0);
#pragma unroll 1
        for (int i = 0; i < 28 + 2 * SA_HEADS; i++) {
          {
            const bool so = i >= 28;
            const int k = so ? i - 28 : i;
            if (so) wait_head(k >> 1);
            if (elect_one()) {
              if (i < 4) { for (int x = 0; x < ((0x1022 >> (4 * i)) & 3); x++) { mbar_wait(bars + B_KE + 8 * dr.s, dr.ph); ring_adv<5>(dr); } }
              if (i == 2) { mbar_wait(bars + B_XF, xph); xph ^= 1; }
              mbar_wait(bars + B_GE + 8 * g.s, g.ph);
              const uint32_t st = sb + ((g.s + SA_ROT) & 3) * G_STAGE, fb = bars + B_GF + 8 * g.s;
              mbar_expect_tx(fb, G_STAGE);
              tma_load_2d(st, &p.tm[so ? TM_O : TM_U], k * 64, m * 128, fb);
              tma_load_3d_mc(st + G_A + rank * 16384, &p.tm[so ? TM_WO : TM_WOUT], k * 64, b * 4 + rank * 2, fb);
            }
            ring_adv<4>(g);
          }
          const int ip = i + OUT_PF;
          if (ip < 28 + 2 * SA_HEADS && elect_one()) {
            const bool so = ip >= 28;
            const int k = so ? ip - 28 : ip;
            if ((ip & 3) == b && (!so || ((ready >> (k >> 1)) & 1))) tma_prefetch_2d(&p.tm[so ? TM_O : TM_U], k * 64, m * 128);
            if ((ip & 7) == (m >> 1)) tma_prefetch_3d(&p.tm[so ? TM_WO : TM_WOUT], k * 64, b * 4 + rank * 2);
          }
          __syncwarp();
        }
        item = items[++it];
      }
      if ((item >> 12) == T_FIN) {
        const bool own = item & 4;
        const int m = ((item >> 5) & 31) * 2 + rank, col = (item & 3) * 256 + (own ? 128 : 0);
        uint32_t ps = own ? FIN_SLOT0 : kv.s;
#pragma unroll 1
        for (int i = 2 * SA_HEADS; i <= 2 * NH; i++) {
          const bool extra = i == 2 * NH - FIN_PREP;
          if (extra && own) continue;
          const int k = i > 2 * NH - FIN_PREP ? i - 1 : i;
          if (!extra) wait_head(k >> 1);
          if (elect_one()) {
            if (i == 2 * SA_HEADS) {
              for (int y = k; y < k + 4; y++) if ((ready >> (y >> 1)) & 1) tma_prefetch_2d(&p.tm[TM_O], y * 64, m * 128);
            }
            if (own && i < 2 * SA_HEADS + 5) {
              const uint32_t s0 = ((0x22100u >> (4 * ps)) - SA_ROT) & 3, s1 = ((0x32110u >> (4 * ps)) - SA_ROT) & 3;
              mbar_wait(bars + B_GE + 8 * s0, g.ph ^ (s0 < g.s)); mbar_wait(bars + B_GE + 8 * s1, g.ph ^ (s1 < g.s));
            }
            if (extra) { flag_wait(&g_flags[F_S + m * 4 + (item & 3)], 2); fence_async_global(); }
            mbar_wait(bars + B_KE + 8 * kv.s, kv.ph);
            const uint32_t dst = sb + ps * KV_SLOT, fb = bars + B_KF + 8 * kv.s;
            if (++ps == 5) ps = 0;
            mbar_expect_tx(fb, KV_SLOT);
            if (!extra) {
              tma_load_2d(dst, &p.tm[TM_O], k * 64, m * 128, fb);
              tma_load_2d_mc(dst + 16384 + rank * 8192, &p.tm[TM_WO64], col + rank * 64, k * 64, fb);
            } else {
              tma_load_2d(dst, &p.tm[TM_SA], col, m * 128, fb);
              tma_load_2d(dst + 16384, &p.tm[TM_SA], col + 64, m * 128, fb);
            }
            ring_adv<5>(kv);
          }
          __syncwarp();
        }
      }
      unsigned last = 0;
      if (lane == 0 && (item >> 12) == T_FIN) mbar_wait_sleep(bars + B_XR, 0, 100);
      if (lane == 0) { __threadfence(); last = atomicInc(&g_done, gridDim.x - 1) == gridDim.x - 1; }
      last = __shfl_sync(0xffffffffu, last, 0);
      if (last) {
        for (int i = lane; i < F_TOTAL / 4; i += 32) reinterpret_cast<uint4*>(g_flags)[i] = make_uint4(0, 0, 0, 0);
        if (lane == 0) g_epoch = g_epoch + 1;
      }
    } else if (warp_id == 1) {
      if (elect_one()) {
        uint32_t ph = 0;
        int t = 0;
        unsigned* fq = nullptr;
        const bool z = (items[0] >> 12) == T_Z2;
#pragma unroll 1
        for (int it = 0;; it++) {
          const int ii = (z && it < 2) ? it ^ 1 : it;
          const int item = items[ii], type = item >> 12, a = (item >> 5) & 31, b = item & 31;
          if (type == T_END) break;
          const int nt = items[ii + 1] >> 12;
          int row = (a * 2 + rank) * 128, col = b * 256;
          unsigned* f = &g_flags[F_S + (a * 2 + rank) * 4 + b];
          int tm = TS_G, npair = 2;
          bool quad = false;
          uint32_t src = sb + OFF_Q0;
          if (type == T_Z2) { tm = TS_Z2; f = &g_flags[F_Z2 + b * 32]; }
          else if (type == T_Q) { tm = TS_Q; f = &g_flags[F_Q + (a * 2 + rank) * 16 + b]; if (z || nt >= T_ATT) { npair = 0; quad = true; } }
          else if (type == T_U) { tm = TS_U; f = &g_flags[F_U + (a * 2 + rank) * 32]; npair = 0; quad = true; }
          else if (type == T_ATT) { tm = TS_O; f = &g_flags[F_O + (b * 2 + rank) * 32 + a]; npair = 1; row = (b * 2 + rank) * 128; col = a * 128; if (t & 1) src = sb + OFF_Q1; }
          else if (type == T_FIN) npair = 1;
          auto load_fin = [&](int fi, int tmi, uint32_t qb) {
            const int fc = (fi & 3) * 256 + ((fi & 4) ? 128 : 0), fr = (((fi >> 5) & 31) * 2 + rank) * 128;
            mbar_expect_tx(bars + B_QF + 8 * qb, 32768);
            tma_load_2d(sb + (qb ? OFF_Q1 : OFF_Q0), &p.tm[tmi], fc, fr, bars + B_QF + 8 * qb);
            tma_load_2d(sb + (qb ? OFF_Q1 : OFF_Q0) + 16384, &p.tm[tmi], fc + 64, fr, bars + B_QF + 8 * qb);
          };
          if (type == T_ATT && nt == T_FIN) load_fin(items[ii + 1], TM_X, (t & 1) ^ 1);
          if (type == T_FIN) {
            if (!(item & 4)) { flag_wait(&g_flags[F_S + (a * 2 + rank) * 4 + (b & 3)], 1); fence_async_global(); load_fin(item, TM_G, (t & 1) ^ 1); }
            mbar_arrive(bars + B_XR);
          }
#pragma unroll 1
          for (int op = 0; op < npair + quad; op++) {
            const bool q = op == npair;
            const int c0 = (q || type == T_SA) ? col : col + op * 128;
            mbar_wait_sleep(bars + B_STG, ph, (type == T_ATT && nt == T_ATT) ? SW_ATT : SW_NS);
            if (type == T_FIN) break;
            ph ^= 1;
            fence_async_smem();
            if (type == T_SA && op == 1) { tm = TS_SA; load_fin(items[ii + 1], TM_X, 1); }
            int c1 = c0;
            if (q) {
              const CUtensorMap* tb = &p.tm[type == T_U ? TM_U : TM_Q];
              const bool pre = nt == T_ATT;
              tma_store_2d(tb, sb + (pre ? 2 * G_STAGE : OFF_Q1), c0 + (pre ? 0 : 128), row);
              tma_store_2d(tb, sb + (pre ? 3 * G_STAGE : OFF_Q1 + 16384), c0 + (pre ? 64 : 192), row);
              bulk_commit();
              bulk_wait_read<0>();
              mbar_arrive_cta(bars + B_XF, 0); mbar_arrive_cta(bars + B_XF, 1);
              if (pre) { src = sb + OFF_Q1; c1 += 128; }
            }
            if (nt != T_END) {
#pragma unroll 1
              for (int r = 0; r < 256; r += ST_ROWS) {
                tma_store_2d(&p.tm[tm], src + r * 128, c1 + (r >> 7) * 64, row + (r & 127));
                bulk_commit();
                bulk_wait_read<ST_FLY>();
              }
            }
            bulk_wait_read<0>();
            mbar_arrive(bars + B_FREE);
            if (type == T_ATT && (t & 1) && (nt == T_SA || (items[ii + 2] >> 12) == T_SA)) { mbar_arrive_cta(bars + B_XF, 0); mbar_arrive_cta(bars + B_XF, 1); }
            if (type == T_ATT) mbar_arrive(bars + B_QE + 8 * (t & 1));
            else if (nt == T_ATT) mbar_arrive(bars + B_QE + 8);
            if (z && it == 0) { fq = f; continue; }
            if (op + 1 >= npair || type == T_SA) {
              bulk_wait<0>();
              red_release(f, 1);
              if (type == T_Z2) red_release(fq, 1);
            }
          }
          if (type == T_ATT) t++;
          else if (t == 0 && (items[it + 1] >> 12) < T_ATT && (items[it + 2] >> 12) == T_ATT) {
            const int im = items[it + 2], h = (im >> 5) & 31, m = (im & 31) * 2 + rank;
            flag_wait(&g_flags[F_Q + m * 16 + (h >> 1)], 1);
            fence_async_global();
            mbar_expect_tx(bars + B_QF, 32768);
            tma_load_2d(sb + OFF_Q0, &p.tm[TM_Q], h * 128, m * 128, bars + B_QF);
            tma_load_2d(sb + OFF_Q0 + 16384, &p.tm[TM_Q], h * 128 + 64, m * 128, bars + B_QF);
          }
        }
      }
      __syncwarp();
    } else if (warp_id == 2) {
      int it = 0;
      while ((items[it] >> 12) <= T_ATT) it++;
      if ((items[it] >> 12) != T_END) {
        const bool sa = (items[it] >> 12) == T_SA;
        const int m = ((items[it] >> 5) & 31) * 2 + rank;
        if (lane == 0) {
          mbar_wait_sleep(bars + B_GO, 0, 500);
          if (sa) {
            const int b = items[it] & 3;
            flag_wait(&g_flags[F_U + m * 32], 7);
            fence_async_global();
            for (int y = b; y < OUT_PF; y += 4) tma_prefetch_2d(&p.tm[TM_U], y * 64, m * 128);
            tma_prefetch_3d(&p.tm[TM_WOUT], (m >> 1) * 64, b * 4 + rank * 2);
          }
          if (!sa) for (int y = m * 4 + (items[it] & 3); y < 16 * (NH - SA_HEADS); y += 64) tma_prefetch_3d(&p.tm[TM_WO], (2 * SA_HEADS + (y >> 3)) * 64, (y & 7) * 2);
        }
        __syncwarp();
        uint32_t cnt = 0;
        while (true) {
          const uint32_t r = __ballot_sync(0xffffffffu, ld_acquire(&g_flags[F_O + m * 32 + lane]) != 0);
          if (lane == 0) asm volatile("st.release.cta.shared.u32 [%0], %1;" :: "r"(bars + B_RDY), "r"(r) : "memory");
          if (r == ~0u) break;
          trap_if(++cnt > SPIN_LIMIT);
          __nanosleep(r >> 28 ? 20 : 300);
        }
        if (lane == 0) mbar_arrive(bars + B_XR);
      }
      __syncwarp();
    }
    cluster_sync_relaxed();
  } else {
    Cons c;
    c.sb = sb; c.warp = warp_id - 4; c.g = {0, 0}; c.fph = 1; c.rot = 0;
    if (gw < SEQ / 2) {
      float f[2][32], rs[2];
#pragma unroll
      for (int rr = 0; rr < 2; rr++) {
#pragma unroll
        for (int i = 0; i < 4; i++) {
          const uint4 v = xv[rr][i];
          f[rr][8 * i + 0] = bf_lo(v.x); f[rr][8 * i + 1] = bf_hi(v.x); f[rr][8 * i + 2] = bf_lo(v.y); f[rr][8 * i + 3] = bf_hi(v.y);
          f[rr][8 * i + 4] = bf_lo(v.z); f[rr][8 * i + 5] = bf_hi(v.z); f[rr][8 * i + 6] = bf_lo(v.w); f[rr][8 * i + 7] = bf_hi(v.w);
        }
        float s = 0.f;
#pragma unroll
        for (int i = 0; i < 32; i++) s += f[rr][i];
#pragma unroll
        for (int o = 16; o; o >>= 1) s += __shfl_xor_sync(0xffffffffu, s, o);
        const float mean = s * (1.f / DM);
        float q = 0.f;
#pragma unroll
        for (int i = 0; i < 32; i++) { f[rr][i] -= mean; q = fmaf(f[rr][i], f[rr][i], q); }
#pragma unroll
        for (int o = 16; o; o >>= 1) q += __shfl_xor_sync(0xffffffffu, q, o);
        rs[rr] = rsqrtf(q * (1.f / DM) + 1e-5f);
      }
      uint4* dst = reinterpret_cast<uint4*>(g_xn + (size_t)gw * 2 * DM) + lane;
#pragma unroll
      for (int rr = 0; rr < 2; rr++) {
        const float r = rs[rr];
#pragma unroll
        for (int i = 0; i < 4; i++) {
          const float* y = &f[rr][8 * i];
          dst[rr * 128 + i * 32] = make_uint4(pack_bf16(y[0] * r, y[1] * r), pack_bf16(y[2] * r, y[3] * r), pack_bf16(y[4] * r, y[5] * r), pack_bf16(y[6] * r, y[7] * r));
        }
      }
      named_sync(7);
      if (tid == 128) red_release(&g_flags[F_XN + (gw >> 6) * 32], 16);
    }
    asm volatile("setmaxnreg.inc.sync.aligned.u32 232;");
    asm volatile("barrier.cluster.wait.acquire.aligned;" ::: "memory");
    int natt = 0;
    int it = 0;
    uint32_t held[64];
#pragma unroll
    for (int i = 0; i < 64; i++) held[i] = 0u;
    Shadow sh = {0, 0};
    float facc[64];
#pragma unroll 1
    while (true) {
      const int item = get_item(p, it), type = item >> 12, a = (item >> 5) & 31;
      c.warp = fresh_warp();
      if (type == T_ATT) {
        const int n = ((item >> 10) & 3) + 3;
        att_run(c, p, it, n);
#pragma unroll
        for (int i = 0; i < 64; i++) held[i] = 0u;
        natt = n;
        it += n;
        c.rot = SA_ROT;
        if ((get_item(p, it) >> 12) == T_SA) continue;
#pragma unroll
        for (int i = 0; i < 64; i++) facc[i] = 0.f;
        break;
      }
      float acc[128];
      const bool sa = type == T_SA;
      bool more = type >= T_U;
      int nsteps = sa ? 28 : 16;
      const bool direct = sh.act == 2 || (get_item(p, it + 1) >> 12) >= T_ATT;
      uint32_t bias0 = 0, bias1 = 0;
#pragma unroll 1
      while (true) {
        gemm_seg(acc, held, c, p, sh, nsteps, more || !direct || sa);
        if (type == T_Q) {
#pragma unroll
          for (int i = 0; i < 128; i++) acc[i] *= SM_C;
        }
        if (!more && direct) break;
#pragma unroll
        for (int i = 0; i < 64; i++) held[i] = pack_bf16(acc[2 * i], acc[2 * i + 1]);
        if (!more) break;
        more = false;
        nsteps = sa ? 2 * SA_HEADS : 32;
        sh.act = sa ? 3 : 1;
        if (sa) {
          sh.store = 3;
        } else {
          const int row0 = (a * 2 + rank) * 128 + c.warp * 16 + (lane_id() >> 2);
          asm volatile("ld.global.nc.u16 %0, [%1];" : "=r"(bias0) : "l"(p.b_sp + row0));
          asm volatile("ld.global.nc.u16 %0, [%1];" : "=r"(bias1) : "l"(p.b_sp + row0 + 8));
        }
      }
      c.warp = fresh_warp();
      if (direct) {
        const bool pre = !sa && sh.store != 2;
        const uint32_t hb0 = bf2_mul(bias0 * 0x10001u, BF2_HALF), hb1 = bf2_mul(bias1 * 0x10001u, BF2_HALF);
        stage_acquire(c);
#pragma unroll
        for (int h = 0; h < 2; h++) {
          uint32_t pk[32];
#pragma unroll
          for (int i = 0; i < 32; i++) pk[i] = pack_bf16(acc[64 * h + 2 * i], acc[64 * h + 2 * i + 1]);
          if (type == T_U) {
#pragma unroll
            for (int i = 0; i < 32; i++) pk[i] = bf2_mul(bf2_fma(pk[i], BF2_HALF, (i & 1) ? hb1 : hb0), held[32 * h + i]);
          }
          if (h) named_sync(5);
          stage_chunks<2>(sb + (h ? OFF_Q1 : (pre ? 2 * G_STAGE : OFF_Q0)) + c.warp * 2048, (!h && pre) ? G_STAGE : 16384, pk);
          if (sa) break;
        }
        stage_commit(c);
        if (sa) {
#pragma unroll
          for (int i = 0; i < 64; i++) facc[i] = acc[64 + i];
          it++;
          break;
        }
      } else if (type == T_Q) {
        sh.store = 1;
      } else {
        sh.act = 2;
      }
      it++;
    }
    const int fin = get_item(p, it);
    if ((fin >> 12) == T_FIN) {
      c.warp = fresh_warp();
      const bool own = fin & 4;
      Ring kv = {(uint32_t)(32 * natt) % 5, ((uint32_t)(32 * natt) / 5) & 1};
      uint32_t prev = 0, ps = own ? FIN_SLOT0 : kv.s;
      fence_regs(facc);
      auto fin_steps = [&](int k0, int k1) {
#pragma unroll 1
        for (int k = k0; k < k1; k++) {
          mbar_spin(bars + B_KF + 8 * kv.s, kv.ph);
          const uint32_t st = ((c.sb & 0x3FFFF) >> 4) + ps * (KV_SLOT >> 4);
          if (++ps == 5) ps = 0;
          const uint32_t da = st + (c.warp >> 2) * 512 + (1u << 16), db = st + 1024 + ((8192u >> 4) << 16);
          wgmma_fence();
#pragma unroll
          for (int kk = 0; kk < 4; kk++) wgmma_m64n128k16_ss_tb1(facc, DESC_HI | (da + kk * 2), DESC_HI | (db + kk * 128), 1);
          wgmma_commit();
          wgmma_wait<1>();
          if (k > 2 * SA_HEADS) release_slot(c, prev);
          prev = bars + B_KE + 8 * kv.s;
          ring_adv<5>(kv);
        }
      };
      const int kp = (own && ((fin >> 5) & 31) == 7) ? 2 * SA_HEADS + 5 : 2 * NH - FIN_PREP - (own ? OWN_OFF : 0);
      fin_steps(2 * SA_HEADS, kp);
      const uint32_t ln = lane_id(), xb = own ? 1 : natt & 1;
      const uint32_t lo = c.warp * 2048 + ((ln & 15) << 7);
      uint32_t xs[32];
      auto load_tile = [&](uint32_t base, uint32_t* d) {
#pragma unroll
        for (int i = 0; i < 8; i++) ldmatrix_x4(base + lo + (i >> 2) * 16384 + (((2 * (i & 3) + (ln >> 4)) ^ (ln & 7)) << 4), d[4 * i], d[4 * i + 1], d[4 * i + 2], d[4 * i + 3]);
      };
      const uint32_t xa = sb + (xb ? OFF_Q1 : OFF_Q0);
      mbar_spin(bars + B_QF + 8 * xb, ((natt + 1 - xb) >> 1) & 1);
      load_tile(xa, xs);
      if (!own) {
        mbar_spin(bars + B_QF + 8 * (xb ^ 1), ((natt + xb) >> 1) & 1);
        load_tile(sb + (xb ? OFF_Q0 : OFF_Q1), held + 32);
      }
      float gf[64], rf[64];
#pragma unroll
      for (int i = 0; i < 32; i++) { gf[2 * i] = bf_lo(held[32 + i]); gf[2 * i + 1] = bf_hi(held[32 + i]); rf[2 * i] = bf_lo(xs[i]); rf[2 * i + 1] = bf_hi(xs[i]); }
      if (!own) {
        mbar_spin(bars + B_KF + 8 * kv.s, kv.ph);
#pragma unroll
        for (int i = 0; i < 8; i++) {
          uint32_t t[4];
          ldmatrix_x4(sb + ps * KV_SLOT + lo + (i >> 2) * 16384 + (((2 * (i & 3) + (ln >> 4)) ^ (ln & 7)) << 4), t[0], t[1], t[2], t[3]);
#pragma unroll
          for (int y = 0; y < 4; y++) {
            rf[8 * i + 2 * y] = fmaf(bf_lo(t[y]), gf[8 * i + 2 * y], rf[8 * i + 2 * y]);
            rf[8 * i + 2 * y + 1] = fmaf(bf_hi(t[y]), gf[8 * i + 2 * y + 1], rf[8 * i + 2 * y + 1]);
          }
        }
        wg_any(c.warp >= 4, false);
        release_slot(c, bars + B_KE + 8 * kv.s);
        if (++ps == 5) ps = 0;
        ring_adv<5>(kv);
      }
      fence_regs(gf); fence_regs(rf);
      fin_steps(kp, 2 * NH);
      wgmma_wait<0>();
      fence_regs(facc);
#pragma unroll
      for (int i = 0; i < 32; i++) xs[i] = pack_bf16(fmaf(facc[2 * i], gf[2 * i], rf[2 * i]), fmaf(facc[2 * i + 1], gf[2 * i + 1], rf[2 * i + 1]));
      __syncwarp();
      stage_chunks<2>(xa + c.warp * 2048, 16384, xs);
      fence_async_smem();
      __syncwarp();
      if (elect_one()) {
        const int col = (fin & 3) * 256 + (own ? 128 : 0), row = (((fin >> 5) & 31) * 2 + rank) * 128 + c.warp * 16;
        tma_store_2d(&p.tm[TS_OUT], xa + c.warp * 2048, col, row);
        tma_store_2d(&p.tm[TS_OUT], xa + c.warp * 2048 + 16384, col + 64, row);
        bulk_commit();
        mbar_arrive(bars + B_STG);
        bulk_wait_read<0>();
      }
    }
    __syncwarp();
    cluster_sync_relaxed();
  }
}

typedef CUresult (*PFN_encodeTiled)(CUtensorMap*, CUtensorMapDataType, cuuint32_t, void*, const cuuint64_t*, const cuuint64_t*, const cuuint32_t*, const cuuint32_t*,
                                    CUtensorMapInterleave, CUtensorMapSwizzle, CUtensorMapL2promotion, CUtensorMapFloatOOBfill);
static PFN_encodeTiled s_encode = nullptr;
static void tm_2d(CUtensorMap* tm, const void* ptr, uint64_t rows, uint64_t cols, uint32_t box_rows) {
  cuuint64_t dims[2] = {cols, rows}; cuuint64_t strides[1] = {cols * 2}; cuuint32_t box[2] = {64, box_rows}; cuuint32_t es[2] = {1, 1};
  CUresult r = s_encode(tm, CU_TENSOR_MAP_DATA_TYPE_BFLOAT16, 2, (void*)ptr, dims, strides, box, es, CU_TENSOR_MAP_INTERLEAVE_NONE,
                        CU_TENSOR_MAP_SWIZZLE_128B, CU_TENSOR_MAP_L2_PROMOTION_L2_128B, CU_TENSOR_MAP_FLOAT_OOB_FILL_NONE);
  if (r != CUDA_SUCCESS) fprintf(stderr, "tensor map encode failed (%d)\n", (int)r);
}
static void tm_3d(CUtensorMap* tm, const void* ptr, uint64_t rows, uint64_t cols) {
  cuuint64_t dims[3] = {64, rows, cols / 64}; cuuint64_t strides[2] = {cols * 2, 128}; cuuint32_t box[3] = {64, 64, 2}; cuuint32_t es[3] = {1, 1, 1};
  CUresult r = s_encode(tm, CU_TENSOR_MAP_DATA_TYPE_BFLOAT16, 3, (void*)ptr, dims, strides, box, es, CU_TENSOR_MAP_INTERLEAVE_NONE,
                        CU_TENSOR_MAP_SWIZZLE_128B, CU_TENSOR_MAP_L2_PROMOTION_L2_128B, CU_TENSOR_MAP_FLOAT_OOB_FILL_NONE);
  if (r != CUDA_SUCCESS) fprintf(stderr, "tensor map encode failed (%d)\n", (int)r);
}
static inline uint16_t mk(int type, int a, int b) { return (uint16_t)(type << 12 | a << 5 | b); }

static void build_schedule(Params& P) {
  int cnt[NCLUSTER];
  for (int c = 0; c < NCLUSTER; c++) { cnt[c] = 0; for (int i = 0; i < MAXI; i++) P.items[c][i] = mk(T_END, 0, 0); }
  auto phys = [](int c) { return c == 64 ? 9 : c == 65 ? 17 : c == 9 ? 64 : c == 17 ? 65 : c; };
  auto push = [&](int c, uint16_t v) { P.items[phys(c)][cnt[c]++] = v; };
  int natt[NCLUSTER], nq[NCLUSTER];
  for (int c = 0; c < NCLUSTER; c++) { natt[c] = c < 32 ? 3 : (c < 56 ? 5 : (c < 62 ? 4 : (c < 64 ? 3 : 5))); nq[c] = c < 56 ? 1 : (c < 62 ? 7 : (c < 64 ? 9 : 6)); }
  for (int c = 0; c < 56; c++) push(c, mk(T_Z2, c % 8, c / 8));
  int qi = 0;
  for (int slot = 0; slot < 9; slot++)
    for (int c = NCLUSTER - 1; c >= 0; c--) {
      const int first = c < 56 ? 1 : 0;
      if (slot >= first && slot < first + nq[c]) { push(c, mk(T_Q, qi % 8, qi / 8)); qi++; }
    }
  for (int c = 0; c < 56; c++) push(c, mk(T_U, c % 8, c / 8));
  int ai = 0;
  for (int slot = 0; slot < 5; slot++)
    for (int c = 0; c < NCLUSTER; c++) {
      const int first = c < 32 ? 0 : 5 - natt[c];
      if (slot >= first && slot < first + natt[c]) { push(c, mk(T_ATT, ai / 8, ai % 8) | (natt[c] - 3) << 10); ai++; }
    }
  for (int c = 0; c < 32; c++) push(c, mk(T_SA, c % 8, c / 8));
  for (int c = 0; c < 64; c++) push(c, mk(T_FIN, c % 8, (c / 8) % 4 | (c < 32 ? 4 : 0)));
  if (qi != 128 || ai != 256) fprintf(stderr, "bad schedule %d %d\n", qi, ai);
}

static Params s_params;
extern "C" void kernel_launch(void* const* d_in, const int* in_sizes, int n_in, void* d_out, int out_size) {
  (void)in_sizes; (void)n_in; (void)out_size;
  if (!s_encode) {
    void* fn = nullptr; cudaDriverEntryPointQueryResult qr;
    cudaGetDriverEntryPoint("cuTensorMapEncodeTiled", &fn, cudaEnableDefault, &qr);
    s_encode = (PFN_encodeTiled)fn;
    cudaFuncSetAttribute(fused_kernel, cudaFuncAttributeMaxDynamicSharedMemorySize, SMEM_BYTES);
    build_schedule(s_params);
  }
  Params& P = s_params;
  void *xn, *q, *o, *z2, *u, *gg, *sa;
  cudaGetSymbolAddress(&gg, g_g); cudaGetSymbolAddress(&sa, g_sa);
  cudaGetSymbolAddress(&xn, g_xn); cudaGetSymbolAddress(&q, g_q); cudaGetSymbolAddress(&o, g_o);
  cudaGetSymbolAddress(&z2, g_z2); cudaGetSymbolAddress(&u, g_u);
  tm_2d(&P.tm[TM_XN], xn, SEQ, DM, 128); tm_2d(&P.tm[TM_WSP], d_in[7], SEQ, SEQ, 128); tm_2d(&P.tm[TM_U], u, SEQ, FH, 128);
  tm_2d(&P.tm[TM_O], o, SEQ, HD, 128); tm_2d(&P.tm[TM_Q], q, SEQ, HD, 128); tm_2d(&P.tm[TM_X], d_in[0], SEQ, DM, 128);
  tm_2d(&P.tm[TM_K], d_in[1], NH * SEQ, 128, 128); tm_2d(&P.tm[TM_V], d_in[2], NH * SEQ, 128, 128);
  tm_2d(&P.tm[TM_SA], sa, SEQ, DM, 128); tm_2d(&P.tm[TM_G], gg, SEQ, DM, 128); tm_2d(&P.tm[TM_WO64], d_in[4], HD, DM, 64);
  tm_3d(&P.tm[TM_WIN], d_in[6], DM, FF); tm_3d(&P.tm[TM_WQ], d_in[3], DM, HD); tm_3d(&P.tm[TM_Z2], z2, SEQ, FH);
  tm_3d(&P.tm[TM_WOUT], d_in[9], FH, DM); tm_3d(&P.tm[TM_WO], d_in[4], HD, DM);
  tm_2d(&P.tm[TS_Q], q, SEQ, HD, ST_ROWS); tm_2d(&P.tm[TS_O], o, SEQ, HD, ST_ROWS); tm_2d(&P.tm[TS_Z2], z2, SEQ, FH, ST_ROWS); tm_2d(&P.tm[TS_U], u, SEQ, FH, ST_ROWS);
  tm_2d(&P.tm[TS_SA], sa, SEQ, DM, ST_ROWS); tm_2d(&P.tm[TS_G], gg, SEQ, DM, ST_ROWS); tm_2d(&P.tm[TS_OUT], d_out, SEQ, DM, 16);
  P.x = (const bf16*)d_in[0]; P.b_sp = (const bf16*)d_in[8];
  fused_kernel<<<2 * NCLUSTER, 384, SMEM_BYTES, cudaStreamPerThread>>>(P);
}
```

```cpp
#include <cuda_runtime.h>
#include <cuda_bf16.h>
#include <cuda.h>
#include <stdint.h>
#include <stdio.h>

typedef __nv_bfloat16 bf16;

constexpr int SEQ = 2048, DM = 1024, NH = 32, HD = 4096, FF = 3584, FH = 1792;

__device__ __align__(1024) bf16 g_xn[SEQ * DM];
__device__ __align__(1024) bf16 g_q[SEQ * HD];
__device__ __align__(1024) bf16 g_o[SEQ * HD];
__device__ __align__(1024) bf16 g_z2[SEQ * FH];
__device__ __align__(1024) bf16 g_u[SEQ * FH];
__device__ __align__(1024) uint2 g_stats[SEQ * 8];
__device__ __align__(1024) bf16 g_g[SEQ * DM];
__device__ __align__(1024) bf16 g_sa[SEQ * DM];
constexpr int F_XN = 0;
constexpr int F_Z2 = 512;
constexpr int F_Q = 768;
constexpr int F_U = 1024;
constexpr int F_O = 1536;
constexpr int F_S = 2048;
constexpr int F_TOTAL = 2112;
__device__ __align__(1024) unsigned g_flags[F_TOTAL];
__device__ unsigned g_done;
__device__ unsigned g_epoch;

__device__ __forceinline__ uint32_t smem_u32(const void* p) { return (uint32_t)__cvta_generic_to_shared(p); }
__device__ __forceinline__ void mbar_init(uint32_t bar, uint32_t cnt) { asm volatile("mbarrier.init.shared::cta.b64 [%0], %1;" :: "r"(bar), "r"(cnt)); }
__device__ __forceinline__ void mbar_expect_tx(uint32_t bar, uint32_t bytes) { asm volatile("mbarrier.arrive.expect_tx.shared::cta.b64 _, [%0], %1;" :: "r"(bar), "r"(bytes) : "memory"); }
__device__ __forceinline__ void mbar_arrive(uint32_t bar) { asm volatile("mbarrier.arrive.shared::cta.b64 _, [%0];" :: "r"(bar) : "memory"); }
__device__ __forceinline__ void mbar_arrive_cta(uint32_t bar, uint32_t cta) {
  asm volatile("{\n.reg .b32 ra;\nmapa.shared::cluster.u32 ra, %0, %1;\nmbarrier.arrive.shared::cluster.b64 _, [ra];\n}" :: "r"(bar), "r"(cta) : "memory");
}
__device__ __forceinline__ bool mbar_test(uint32_t bar, uint32_t parity) {
  uint32_t ok;
  asm volatile("{\n.reg .pred P1;\nmbarrier.test_wait.parity.shared::cta.b64 P1, [%1], %2;\nselp.u32 %0, 1, 0, P1;\n}" : "=r"(ok) : "r"(bar), "r"(parity) : "memory");
  return ok;
}
constexpr uint32_t SPIN_LIMIT = 1u << 22;
__device__ __forceinline__ void trap_if(bool c) { asm volatile("{\n.reg .pred P;\nsetp.ne.u32 P, %0, 0;\n@P trap;\n}" :: "r"((uint32_t)c)); }
__device__ __forceinline__ void mbar_wait(uint32_t bar, uint32_t parity) {
  asm volatile("{\n.reg .pred P1;\n.reg .u32 n;\nmbarrier.try_wait.parity.shared::cta.b64 P1, [%0], %1;\n@P1 bra DONE;\nmov.u32 n, 0;\n"
               "LOOP:\nmbarrier.try_wait.parity.shared::cta.b64 P1, [%0], %1;\n@P1 bra DONE;\nadd.u32 n, n, 1;\nsetp.gt.u32 P1, n, %2;\n@P1 trap;\nbra LOOP;\nDONE:\n}"
               :: "r"(bar), "r"(parity), "n"(SPIN_LIMIT) : "memory");
}
__device__ __forceinline__ void mbar_spin(uint32_t bar, uint32_t parity) {
  asm volatile("{\n.reg .pred P1;\nLOOP:\nmbarrier.try_wait.parity.shared::cta.b64 P1, [%0], %1;\n@!P1 bra LOOP;\n}" :: "r"(bar), "r"(parity) : "memory");
}
__device__ __forceinline__ void mbar_wait_sleep(uint32_t bar, uint32_t parity, uint32_t ns) {
  uint32_t n = 0;
  while (!mbar_test(bar, parity)) { trap_if(++n > SPIN_LIMIT * 4); __nanosleep(ns); }
}
__device__ __forceinline__ void tma_load_2d(uint32_t dst, const CUtensorMap* tm, int c0, int c1, uint32_t bar) {
  asm volatile("cp.async.bulk.tensor.2d.shared::cluster.global.mbarrier::complete_tx::bytes [%0], [%1, {%3, %4}], [%2];"
    :: "r"(dst), "l"(tm), "r"(bar), "r"(c0), "r"(c1) : "memory");
}
__device__ __forceinline__ void tma_load_2d_mc(uint32_t dst, const CUtensorMap* tm, int c0, int c1, uint32_t bar) {
  asm volatile("cp.async.bulk.tensor.2d.shared::cluster.global.mbarrier::complete_tx::bytes.multicast::cluster [%0], [%1, {%3, %4}], [%2], %5;"
    :: "r"(dst), "l"(tm), "r"(bar), "r"(c0), "r"(c1), "h"((uint16_t)3) : "memory");
}
__device__ __forceinline__ void tma_prefetch_2d(const CUtensorMap* tm, int c0, int c1) {
  asm volatile("cp.async.bulk.prefetch.tensor.2d.L2.global [%0, {%1, %2}];" :: "l"(tm), "r"(c0), "r"(c1) : "memory");
}
__device__ __forceinline__ void tma_prefetch_3d(const CUtensorMap* tm, int c1, int c2) {
  asm volatile("cp.async.bulk.prefetch.tensor.3d.L2.global [%0, {%1, %2, %3}];" :: "l"(tm), "r"(0), "r"(c1), "r"(c2) : "memory");
}
__device__ __forceinline__ void tma_load_3d_mc(uint32_t dst, const CUtensorMap* tm, int c1, int c2, uint32_t bar) {
  asm volatile("cp.async.bulk.tensor.3d.shared::cluster.global.mbarrier::complete_tx::bytes.multicast::cluster [%0], [%1, {%3, %4, %5}], [%2], %6;"
    :: "r"(dst), "l"(tm), "r"(bar), "r"(0), "r"(c1), "r"(c2), "h"((uint16_t)3) : "memory");
}
__device__ __forceinline__ void tma_store_2d(const CUtensorMap* tm, uint32_t src, int c0, int c1) {
  asm volatile("cp.async.bulk.tensor.2d.global.shared::cta.bulk_group [%0, {%2, %3}], [%1];" :: "l"(tm), "r"(src), "r"(c0), "r"(c1) : "memory");
}
__device__ __forceinline__ void bulk_commit() { asm volatile("cp.async.bulk.commit_group;" ::: "memory"); }
template <int N> __device__ __forceinline__ void bulk_wait_read() { asm volatile("cp.async.bulk.wait_group.read %0;" :: "n"(N) : "memory"); }
template <int N> __device__ __forceinline__ void bulk_wait() { asm volatile("cp.async.bulk.wait_group %0;" :: "n"(N) : "memory"); }
__device__ __forceinline__ void fence_async_smem() { asm volatile("fence.proxy.async.shared::cta;" ::: "memory"); }
__device__ __forceinline__ void fence_async_global() { asm volatile("fence.proxy.async.global;" ::: "memory"); }
__device__ __forceinline__ void wgmma_fence() { asm volatile("wgmma.fence.sync.aligned;" ::: "memory"); }
__device__ __forceinline__ void wgmma_commit() { asm volatile("wgmma.commit_group.sync.aligned;" ::: "memory"); }
template <int N> __device__ __forceinline__ void wgmma_wait() { asm volatile("wgmma.wait_group.sync.aligned %0;" :: "n"(N) : "memory"); }
__device__ __forceinline__ uint64_t make_desc(uint32_t addr, uint32_t lbo, uint32_t sbo) {
  return (uint64_t)((addr & 0x3FFFF) >> 4) | ((uint64_t)(lbo >> 4) << 16) | ((uint64_t)(sbo >> 4) << 32) | (1ull << 62);
}
template <int N> __device__ __forceinline__ void fence_regs(float (&d)[N]) {
#pragma unroll
  for (int i = 0; i < N; i++) asm volatile("" : "+f"(d[i]) :: "memory");
}
template <int N> __device__ __forceinline__ void fence_regs(uint32_t (&d)[N]) {
#pragma unroll
  for (int i = 0; i < N; i++) asm volatile("" : "+r"(d[i]) :: "memory");
}
__device__ __forceinline__ void named_sync(int id) { asm volatile("bar.sync %0, 256;" :: "r"(id) : "memory"); }
__device__ __forceinline__ bool wg_any(bool w, bool v) {
  uint32_t r;
  asm volatile("{\n.reg .pred p, q;\nsetp.ne.u32 p, %1, 0;\nbar.red.or.pred q, %2, 128, p;\nselp.u32 %0, 1, 0, q;\n}" : "=r"(r) : "r"((uint32_t)v), "r"(w ? 4 : 3) : "memory");
  return __any_sync(0xffffffffu, r);
}
__device__ __forceinline__ int fresh_warp() { uint32_t t; asm volatile("mov.u32 %0, %%tid.x;" : "=r"(t)); return __shfl_sync(0xffffffffu, (int)(t >> 5) - 4, 0); }
__device__ __forceinline__ void cluster_sync_relaxed() { asm volatile("barrier.cluster.arrive.relaxed.aligned;\nbarrier.cluster.wait.aligned;" ::: "memory"); }
__device__ __forceinline__ unsigned ld_acquire(const unsigned* p) { unsigned v; asm volatile("ld.acquire.gpu.global.u32 %0, [%1];" : "=r"(v) : "l"(p) : "memory"); return v; }
__device__ __forceinline__ void red_release(unsigned* p, unsigned v) { asm volatile("red.release.gpu.global.add.u32 [%0], %1;" :: "l"(p), "r"(v) : "memory"); }
__device__ __forceinline__ void flag_wait(const unsigned* p, unsigned target) {
  uint32_t n = 0;
  while (ld_acquire(p) < target) { trap_if(++n > SPIN_LIMIT); __nanosleep(20); }
}
__device__ __forceinline__ void st_tagged(uint2* p, float a, float b, uint32_t tag) {
  asm volatile("{\n.reg .b64 x;\nmov.b64 x, {%1, %2};\nst.relaxed.gpu.global.b64 [%0], x;\n}" :: "l"(p),
               "r"((__float_as_uint(a) & ~63u) | (tag & 63u)), "r"((__float_as_uint(b) & ~63u) | (tag >> 6)) : "memory");
}
__device__ __forceinline__ uint4 ld_tagged2(const uint2* p) {
  uint4 v;
  asm volatile("{\n.reg .b64 x, y;\nld.relaxed.gpu.global.v2.b64 {x, y}, [%4];\nmov.b64 {%0, %1}, x;\nmov.b64 {%2, %3}, y;\n}" : "=r"(v.x), "=r"(v.y), "=r"(v.z), "=r"(v.w) : "l"(p) : "memory");
  return v;
}
__device__ __forceinline__ bool tag_ok(uint32_t a, uint32_t b, uint32_t tag) { return ((a & 63u) | ((b & 63u) << 6)) == tag; }
__device__ __forceinline__ float untag(uint32_t v) { return __uint_as_float(v & ~63u); }
__device__ __forceinline__ uint32_t pack_bf16(float lo, float hi) { uint32_t r; asm("cvt.rn.bf16x2.f32 %0, %1, %2;" : "=r"(r) : "f"(hi), "f"(lo)); return r; }
__device__ __forceinline__ uint32_t bf2_fma(uint32_t a, uint32_t b, uint32_t c) { uint32_t r; asm("fma.rn.bf16x2 %0, %1, %2, %3;" : "=r"(r) : "r"(a), "r"(b), "r"(c)); return r; }
__device__ __forceinline__ uint32_t bf2_mul(uint32_t a, uint32_t b) { uint32_t r; asm("mul.rn.bf16x2 %0, %1, %2;" : "=r"(r) : "r"(a), "r"(b)); return r; }
__device__ __forceinline__ uint32_t bf2_add(uint32_t a, uint32_t b) { uint32_t r; asm("add.rn.bf16x2 %0, %1, %2;" : "=r"(r) : "r"(a), "r"(b)); return r; }
constexpr uint32_t BF2_HALF = 0x3f003f00u;
__device__ __forceinline__ float bf_lo(uint32_t v) { return __uint_as_float(v << 16); }
__device__ __forceinline__ float bf_hi(uint32_t v) { return __uint_as_float(v & 0xffff0000u); }
__device__ __forceinline__ float ex2(float x) { float y; asm("ex2.approx.ftz.f32 %0, %1;" : "=f"(y) : "f"(x)); return y; }
__device__ __forceinline__ float tanh_fast(float x) { float y; asm("tanh.approx.f32 %0, %1;" : "=f"(y) : "f"(x)); return y; }
__device__ __forceinline__ void stmatrix_x4(uint32_t addr, uint32_t a, uint32_t b, uint32_t c, uint32_t d) {
  asm volatile("stmatrix.sync.aligned.m8n8.x4.shared.b16 [%0], {%1, %2, %3, %4};" :: "r"(addr), "r"(a), "r"(b), "r"(c), "r"(d) : "memory");
}
__device__ __forceinline__ void ldmatrix_x4(uint32_t addr, uint32_t& a, uint32_t& b, uint32_t& c, uint32_t& d) {
  asm volatile("ldmatrix.sync.aligned.m8n8.x4.shared.b16 {%0, %1, %2, %3}, [%4];" : "=r"(a), "=r"(b), "=r"(c), "=r"(d) : "r"(addr) : "memory");
}
__device__ __forceinline__ uint32_t lane_id() { uint32_t l; asm volatile("mov.u32 %0, %%laneid;" : "=r"(l)); return l; }
__device__ __forceinline__ bool elect_one() {
  uint32_t r;
  asm volatile("{\n.reg .pred P;\nelect.sync _|P, 0xffffffff;\nselp.u32 %0, 1, 0, P;\n}" : "=r"(r));
  return r;
}

__device__ __forceinline__ void wgmma_m64n128k16_ss_tb0(float (&d)[64], uint64_t da, uint64_t db, int scale_d) {
  asm volatile("{\n.reg .pred p;\nsetp.ne.b32 p, %66, 0;\n"
    "wgmma.mma_async.sync.aligned.m64n128k16.f32.bf16.bf16 "
    "{%0, %1, %2, %3, %4, %5, %6, %7, %8, %9, %10, %11, %12, %13, %14, %15, %16, %17, %18, %19, %20, %21, %22, %23, %24, %25, %26, %27, %28, %29, %30, %31, %32, %33, %34, %35, %36, %37, %38, %39, %40, %41, %42, %43, %44, %45, %46, %47, %48, %49, %50, %51, %52, %53, %54, %55, %56, %57, %58, %59, %60, %61, %62, %63}, "
    "%64, %65, p, 1, 1, 0, 0;\n}\n"
    : "+f"(d[0]), "+f"(d[1]), "+f"(d[2]), "+f"(d[3]), "+f"(d[4]), "+f"(d[5]), "+f"(d[6]), "+f"(d[7]), "+f"(d[8]), "+f"(d[9]), "+f"(d[10]), "+f"(d[11]), "+f"(d[12]), "+f"(d[13]), "+f"(d[14]), "+f"(d[15]), "+f"(d[16]), "+f"(d[17]), "+f"(d[18]), "+f"(d[19]), "+f"(d[20]), "+f"(d[21]), "+f"(d[22]), "+f"(d[23]), "+f"(d[24]), "+f"(d[25]), "+f"(d[26]), "+f"(d[27]), "+f"(d[28]), "+f"(d[29]), "+f"(d[30]), "+f"(d[31]), "+f"(d[32]), "+f"(d[33]), "+f"(d[34]), "+f"(d[35]), "+f"(d[36]), "+f"(d[37]), "+f"(d[38]), "+f"(d[39]), "+f"(d[40]), "+f"(d[41]), "+f"(d[42]), "+f"(d[43]), "+f"(d[44]), "+f"(d[45]), "+f"(d[46]), "+f"(d[47]), "+f"(d[48]), "+f"(d[49]), "+f"(d[50]), "+f"(d[51]), "+f"(d[52]), "+f"(d[53]), "+f"(d[54]), "+f"(d[55]), "+f"(d[56]), "+f"(d[57]), "+f"(d[58]), "+f"(d[59]), "+f"(d[60]), "+f"(d[61]), "+f"(d[62]), "+f"(d[63])
    : "l"(da), "l"(db), "r"(scale_d));
}
__device__ __forceinline__ void wgmma_m64n256k16_ss_tb1(float (&d)[128], uint64_t da, uint64_t db, int scale_d) {
  asm volatile("{\n.reg .pred p;\nsetp.ne.b32 p, %130, 0;\n"
    "wgmma.mma_async.sync.aligned.m64n256k16.f32.bf16.bf16 "
    "{%0, %1, %2, %3, %4, %5, %6, %7, %8, %9, %10, %11, %12, %13, %14, %15, %16, %17, %18, %19, %20, %21, %22, %23, %24, %25, %26, %27, %28, %29, %30, %31, %32, %33, %34, %35, %36, %37, %38, %39, %40, %41, %42, %43, %44, %45, %46, %47, %48, %49, %50, %51, %52, %53, %54, %55, %56, %57, %58, %59, %60, %61, %62, %63, %64, %65, %66, %67, %68, %69, %70, %71, %72, %73, %74, %75, %76, %77, %78, %79, %80, %81, %82, %83, %84, %85, %86, %87, %88, %89, %90, %91, %92, %93, %94, %95, %96, %97, %98, %99, %100, %101, %102, %103, %104, %105, %106, %107, %108, %109, %110, %111, %112, %113, %114, %115, %116, %117, %118, %119, %120, %121, %122, %123, %124, %125, %126, %127}, "
    "%128, %129, p, 1, 1, 0, 1;\n}\n"
    : "+f"(d[0]), "+f"(d[1]), "+f"(d[2]), "+f"(d[3]), "+f"(d[4]), "+f"(d[5]), "+f"(d[6]), "+f"(d[7]), "+f"(d[8]), "+f"(d[9]), "+f"(d[10]), "+f"(d[11]), "+f"(d[12]), "+f"(d[13]), "+f"(d[14]), "+f"(d[15]), "+f"(d[16]), "+f"(d[17]), "+f"(d[18]), "+f"(d[19]), "+f"(d[20]), "+f"(d[21]), "+f"(d[22]), "+f"(d[23]), "+f"(d[24]), "+f"(d[25]), "+f"(d[26]), "+f"(d[27]), "+f"(d[28]), "+f"(d[29]), "+f"(d[30]), "+f"(d[31]), "+f"(d[32]), "+f"(d[33]), "+f"(d[34]), "+f"(d[35]), "+f"(d[36]), "+f"(d[37]), "+f"(d[38]), "+f"(d[39]), "+f"(d[40]), "+f"(d[41]), "+f"(d[42]), "+f"(d[43]), "+f"(d[44]), "+f"(d[45]), "+f"(d[46]), "+f"(d[47]), "+f"(d[48]), "+f"(d[49]), "+f"(d[50]), "+f"(d[51]), "+f"(d[52]), "+f"(d[53]), "+f"(d[54]), "+f"(d[55]), "+f"(d[56]), "+f"(d[57]), "+f"(d[58]), "+f"(d[59]), "+f"(d[60]), "+f"(d[61]), "+f"(d[62]), "+f"(d[63]), "+f"(d[64]), "+f"(d[65]), "+f"(d[66]), "+f"(d[67]), "+f"(d[68]), "+f"(d[69]), "+f"(d[70]), "+f"(d[71]), "+f"(d[72]), "+f"(d[73]), "+f"(d[74]), "+f"(d[75]), "+f"(d[76]), "+f"(d[77]), "+f"(d[78]), "+f"(d[79]), "+f"(d[80]), "+f"(d[81]), "+f"(d[82]), "+f"(d[83]), "+f"(d[84]), "+f"(d[85]), "+f"(d[86]), "+f"(d[87]), "+f"(d[88]), "+f"(d[89]), "+f"(d[90]), "+f"(d[91]), "+f"(d[92]), "+f"(d[93]), "+f"(d[94]), "+f"(d[95]), "+f"(d[96]), "+f"(d[97]), "+f"(d[98]), "+f"(d[99]), "+f"(d[100]), "+f"(d[101]), "+f"(d[102]), "+f"(d[103]), "+f"(d[104]), "+f"(d[105]), "+f"(d[106]), "+f"(d[107]), "+f"(d[108]), "+f"(d[109]), "+f"(d[110]), "+f"(d[111]), "+f"(d[112]), "+f"(d[113]), "+f"(d[114]), "+f"(d[115]), "+f"(d[116]), "+f"(d[117]), "+f"(d[118]), "+f"(d[119]), "+f"(d[120]), "+f"(d[121]), "+f"(d[122]), "+f"(d[123]), "+f"(d[124]), "+f"(d[125]), "+f"(d[126]), "+f"(d[127])
    : "l"(da), "l"(db), "r"(scale_d));
}
__device__ __forceinline__ void wgmma_m64n128k16_rs_tb1(float (&d)[64], uint32_t a0, uint32_t a1, uint32_t a2, uint32_t a3, uint64_t db, int scale_d) {
  asm volatile("{\n.reg .pred p;\nsetp.ne.b32 p, %69, 0;\n"
    "wgmma.mma_async.sync.aligned.m64n128k16.f32.bf16.bf16 "
    "{%0, %1, %2, %3, %4, %5, %6, %7, %8, %9, %10, %11, %12, %13, %14, %15, %16, %17, %18, %19, %20, %21, %22, %23, %24, %25, %26, %27, %28, %29, %30, %31, %32, %33, %34, %35, %36, %37, %38, %39, %40, %41, %42, %43, %44, %45, %46, %47, %48, %49, %50, %51, %52, %53, %54, %55, %56, %57, %58, %59, %60, %61, %62, %63}, "
    "{%64, %65, %66, %67}, %68, p, 1, 1, 1;\n}\n"
    : "+f"(d[0]), "+f"(d[1]), "+f"(d[2]), "+f"(d[3]), "+f"(d[4]), "+f"(d[5]), "+f"(d[6]), "+f"(d[7]), "+f"(d[8]), "+f"(d[9]), "+f"(d[10]), "+f"(d[11]), "+f"(d[12]), "+f"(d[13]), "+f"(d[14]), "+f"(d[15]), "+f"(d[16]), "+f"(d[17]), "+f"(d[18]), "+f"(d[19]), "+f"(d[20]), "+f"(d[21]), "+f"(d[22]), "+f"(d[23]), "+f"(d[24]), "+f"(d[25]), "+f"(d[26]), "+f"(d[27]), "+f"(d[28]), "+f"(d[29]), "+f"(d[30]), "+f"(d[31]), "+f"(d[32]), "+f"(d[33]), "+f"(d[34]), "+f"(d[35]), "+f"(d[36]), "+f"(d[37]), "+f"(d[38]), "+f"(d[39]), "+f"(d[40]), "+f"(d[41]), "+f"(d[42]), "+f"(d[43]), "+f"(d[44]), "+f"(d[45]), "+f"(d[46]), "+f"(d[47]), "+f"(d[48]), "+f"(d[49]), "+f"(d[50]), "+f"(d[51]), "+f"(d[52]), "+f"(d[53]), "+f"(d[54]), "+f"(d[55]), "+f"(d[56]), "+f"(d[57]), "+f"(d[58]), "+f"(d[59]), "+f"(d[60]), "+f"(d[61]), "+f"(d[62]), "+f"(d[63])
    : "r"(a0), "r"(a1), "r"(a2), "r"(a3), "l"(db), "r"(scale_d));
}
__device__ __forceinline__ void wgmma_m64n128k16_ss_tb1(float (&d)[64], uint64_t da, uint64_t db, int scale_d) {
  asm volatile("{\n.reg .pred p;\nsetp.ne.b32 p, %66, 0;\n"
    "wgmma.mma_async.sync.aligned.m64n128k16.f32.bf16.bf16 "
    "{%0, %1, %2, %3, %4, %5, %6, %7, %8, %9, %10, %11, %12, %13, %14, %15, %16, %17, %18, %19, %20, %21, %22, %23, %24, %25, %26, %27, %28, %29, %30, %31, %32, %33, %34, %35, %36, %37, %38, %39, %40, %41, %42, %43, %44, %45, %46, %47, %48, %49, %50, %51, %52, %53, %54, %55, %56, %57, %58, %59, %60, %61, %62, %63}, "
    "%64, %65, p, 1, 1, 0, 1;\n}\n"
    : "+f"(d[0]), "+f"(d[1]), "+f"(d[2]), "+f"(d[3]), "+f"(d[4]), "+f"(d[5]), "+f"(d[6]), "+f"(d[7]), "+f"(d[8]), "+f"(d[9]), "+f"(d[10]), "+f"(d[11]), "+f"(d[12]), "+f"(d[13]), "+f"(d[14]), "+f"(d[15]), "+f"(d[16]), "+f"(d[17]), "+f"(d[18]), "+f"(d[19]), "+f"(d[20]), "+f"(d[21]), "+f"(d[22]), "+f"(d[23]), "+f"(d[24]), "+f"(d[25]), "+f"(d[26]), "+f"(d[27]), "+f"(d[28]), "+f"(d[29]), "+f"(d[30]), "+f"(d[31]), "+f"(d[32]), "+f"(d[33]), "+f"(d[34]), "+f"(d[35]), "+f"(d[36]), "+f"(d[37]), "+f"(d[38]), "+f"(d[39]), "+f"(d[40]), "+f"(d[41]), "+f"(d[42]), "+f"(d[43]), "+f"(d[44]), "+f"(d[45]), "+f"(d[46]), "+f"(d[47]), "+f"(d[48]), "+f"(d[49]), "+f"(d[50]), "+f"(d[51]), "+f"(d[52]), "+f"(d[53]), "+f"(d[54]), "+f"(d[55]), "+f"(d[56]), "+f"(d[57]), "+f"(d[58]), "+f"(d[59]), "+f"(d[60]), "+f"(d[61]), "+f"(d[62]), "+f"(d[63])
    : "l"(da), "l"(db), "r"(scale_d));
}


enum { TM_XN, TM_WSP, TM_U, TM_O, TM_Q, TM_X, TM_SA, TM_G, TM_K, TM_V, TM_WO64,
       TM_WIN, TM_WQ, TM_Z2, TM_WOUT, TM_WO, TS_Q, TS_O, TS_Z2, TS_U, TS_SA, TS_G, TS_OUT, TM_COUNT };
enum { T_Z2 = 0, T_Q = 1, T_U = 2, T_ATT = 3, T_SA = 4, T_FIN = 5, T_END = 7 };
constexpr int NCLUSTER = 66, MAXI = 14;
struct alignas(64) Params {
  const bf16* x;
  const bf16* b_sp;
  CUtensorMap tm[TM_COUNT];
  uint16_t items[NCLUSTER][MAXI];
};

constexpr uint32_t G_STAGE = 49152, G_A = 16384, KV_SLOT = 32768;
constexpr uint32_t OFF_Q1 = 163840, OFF_Q0 = 196608, OFF_BAR = 229376, OFF_LN = OFF_BAR + 256, SMEM_BYTES = OFF_LN + 1024;
constexpr uint32_t B_GF = 0, B_GE = 32, B_KF = 64, B_KE = 104, B_QF = 144, B_QE = 160, B_XF = 176, B_XR = 184, B_STG = 192, B_FREE = 200, B_GO = 208, B_LN = 216, B_TAG = 224, B_RDY = 228, B_PROG = 232, B_PUB = 248;
constexpr int SA_HEADS = 18;
constexpr int SW_NS = 40;
constexpr int ST_ROWS = 16;
constexpr int ST_FLY = 2;
constexpr int KV_PF = 4;
constexpr int FIN_PREP = 8;
constexpr int OWN_OFF = 8;
constexpr int Z_DELAY = 3;
constexpr int SW_ATT = 800;
constexpr int OUT_PF = 8;
constexpr uint32_t OFF_ZQ = 2 * G_STAGE + G_A;
constexpr uint32_t FIN_SLOT0 = (0x0320u >> (4 * ((29 + 2 * SA_HEADS) & 3))) & 15;
constexpr float SM_C = 0.08838834764831845f * 1.4426950408889634f;
constexpr float GELU_A = 0.7978845608028654f, GELU_B = 0.7978845608028654f * 0.044715f;
constexpr float SM_LO = 1e-7f, SM_HI = 1e12f;
constexpr float SM_THR = 1024.f;


extern __shared__ __align__(1024) uint8_t smem_raw[];
__device__ __forceinline__ uint32_t smem_base() { return smem_u32(smem_raw); }

struct Ring { uint32_t s, ph; };
template <int N> __device__ __forceinline__ void ring_adv(Ring& r) { if (++r.s == N) { r.s = 0; r.ph ^= 1; } }

__device__ __forceinline__ int get_item(const Params& p, int i) {
  uint32_t b; asm volatile("mov.u32 %0, %%ctaid.x;" : "=r"(b));
  return p.items[b >> 1][i];
}
struct Cons {
  uint32_t sb;
  int warp;
  Ring g;
  uint32_t rot;
  uint32_t fph;
};

__device__ __forceinline__ void stage_acquire(const Cons& c) { mbar_spin(c.sb + OFF_BAR + B_FREE, c.fph); }
__device__ __forceinline__ void stage_commit(Cons& c) {
  __syncwarp();
  if (lane_id() == 0) mbar_arrive(c.sb + OFF_BAR + B_STG);
  c.fph ^= 1;
}

__device__ __forceinline__ void release_slot(const Cons& c, uint32_t bar) {
  if (lane_id() == 0 && (c.warp & 3) < 2) mbar_arrive_cta(bar, c.warp & 1);
}
constexpr uint64_t DESC_HI = (uint64_t)0x40000040u << 32;

template <bool FIRST> __device__ __forceinline__ void gemm_step(float (&acc)[128], Cons& c) {
  mbar_spin(c.sb + OFF_BAR + B_GF + 8 * c.g.s, c.g.ph);
  const uint32_t st = ((c.sb & 0x3FFFF) >> 4) + ((c.g.s + c.rot) & 3) * (G_STAGE >> 4);
  const uint32_t da = st + (c.warp >> 2) * 512 + (1u << 16), db = st + (G_A >> 4) + ((8192u >> 4) << 16);
  wgmma_fence();
#pragma unroll
  for (int kk = 0; kk < 4; kk++) wgmma_m64n256k16_ss_tb1(acc, DESC_HI | (da + kk * 2), DESC_HI | (db + kk * 128), !(FIRST && kk == 0));
  wgmma_commit();
}

template <int N> __device__ __forceinline__ void stage_chunks(uint32_t buf, uint32_t stride, const uint32_t* pk) {
  const uint32_t ln = lane_id();
  const uint32_t a = buf + ((ln & 15) << 7);
  const uint32_t x = ln & 7, hi = ln >> 4;
#pragma unroll
  for (int i = 0; i < 4 * N; i++) stmatrix_x4(a + (i >> 2) * stride + (((2 * (i & 3) + hi) ^ x) << 4), pk[4 * i], pk[4 * i + 1], pk[4 * i + 2], pk[4 * i + 3]);
}

__device__ __forceinline__ float act2_fn(float x, float a, float b) {
  return fmaf(x, tanh_fast(x * fmaf(x * x, b, a)), x);
}
__device__ __forceinline__ float quad_sum(float v) { v += __shfl_xor_sync(0xffffffffu, v, 1); v += __shfl_xor_sync(0xffffffffu, v, 2); return v; }
__device__ __forceinline__ float quad_max(float v) { v = fmaxf(v, __shfl_xor_sync(0xffffffffu, v, 1)); v = fmaxf(v, __shfl_xor_sync(0xffffffffu, v, 2)); return v; }

__device__ __forceinline__ uint32_t load_tag(const Cons& c) { uint32_t t; asm volatile("ld.volatile.shared.u32 %0, [%1];" : "=r"(t) : "r"(c.sb + OFF_BAR + B_TAG)); return t; }

struct Shadow {
  int act;
  int store;
};
__device__ __forceinline__ void rotate16(uint32_t (&h)[64]) {
#pragma unroll
  for (int i = 0; i < 16; i++)
    asm volatile("{\n.reg .b32 t;\nmov.b32 t, %0;\nmov.b32 %0, %1;\nmov.b32 %1, %2;\nmov.b32 %2, %3;\nmov.b32 %3, t;\n}" : "+r"(h[i]), "+r"(h[i + 16]), "+r"(h[i + 32]), "+r"(h[i + 48]));
}

template <int O>
__device__ __forceinline__ void act_block(uint32_t (&held)[64], float ca, float cb, bool first, float& u0, float& u1, float& s0, float& s1, float& q0, float& q1) {
#pragma unroll
  for (int i = O; i < O + 4; i += 2) {
    const float a0 = act2_fn(bf_lo(held[i]), ca, cb), a1 = act2_fn(bf_hi(held[i]), ca, cb);
    const float b0 = act2_fn(bf_lo(held[i + 1]), ca, cb), b1 = act2_fn(bf_hi(held[i + 1]), ca, cb);
    if (i == 0 && first) { u0 = a0; u1 = b0; }
    float d;
    d = a0 - u0; s0 += d; q0 = fmaf(d, d, q0); d = a1 - u0; s0 += d; q0 = fmaf(d, d, q0);
    d = b0 - u1; s1 += d; q1 = fmaf(d, d, q1); d = b1 - u1; s1 += d; q1 = fmaf(d, d, q1);
    held[i] = pack_bf16(a0, a1); held[i + 1] = pack_bf16(b0, b1);
  }
}

template <int O> __device__ __forceinline__ void stage_half(Cons& c, uint32_t (&held)[64], int mode) {
  if (mode == 2) {
    uint32_t a0, a1, r0, r1;
    const uint32_t la = c.sb + OFF_LN + (c.warp * 16 + (lane_id() >> 2)) * 8;
    mbar_spin(c.sb + OFF_BAR + B_LN, 0);
    asm volatile("ld.shared.v2.b32 {%0, %1}, [%2];" : "=r"(r0), "=r"(a0) : "r"(la));
    asm volatile("ld.shared.v2.b32 {%0, %1}, [%2];" : "=r"(r1), "=r"(a1) : "r"(la + 64));
#pragma unroll
    for (int i = O; i < O + 32; i += 2) { held[i] = bf2_mul(bf2_add(held[i], a0), r0); held[i + 1] = bf2_mul(bf2_add(held[i + 1], a1), r1); }
  }
  if (O == 0 && mode == 3) {
#pragma unroll
    for (int i = 0; i < 64; i++) held[i] = bf2_mul(held[i], BF2_HALF);
  }
  stage_acquire(c);
  stage_chunks<2>(c.sb + OFF_Q0 + c.warp * 2048, 16384, held + O);
  stage_commit(c);
}

__device__ __forceinline__ void gemm_seg(float (&acc)[128], uint32_t (&held)[64], Cons& c, const Params& p, Shadow& sh, int nsteps, bool hold) {
  const bool elected = lane_id() == 0 && (c.warp & 3) < 2;
  uint32_t rel;
  asm("mapa.shared::cluster.u32 %0, %1, %2;" : "=r"(rel) : "r"(c.sb + OFF_BAR + B_GE), "r"((uint32_t)(c.warp & 1)));
  gemm_step<true>(acc, c);
  uint32_t prev = c.g.s;
  ring_adv<4>(c.g);
  int k = 1;
#define G_STEP()                                                                                                       \
  { gemm_step<false>(acc, c);                                                                                          \
    wgmma_wait<1>();                                                                                                   \
    if (elected) asm volatile("mbarrier.arrive.shared::cluster.b64 _, [%0];" :: "r"(rel + 8 * prev) : "memory");       \
    prev = c.g.s; ring_adv<4>(c.g);                                                                                    \
    k++; }
  if (sh.act != 0) {
    float u0 = 0.f, u1 = 0.f, s0 = 0.f, s1 = 0.f, q0 = 0.f, q1 = 0.f;
    const float ca = sh.act == 3 ? 0.5f : GELU_A, cb = sh.act == 3 ? 0.f : GELU_B;
#pragma unroll 1
    while (true) {
      act_block<0>(held, ca, cb, k == 1, u0, u1, s0, s1, q0, q1);
      G_STEP()
      act_block<4>(held, ca, cb, false, u0, u1, s0, s1, q0, q1);
      G_STEP()
      act_block<8>(held, ca, cb, false, u0, u1, s0, s1, q0, q1);
      G_STEP()
      act_block<12>(held, ca, cb, false, u0, u1, s0, s1, q0, q1);
      rotate16(held);
      if (k == 16) break;
      G_STEP()
    }
    if (sh.act == 2) {
      const int zi = get_item(p, 0);
      const int ln = lane_id(), row0 = (((zi >> 5) & 31) * 2 + (blockIdx.x & 1)) * 128 + c.warp * 16 + (ln >> 2), ql = ln & 3;
      const float m0 = fmaf(s0, 1.f / 64, u0), m1 = fmaf(s1, 1.f / 64, u1);
      q0 -= s0 * s0 * (1.f / 64); q1 -= s1 * s1 * (1.f / 64);
      const float mu0 = quad_sum(m0) * 0.25f, mu1 = quad_sum(m1) * 0.25f;
      q0 = quad_sum(fmaf(64.f * (m0 - mu0), m0 - mu0, q0)); q1 = quad_sum(fmaf(64.f * (m1 - mu1), m1 - mu1, q1));
      if (ql < 2) st_tagged(&g_stats[(row0 + 8 * ql) * 8 + (zi & 31)], ql ? mu1 : mu0, ql ? q1 : q0, load_tag(c));
      if (ln == 0) mbar_arrive(c.sb + OFF_BAR + B_PUB);
    }
  }
  const int s0 = sh.store == 0 ? -9 : k + (sh.store == 2 ? Z_DELAY : 1), s1 = sh.store == 3 ? -9 : s0 + 3;
  hold = hold && k < nsteps;
  const int ksk = sh.store == 2 ? 3 : -1;
#pragma unroll 1
  while (k < nsteps) {
    G_STEP()
    if (k == ksk) ring_adv<4>(c.g);
    if (k == s0) stage_half<0>(c, held, sh.store);
    else if (k == s1) stage_half<32>(c, held, sh.store);
    else if (hold && k == nsteps - 2 && c.warp >= 4) named_sync(6);
  }
  if (hold && c.warp < 4) asm volatile("bar.arrive 6, 256;" ::: "memory");
  wgmma_wait<0>();
  fence_regs(acc);
  if (elected) asm volatile("mbarrier.arrive.shared::cluster.b64 _, [%0];" :: "r"(rel + 8 * prev) : "memory");
  sh.store = sh.act == 2 ? 2 : 0;
  sh.act = 0;
}

template <bool SUB> __device__ __forceinline__ void softmax_exp(const float (&S)[64], uint32_t (&P)[32], float m0, float m1, float& s0, float& s1) {
  float a0 = 0.f, a1 = 0.f, b0 = 0.f, b1 = 0.f;
#pragma unroll
  for (int j = 0; j < 16; j++) {
    const float p0 = ex2(SUB ? S[4 * j] - m0 : S[4 * j]), p1 = ex2(SUB ? S[4 * j + 1] - m0 : S[4 * j + 1]);
    const float p2 = ex2(SUB ? S[4 * j + 2] - m1 : S[4 * j + 2]), p3 = ex2(SUB ? S[4 * j + 3] - m1 : S[4 * j + 3]);
    a0 += p0; b0 += p1; a1 += p2; b1 += p3;
    P[2 * j] = pack_bf16(p0, p1); P[2 * j + 1] = pack_bf16(p2, p3);
  }
  s0 = a0 + b0; s1 = a1 + b1;
}
__device__ __forceinline__ void row_max(const float (&S)[64], float& x0, float& x1) {
  float a0 = fmaxf(S[0], S[1]), a1 = fmaxf(S[2], S[3]);
#pragma unroll
  for (int j = 1; j < 16; j++) { a0 = fmaxf(a0, fmaxf(S[4 * j], S[4 * j + 1])); a1 = fmaxf(a1, fmaxf(S[4 * j + 2], S[4 * j + 3])); }
  x0 = quad_max(a0); x1 = quad_max(a1);
}

__device__ __forceinline__ void issue_qk(float (&S)[64], uint32_t da, uint32_t db) {
#pragma unroll
  for (int kk = 0; kk < 8; kk++) {
    const uint32_t o = (kk >> 2) * 1024 + (kk & 3) * 2;
    wgmma_m64n128k16_ss_tb0(S, DESC_HI | (da + o), DESC_HI | (db + o), kk > 0);
  }
}
__device__ __forceinline__ void issue_pv(float (&O)[64], const uint32_t (&P)[32], uint32_t db, int acc) {
#pragma unroll
  for (int kk = 0; kk < 8; kk++) wgmma_m64n128k16_rs_tb1(O, P[4 * kk], P[4 * kk + 1], P[4 * kk + 2], P[4 * kk + 3], DESC_HI | (db + kk * 128), (acc || kk > 0));
}

__device__ __forceinline__ void att_pack(const float (&O)[64], uint32_t (&pk)[32], float i0, float i1) {
#pragma unroll
  for (int j = 0; j < 16; j++) {
    pk[2 * j] = pack_bf16(O[4 * j] * i0, O[4 * j + 1] * i0);
    pk[2 * j + 1] = pack_bf16(O[4 * j + 2] * i1, O[4 * j + 3] * i1);
  }
}
__device__ __forceinline__ void att_stage(Cons& c, const uint32_t (&pk)[32], uint32_t qbuf) {
  stage_chunks<2>(c.sb + (qbuf ? OFF_Q1 : OFF_Q0) + c.warp * 2048, 16384, pk);
  stage_commit(c);
}

#define ATT_ISSUE(PIN, ACC, PV)                                                                                        \
  wgmma_fence();                                                                                                       \
  issue_qk(S, qd, kd); wgmma_commit();                                                                                 \
  if (g > 1) release_slot(c, vrel);                                                                                    \
  vready = mbar_test(vbar, vph);                                                                                       \
  if (PV) {                                                                                                            \
    mbar_spin(vbar, vph);                                                                                              \
    wgmma_fence();                                                                                                     \
    issue_pv(O, PIN, vd, ACC); wgmma_commit();                                                                         \
  } else {                                                                                                             \
    asm volatile("wgmma.commit_group.sync.aligned; // empty" ::: "memory");                                            \
  }                                                                                                                    \
  krel = kbar + (B_KE - B_KF); vrel = vbar + (B_KE - B_KF);                                                            \
  g++;                                                                                                                 \
  if (g < total) { kd = kd0 + kv.s * (KV_SLOT >> 4); kbar = bars + B_KF + 8 * kv.s; kph = kv.ph; ring_adv<5>(kv); }    \
  vd = vd0 + kv.s * (KV_SLOT >> 4); vbar = bars + B_KF + 8 * kv.s; vph = kv.ph; ring_adv<5>(kv);

#define ATT_WAIT_S()                                                                                                   \
  wgmma_wait<1>();                                                                                                     \
  fence_regs(S);                                                                                                       \
  release_slot(c, krel);                                                                                               \
  if (c.warp == 2) asm volatile("st.volatile.shared.u32 [%0], %1;" :: "r"(bars + B_PROG), "r"(g) : "memory");

#define ATT_SOFTMAX(POUT, FIRST)                                                                                       \
  fresh = false;                                                                                                       \
  _Pragma("unroll 1")                                                                                                  \
  while (true) {                                                                                                       \
    if (__builtin_expect(fresh, 0)) {                                                                                  \
      float x0, x1;                                                                                                    \
      row_max(S, x0, x1);                                                                                              \
      if (FIRST) m0 = m1 = -1e38f;                                                                                     \
      x0 = fmaxf(x0, m0); x1 = fmaxf(x1, m1);                                                                          \
      f0 = ex2(m0 - x0); f1 = ex2(m1 - x1);                                                                            \
      m0 = x0; m1 = x1; l0 *= f0; l1 *= f1;                                                                            \
      zero = false;                                                                                                    \
    }                                                                                                                  \
    if (zero) {                                                                                                        \
      softmax_exp<false>(S, POUT, m0, m1, s0, s1);                                                                     \
      bad = !(s0 <= SM_HI && s1 <= SM_HI) || ((FIRST) && (s0 < SM_LO || s1 < SM_LO));                                  \
    } else {                                                                                                           \
      softmax_exp<true>(S, POUT, m0, m1, s0, s1);                                                                      \
      bad = !(s0 <= SM_THR && s1 <= SM_THR);                                                                           \
    }                                                                                                                  \
    kready = mbar_test(kbar, kph) && vready;                                                                           \
    slow = fresh || __any_sync(0xffffffffu, bad || !kready);                                                           \
    if (__builtin_expect(!slow, 1)) break;                                                                             \
    if (fresh || !__any_sync(0xffffffffu, bad)) break;                                                                 \
    fresh = true;                                                                                                      \
  }                                                                                                                    \
  l0 += s0; l1 += s1;                                                                                                  \
  wgmma_wait<0>(); fence_regs(O);

#define ATT_RESCALE()                                                                                                  \
  { _Pragma("unroll")                                                                                                  \
    for (int i = 0; i < 16; i++) { O[4 * i] *= f0; O[4 * i + 1] *= f0; O[4 * i + 2] *= f1; O[4 * i + 3] *= f1; } }

__device__ __forceinline__ void att_stagger(const Cons& c, int g) {
  if (c.warp >= 4)
    asm volatile("{\n.reg .pred p;\n.reg .s32 v;\nLOOP:\nld.volatile.shared.s32 v, [%0];\nsetp.le.s32 p, v, %1;\n@p bra LOOP;\n}" :: "r"(c.sb + OFF_BAR + B_PROG), "r"(g) : "memory");
}

__device__ __forceinline__ void att_run(Cons& c, const Params& p, int it, int n) {
  const uint32_t bars = c.sb + OFF_BAR;
  float S[64], O[64];
  uint32_t P0[32], P1[32];
#pragma unroll
  for (int i = 0; i < 64; i++) O[i] = 0.f;
#pragma unroll
  for (int i = 0; i < 32; i++) P0[i] = P1[i] = 0u;
  fence_regs(O); fence_regs(P0); fence_regs(P1);
  float m0 = 0.f, m1 = 0.f, l0 = 0.f, l1 = 0.f, f0 = 1.f, f1 = 1.f, s0, s1, pl0 = 0.f, pl1 = 0.f;
  const int total = 16 * n;
  int g = 0;
  Ring kv = {1, 0};
  uint32_t kbar = bars + B_KF, kph = 0, vbar = bars + B_KF, vph = 0, krel, vrel = 0;
  const uint32_t kd0 = (uint32_t)make_desc(c.sb, 16, 1024), vd0 = (uint32_t)make_desc(c.sb, 16384, 1024);
  uint32_t qd = kd0 + ((OFF_Q0 + (c.warp >> 2) * 8192) >> 4), kd = kd0, vd = vd0;
  bool fresh, kready, vready, bad, slow, zero = false;
  mbar_spin(bars + B_QF, 0);
  mbar_spin(bars + B_KF, 0);
  att_stagger(c, 0);
#pragma unroll 1
  while (true) {
    ATT_ISSUE(P1, 1, g > 0)
    const bool first = ((g - 1) & 15) == 0;
    if (first) { pl0 = l0; pl1 = l1; m0 = m1 = l0 = l1 = 0.f; zero = true; }
    ATT_WAIT_S()
    ATT_SOFTMAX(P0, first)
    if (__builtin_expect(slow || first, 0)) {
      if (first) {
        if (g > 1) {
          att_pack(O, P1, __fdividef(1.f, quad_sum(pl0)), __fdividef(1.f, quad_sum(pl1)));
          att_stage(c, P1, ((g >> 4) & 1) ^ 1);
        }
      } else if (fresh) ATT_RESCALE();
      mbar_spin(kbar, kph);
      if (__any_sync(0xffffffffu, !kready)) att_stagger(c, g);
    }
    ATT_ISSUE(P0, !first, true)
    ATT_WAIT_S()
    ATT_SOFTMAX(P1, false)
    if (__builtin_expect(slow || (g & 15) == 0, 0)) {
      if (fresh) ATT_RESCALE();
      if (g == total) break;
      mbar_spin(kbar, kph);
      if (__any_sync(0xffffffffu, !kready)) att_stagger(c, g);
      if ((g & 15) == 0) {
        const int t = g >> 4;
        const uint32_t qb = t & 1;
        mbar_spin(bars + B_QF + 8 * qb, (t >> 1) & 1);
        qd = kd0 + (((qb ? OFF_Q1 : OFF_Q0) + (c.warp >> 2) * 8192) >> 4);
      }
    }
  }
  release_slot(c, vrel);
  mbar_spin(vbar, vph);
  wgmma_fence();
  issue_pv(O, P1, vd, 1); wgmma_commit();
  pl0 = __fdividef(1.f, quad_sum(l0)); pl1 = __fdividef(1.f, quad_sum(l1));
  wgmma_wait<0>();
  fence_regs(O);
  release_slot(c, vbar + (B_KE - B_KF));
  att_pack(O, P0, pl0, pl1);
  if ((get_item(p, it + n) >> 12) == T_END) {
    const uint32_t buf = c.sb + (((n - 1) & 1) ? OFF_Q1 : OFF_Q0) + c.warp * 2048;
    stage_chunks<2>(buf, 16384, P0);
    fence_async_smem();
    __syncwarp();
    if (elect_one()) {
      const int im = get_item(p, it + n - 1), col = ((im >> 5) & 31) * 128, row = ((im & 31) * 2 + (blockIdx.x & 1)) * 128 + c.warp * 16;
      tma_store_2d(&p.tm[TS_O], buf, col, row); tma_store_2d(&p.tm[TS_O], buf + 16384, col + 64, row);
      bulk_commit();
      bulk_wait<0>();
      mbar_arrive(bars + B_STG);
    }
    __syncwarp();
  } else {
    att_stage(c, P0, (n - 1) & 1);
  }
}

__global__ void __cluster_dims__(2, 1, 1) __launch_bounds__(384, 1) fused_kernel(const __grid_constant__ Params p) {
  const uint32_t sb = smem_base();
  const uint32_t bars = sb + OFF_BAR;
  const int tid = threadIdx.x, lane = tid & 31;
  const int warp_id = __shfl_sync(0xffffffffu, tid >> 5, 0), wg = warp_id >> 2;
  const uint32_t rank = blockIdx.x & 1;
  const uint16_t* items = p.items[blockIdx.x >> 1];
  const int gw = blockIdx.x * 8 + warp_id - 4;
  uint4 xv[2][4];
  if (wg != 0 && gw < SEQ / 2) {
#pragma unroll
    for (int rr = 0; rr < 2; rr++)
#pragma unroll
      for (int i = 0; i < 4; i++) xv[rr][i] = __ldg(reinterpret_cast<const uint4*>(p.x + (size_t)(gw * 2 + rr) * DM) + i * 32 + lane);
  }
  if (warp_id == 1 && lane < TM_COUNT) asm volatile("prefetch.tensormap [%0];" :: "l"(&p.tm[lane]) : "memory");
  if (tid == 0) {
    for (int i = 0; i < 4; i++) { mbar_init(bars + B_GF + 8 * i, 1); mbar_init(bars + B_GE + 8 * i, 4); }
    for (int i = 0; i < 5; i++) { mbar_init(bars + B_KF + 8 * i, 1); mbar_init(bars + B_KE + 8 * i, 4); }
    for (int i = 0; i < 2; i++) { mbar_init(bars + B_QF + 8 * i, 1); mbar_init(bars + B_QE + 8 * i, 1); }
    mbar_init(bars + B_XF, 2); mbar_init(bars + B_XR, 2); mbar_init(bars + B_STG, 8); mbar_init(bars + B_FREE, 1); mbar_init(bars + B_GO, 1); mbar_init(bars + B_LN, 2); mbar_init(bars + B_PUB, 8);
    asm volatile("fence.mbarrier_init.release.cluster;" ::: "memory");
  }
  asm volatile("barrier.cluster.arrive.relaxed.aligned;" ::: "memory");

  if (wg == 0) {
    asm volatile("setmaxnreg.dec.sync.aligned.u32 40;");
    asm volatile("barrier.cluster.wait.acquire.aligned;" ::: "memory");
    if (warp_id >= 2 && (items[0] >> 12) == T_Z2) {
      if (lane == 0) mbar_wait_sleep(bars + B_PUB, 0, 100);
      __syncwarp();
      uint32_t tag;
      asm volatile("ld.volatile.shared.u32 %0, [%1];" : "=r"(tag) : "r"(bars + B_TAG));
      const int r = (warp_id - 2) * 64 + lane;
      const uint2* ps = &g_stats[((((items[0] >> 5) & 31) * 2 + rank) * 128 + r) * 8];
      uint4 t[2][4];
      uint32_t cnt = 0;
      while (true) {
        bool ok = true;
#pragma unroll
        for (int i = 0; i < 8; i++) t[i >> 2][i & 3] = ld_tagged2(ps + (i >> 2) * 256 + (i & 3) * 2);
#pragma unroll
        for (int i = 0; i < 8; i++) { const uint4 v = t[i >> 2][i & 3]; ok = ok && tag_ok(v.x, v.y, tag) && ((i & 3) == 3 || tag_ok(v.z, v.w, tag)); }
        if (__all_sync(0xffffffffu, ok)) break;
        trap_if(++cnt > SPIN_LIMIT);
        __nanosleep(100);
      }
#pragma unroll
      for (int y = 0; y < 2; y++) {
        float u = 0.f, v = 0.f;
#pragma unroll
        for (int i = 0; i < 7; i++) u += untag((i & 1) ? t[y][i >> 1].z : t[y][i >> 1].x);
        u *= 1.f / 7;
#pragma unroll
        for (int i = 0; i < 7; i++) {
          const float d = untag((i & 1) ? t[y][i >> 1].z : t[y][i >> 1].x) - u;
          v += fmaf(256.f * d, d, untag((i & 1) ? t[y][i >> 1].w : t[y][i >> 1].y));
        }
        const float rs = rsqrtf(fmaxf(v, 0.f) * (1.f / FH) + 4e-5f);
        asm volatile("st.shared.v2.b32 [%0], {%1, %2};" :: "r"(sb + OFF_LN + (r + 32 * y) * 8), "r"(pack_bf16(rs, rs)), "r"(pack_bf16(-u, -u)) : "memory");
      }
      __syncwarp();
      if (lane == 0) mbar_arrive(bars + B_LN);
      __syncwarp();
    }
    if (warp_id == 0) {
      trap_if(sb & 1023);
      Ring g = {0, 1};
      int it = 0;
      const uint32_t rot = (items[0] >> 12) == T_Z2 ? 3 : 0;
      uint32_t xph = 0;
      if (elect_one()) {
#pragma unroll 1
        for (;; it++) {
          const int item = items[it], type = item >> 12, b = item & 31, row = (((item >> 5) & 31) * 2 + rank) * 128;
          if (type >= T_ATT) break;
#pragma unroll 1
          for (int seg = 0; seg < (type == T_U ? 2 : 1); seg++) {
            const CUtensorMap* tA = &p.tm[seg ? TM_WSP : TM_XN];
            const CUtensorMap* tB = &p.tm[seg ? TM_Z2 : (type == T_Q ? TM_WQ : TM_WIN)];
            const int bchunk = b * 4 + (type == T_Z2 ? 28 : 0) + rank * 2;
            const unsigned* fl = seg ? &g_flags[F_Z2 + b * 32] : &g_flags[F_XN + (row >> 2)];
            const unsigned tgt = seg ? 16 : 128;
            int k = 0;
            if (it == 0 && seg == 0) {
              for (; k < 4; k++) {
                mbar_expect_tx(bars + B_GF + 8 * k, G_STAGE);
                tma_load_3d_mc(sb + ((k + rot) & 3) * G_STAGE + G_A + rank * 16384, tB, k * 64, bchunk, bars + B_GF + 8 * k);
              }
              g.ph ^= 1;
            }
            if (seg || type != T_U) { flag_wait(fl, tgt); fence_async_global(); }
            for (int x = 0; x < k; x++) tma_load_2d(sb + ((x + rot) & 3) * G_STAGE, tA, x * 64, row, bars + B_GF + 8 * x);
            if (it == 0) asm volatile("st.volatile.shared.v4.u32 [%0], {%1, %2, %2, %2};" :: "r"(bars + B_TAG), "r"(__ldcg(&g_epoch) % 4095u + 1), "r"(0) : "memory");
#pragma unroll 1
            for (; k < (seg ? 32 : 16); k++) {
              if (type == T_U && seg == 0) {
                if (k == 3) {
                  mbar_wait(bars + B_GE + 8 * g.s, g.ph);
                  mbar_arrive(bars + B_GF + 8 * g.s);
                  asm volatile("mbarrier.arrive.shared::cta.b64 _, [%0], 4;" :: "r"(bars + B_GE + 8 * g.s) : "memory");
                  ring_adv<4>(g);
                }
                if (k == 6) { mbar_wait(bars + B_XF, xph); xph ^= 1; }
              }
              mbar_wait(bars + B_GE + 8 * g.s, g.ph);
              const uint32_t st = sb + ((g.s + rot) & 3) * G_STAGE, fb = bars + B_GF + 8 * g.s;
              mbar_expect_tx(fb, G_STAGE);
              tma_load_2d(st, tA, k * 64, row, fb);
              tma_load_3d_mc(st + G_A + rank * 16384, tB, k * 64, bchunk, fb);
              ring_adv<4>(g);
            }
          }
        }
      }
      { const int e = __ffs(__ballot_sync(0xffffffffu, elect_one())) - 1; it = __shfl_sync(0xffffffffu, it, e); g.s = __shfl_sync(0xffffffffu, g.s, e); g.ph = __shfl_sync(0xffffffffu, g.ph, e); }
      const int n = ((items[it] >> 10) & 3) + 3;
      Ring kv = {0, 1};
      if (elect_one()) {
        int prow = 0;
        {
          const int im = items[it];
          tma_prefetch_2d(&p.tm[(im & 1) ? TM_V : TM_K], rank * 64, ((im >> 5) & 31) * SEQ + ((im & 7) >> 1) * 128);
        }
#pragma unroll 1
        for (int x = 0; x <= 32 * n; x++) {
          const int gb = x >> 1, t = gb >> 4;
          const int hrow = ((items[it + t] >> 5) & 31) * SEQ;
          const bool isv = (x & 1) || x == 32 * n;
          if (x != 1) {
            if (x == 0 || x == 2) mbar_wait(bars + B_GE + 8 * g.s + 4 * x, g.ph);
            if (x == 4) { mbar_wait(bars + B_XF, xph); xph ^= 1; }
            mbar_wait(bars + B_KE + 8 * kv.s, kv.ph);
            mbar_expect_tx(bars + B_KF + 8 * kv.s, KV_SLOT);
            tma_load_2d_mc(sb + kv.s * KV_SLOT + rank * 16384, &p.tm[isv ? TM_V : TM_K], rank * 64, isv ? prow : hrow + (gb & 15) * 128, bars + B_KF + 8 * kv.s);
            ring_adv<5>(kv);
          }
          {
            const int gp = gb + KV_PF, ip = items[it + (gp >> 4)];
            if (gp < 16 * n && ((gp ^ ip) & 7) == 0) tma_prefetch_2d(&p.tm[(x & 1) ? TM_V : TM_K], rank * 64, ((ip >> 5) & 31) * SEQ + (gp & 15) * 128);
          }
          if (x == 32 * n - 8) mbar_arrive(bars + B_GO);
          if (x & 1) prow = hrow + (gb & 15) * 128;
          if ((x & 31) == 11 && t + 1 < n) {
            const int tq = t + 1;
            const int im = items[it + tq], h = (im >> 5) & 31, m = (im & 31) * 2 + rank;
            const uint32_t qb = tq & 1;
            flag_wait(&g_flags[F_Q + m * 16 + (h >> 1)], 1);
            fence_async_global();
            mbar_wait(bars + B_QE + 8 * qb, ((tq - 1) >> 1) & 1);
            const uint32_t dst = sb + (qb ? OFF_Q1 : OFF_Q0), fb = bars + B_QF + 8 * qb;
            mbar_expect_tx(fb, 32768);
            tma_load_2d(dst, &p.tm[TM_Q], h * 128, m * 128, fb);
            tma_load_2d(dst + 16384, &p.tm[TM_Q], h * 128 + 64, m * 128, fb);
          }
        }
      }
      __syncwarp();
      it += n;
      uint32_t ready = 0;
      auto wait_head = [&](int h) {
        if ((ready >> h) & 1) return;
        uint32_t cnt = 0;
        while (true) {
          asm volatile("ld.acquire.cta.shared.u32 %0, [%1];" : "=r"(ready) : "r"(bars + B_RDY) : "memory");
          if ((ready >> h) & 1) break;
          trap_if(++cnt > SPIN_LIMIT * 8);
          __nanosleep(20);
        }
        fence_async_global();
      };
      int item = items[it];
      if ((item >> 12) == T_SA) {
        const int m = ((item >> 5) & 31) * 2 + rank, b = item & 31;
        Ring dr = kv;
        wait_head(0);
#pragma unroll 1
        for (int i = 0; i < 28 + 2 * SA_HEADS; i++) {
          {
            const bool so = i >= 28;
            const int k = so ? i - 28 : i;
            if (so) wait_head(k >> 1);
            if (elect_one()) {
              if (i < 4) { for (int x = 0; x < ((0x1022 >> (4 * i)) & 3); x++) { mbar_wait(bars + B_KE + 8 * dr.s, dr.ph); ring_adv<5>(dr); } }
              if (i == 2) { mbar_wait(bars + B_XF, xph); xph ^= 1; }
              mbar_wait(bars + B_GE + 8 * g.s, g.ph);
              const uint32_t st = sb + g.s * G_STAGE, fb = bars + B_GF + 8 * g.s;
              mbar_expect_tx(fb, G_STAGE);
              tma_load_2d(st, &p.tm[so ? TM_O : TM_U], k * 64, m * 128, fb);
              tma_load_3d_mc(st + G_A + rank * 16384, &p.tm[so ? TM_WO : TM_WOUT], k * 64, b * 4 + rank * 2, fb);
            }
            ring_adv<4>(g);
          }
          const int ip = i + OUT_PF;
          if (ip < 28 + 2 * SA_HEADS && elect_one()) {
            const bool so = ip >= 28;
            const int k = so ? ip - 28 : ip;
            if ((ip & 3) == b && (!so || ((ready >> (k >> 1)) & 1))) tma_prefetch_2d(&p.tm[so ? TM_O : TM_U], k * 64, m * 128);
            if ((ip & 7) == (m >> 1)) tma_prefetch_3d(&p.tm[so ? TM_WO : TM_WOUT], k * 64, b * 4 + rank * 2);
          }
          __syncwarp();
        }
        item = items[++it];
      }
      if ((item >> 12) == T_FIN) {
        const bool own = item & 4;
        const int m = ((item >> 5) & 31) * 2 + rank, col = (item & 3) * 256 + (own ? 128 : 0);
        uint32_t ps = own ? FIN_SLOT0 : kv.s;
#pragma unroll 1
        for (int i = 2 * SA_HEADS; i <= 2 * NH; i++) {
          const bool extra = i == 2 * NH - FIN_PREP;
          if (extra && own) continue;
          const int k = i > 2 * NH - FIN_PREP ? i - 1 : i;
          if (!extra) wait_head(k >> 1);
          if (elect_one()) {
            if (i == 2 * SA_HEADS) {
              for (int y = k; y < k + 4; y++) if ((ready >> (y >> 1)) & 1) tma_prefetch_2d(&p.tm[TM_O], y * 64, m * 128);
            }
            if (own && i < 2 * SA_HEADS + 5) {
              const uint32_t s0 = (0x22100u >> (4 * ps)) & 3, s1 = (0x32110u >> (4 * ps)) & 3;
              mbar_wait(bars + B_GE + 8 * s0, g.ph ^ (s0 < g.s)); mbar_wait(bars + B_GE + 8 * s1, g.ph ^ (s1 < g.s));
            }
            if (extra) { flag_wait(&g_flags[F_S + m * 4 + (item & 3)], 2); fence_async_global(); }
            mbar_wait(bars + B_KE + 8 * kv.s, kv.ph);
            const uint32_t dst = sb + ps * KV_SLOT, fb = bars + B_KF + 8 * kv.s;
            if (++ps == 5) ps = 0;
            mbar_expect_tx(fb, KV_SLOT);
            if (!extra) {
              tma_load_2d(dst, &p.tm[TM_O], k * 64, m * 128, fb);
              tma_load_2d_mc(dst + 16384 + rank * 8192, &p.tm[TM_WO64], col + rank * 64, k * 64, fb);
            } else {
              tma_load_2d(dst, &p.tm[TM_SA], col, m * 128, fb);
              tma_load_2d(dst + 16384, &p.tm[TM_SA], col + 64, m * 128, fb);
            }
            ring_adv<5>(kv);
          }
          __syncwarp();
        }
      }
      unsigned last = 0;
      if (lane == 0 && (item >> 12) == T_FIN) mbar_wait_sleep(bars + B_XR, 0, 100);
      if (lane == 0) { __threadfence(); last = atomicInc(&g_done, gridDim.x - 1) == gridDim.x - 1; }
      last = __shfl_sync(0xffffffffu, last, 0);
      if (last) {
        for (int i = lane; i < F_TOTAL / 4; i += 32) reinterpret_cast<uint4*>(g_flags)[i] = make_uint4(0, 0, 0, 0);
        if (lane == 0) g_epoch = g_epoch + 1;
      }
    } else if (warp_id == 1) {
      if (elect_one()) {
        uint32_t ph = 0;
        int t = 0;
        unsigned* fq = nullptr;
        const bool z = (items[0] >> 12) == T_Z2;
#pragma unroll 1
        for (int it = 0;; it++) {
          const int ii = (z && it < 2) ? it ^ 1 : it;
          const int item = items[ii], type = item >> 12, a = (item >> 5) & 31, b = item & 31;
          if (type == T_END) break;
          const int nt = items[ii + 1] >> 12;
          int row = (a * 2 + rank) * 128, col = b * 256;
          unsigned* f = &g_flags[F_S + (a * 2 + rank) * 4 + b];
          int tm = TS_G, npair = 2;
          bool quad = false;
          uint32_t src = sb + OFF_Q0;
          if (type == T_Z2) { tm = TS_Z2; f = &g_flags[F_Z2 + b * 32]; }
          else if (type == T_Q) { tm = TS_Q; f = &g_flags[F_Q + (a * 2 + rank) * 16 + b]; if (z || nt >= T_ATT) { npair = 0; quad = true; } }
          else if (type == T_U) { tm = TS_U; f = &g_flags[F_U + (a * 2 + rank) * 32]; npair = 0; quad = true; }
          else if (type == T_ATT) { tm = TS_O; f = &g_flags[F_O + (b * 2 + rank) * 32 + a]; npair = 1; row = (b * 2 + rank) * 128; col = a * 128; if (t & 1) src = sb + OFF_Q1; }
          else if (type == T_FIN) npair = 1;
          auto load_fin = [&](int fi, int tmi, uint32_t qb) {
            const int fc = (fi & 3) * 256 + ((fi & 4) ? 128 : 0), fr = (((fi >> 5) & 31) * 2 + rank) * 128;
            mbar_expect_tx(bars + B_QF + 8 * qb, 32768);
            tma_load_2d(sb + (qb ? OFF_Q1 : OFF_Q0), &p.tm[tmi], fc, fr, bars + B_QF + 8 * qb);
            tma_load_2d(sb + (qb ? OFF_Q1 : OFF_Q0) + 16384, &p.tm[tmi], fc + 64, fr, bars + B_QF + 8 * qb);
          };
          if (type == T_ATT && nt == T_FIN) load_fin(items[ii + 1], TM_X, (t & 1) ^ 1);
          if (type == T_FIN) {
            if (!(item & 4)) { flag_wait(&g_flags[F_S + (a * 2 + rank) * 4 + (b & 3)], 1); fence_async_global(); load_fin(item, TM_G, (t & 1) ^ 1); }
            mbar_arrive(bars + B_XR);
          }
#pragma unroll 1
          for (int op = 0; op < npair + quad; op++) {
            const bool q = op == npair;
            const int c0 = (q || type == T_SA) ? col : col + op * 128;
            mbar_wait_sleep(bars + B_STG, ph, (type == T_ATT && nt == T_ATT) ? SW_ATT : SW_NS);
            if (type == T_FIN) break;
            ph ^= 1;
            fence_async_smem();
            if (type == T_SA && op == 1) { tm = TS_SA; load_fin(items[ii + 1], TM_X, 1); }
            int c1 = c0;
            const bool pre = q && nt == T_ATT;
            if (pre) {
              const CUtensorMap* tb = &p.tm[type == T_U ? TM_U : TM_Q];
              tma_store_2d(tb, sb + 2 * G_STAGE, c0, row);
              tma_store_2d(tb, sb + 3 * G_STAGE, c0 + 64, row);
              bulk_commit();
              bulk_wait_read<0>();
              mbar_arrive_cta(bars + B_XF, 0); mbar_arrive_cta(bars + B_XF, 1);
              src = sb + OFF_Q1; c1 += 128;
            }
#pragma unroll 1
            for (int y = 0; y < ((q && !pre) ? 2 : 1); y++) {
              if (nt != T_END) {
#pragma unroll 1
                for (int r = 0; r < 256; r += ST_ROWS) {
                  tma_store_2d(&p.tm[tm], src + r * 128, c1 + (r >> 7) * 64, row + (r & 127));
                  bulk_commit();
                  bulk_wait_read<ST_FLY>();
                }
              }
              bulk_wait_read<0>();
              if (y == 0) mbar_arrive(bars + B_FREE);
              else { mbar_arrive_cta(bars + B_XF, 0); mbar_arrive_cta(bars + B_XF, 1); }
              if (q) { src = sb + OFF_ZQ; c1 += 128; }
            }
            if (type == T_ATT && (t & 1) && (nt == T_SA || (items[ii + 2] >> 12) == T_SA)) { mbar_arrive_cta(bars + B_XF, 0); mbar_arrive_cta(bars + B_XF, 1); }
            if (type == T_ATT) mbar_arrive(bars + B_QE + 8 * (t & 1));
            else if (nt == T_ATT) mbar_arrive(bars + B_QE + 8);
            if (z && it == 0) { fq = f; continue; }
            if (op + 1 >= npair || type == T_SA) {
              bulk_wait<0>();
              red_release(f, 1);
              if (type == T_Z2) red_release(fq, 1);
            }
          }
          if (type == T_ATT) t++;
          else if (t == 0 && (items[it + 1] >> 12) < T_ATT && (items[it + 2] >> 12) == T_ATT) {
            const int im = items[it + 2], h = (im >> 5) & 31, m = (im & 31) * 2 + rank;
            flag_wait(&g_flags[F_Q + m * 16 + (h >> 1)], 1);
            fence_async_global();
            mbar_expect_tx(bars + B_QF, 32768);
            tma_load_2d(sb + OFF_Q0, &p.tm[TM_Q], h * 128, m * 128, bars + B_QF);
            tma_load_2d(sb + OFF_Q0 + 16384, &p.tm[TM_Q], h * 128 + 64, m * 128, bars + B_QF);
          }
        }
      }
      __syncwarp();
    } else if (warp_id == 2) {
      int it = 0;
      while ((items[it] >> 12) <= T_ATT) it++;
      if ((items[it] >> 12) != T_END) {
        const bool sa = (items[it] >> 12) == T_SA;
        const int m = ((items[it] >> 5) & 31) * 2 + rank;
        if (lane == 0) {
          mbar_wait_sleep(bars + B_GO, 0, 500);
          if (sa) {
            const int b = items[it] & 3;
            flag_wait(&g_flags[F_U + m * 32], 7);
            fence_async_global();
            for (int y = b; y < OUT_PF; y += 4) tma_prefetch_2d(&p.tm[TM_U], y * 64, m * 128);
            tma_prefetch_3d(&p.tm[TM_WOUT], (m >> 1) * 64, b * 4 + rank * 2);
          }
          if (!sa) for (int y = m * 4 + (items[it] & 3); y < 16 * (NH - SA_HEADS); y += 64) tma_prefetch_3d(&p.tm[TM_WO], (2 * SA_HEADS + (y >> 3)) * 64, (y & 7) * 2);
        }
        __syncwarp();
        uint32_t cnt = 0;
        while (true) {
          const uint32_t r = __ballot_sync(0xffffffffu, ld_acquire(&g_flags[F_O + m * 32 + lane]) != 0);
          if (lane == 0) asm volatile("st.release.cta.shared.u32 [%0], %1;" :: "r"(bars + B_RDY), "r"(r) : "memory");
          if (r == ~0u) break;
          trap_if(++cnt > SPIN_LIMIT);
          __nanosleep(r >> 28 ? 20 : 300);
        }
        if (lane == 0) mbar_arrive(bars + B_XR);
      }
      __syncwarp();
    }
    cluster_sync_relaxed();
  } else {
    Cons c;
    c.sb = sb; c.warp = warp_id - 4; c.g = {0, 0}; c.fph = 1; c.rot = (get_item(p, 0) >> 12) == T_Z2 ? 3 : 0;
    if (gw < SEQ / 2) {
      float f[2][32], rs[2];
#pragma unroll
      for (int rr = 0; rr < 2; rr++) {
#pragma unroll
        for (int i = 0; i < 4; i++) {
          const uint4 v = xv[rr][i];
          f[rr][8 * i + 0] = bf_lo(v.x); f[rr][8 * i + 1] = bf_hi(v.x); f[rr][8 * i + 2] = bf_lo(v.y); f[rr][8 * i + 3] = bf_hi(v.y);
          f[rr][8 * i + 4] = bf_lo(v.z); f[rr][8 * i + 5] = bf_hi(v.z); f[rr][8 * i + 6] = bf_lo(v.w); f[rr][8 * i + 7] = bf_hi(v.w);
        }
        float s = 0.f;
#pragma unroll
        for (int i = 0; i < 32; i++) s += f[rr][i];
#pragma unroll
        for (int o = 16; o; o >>= 1) s += __shfl_xor_sync(0xffffffffu, s, o);
        const float mean = s * (1.f / DM);
        float q = 0.f;
#pragma unroll
        for (int i = 0; i < 32; i++) { f[rr][i] -= mean; q = fmaf(f[rr][i], f[rr][i], q); }
#pragma unroll
        for (int o = 16; o; o >>= 1) q += __shfl_xor_sync(0xffffffffu, q, o);
        rs[rr] = rsqrtf(q * (1.f / DM) + 1e-5f);
      }
      uint4* dst = reinterpret_cast<uint4*>(g_xn + (size_t)gw * 2 * DM) + lane;
#pragma unroll
      for (int rr = 0; rr < 2; rr++) {
        const float r = rs[rr];
#pragma unroll
        for (int i = 0; i < 4; i++) {
          const float* y = &f[rr][8 * i];
          dst[rr * 128 + i * 32] = make_uint4(pack_bf16(y[0] * r, y[1] * r), pack_bf16(y[2] * r, y[3] * r), pack_bf16(y[4] * r, y[5] * r), pack_bf16(y[6] * r, y[7] * r));
        }
      }
      named_sync(7);
      if (tid == 128) red_release(&g_flags[F_XN + (gw >> 6) * 32], 16);
    }
    asm volatile("setmaxnreg.inc.sync.aligned.u32 232;");
    asm volatile("barrier.cluster.wait.acquire.aligned;" ::: "memory");
    int natt = 0;
    int it = 0;
    uint32_t held[64];
#pragma unroll
    for (int i = 0; i < 64; i++) held[i] = 0u;
    Shadow sh = {0, 0};
    float facc[64];
#pragma unroll 1
    while (true) {
      const int item = get_item(p, it), type = item >> 12, a = (item >> 5) & 31;
      c.warp = fresh_warp();
      if (type == T_ATT) {
        const int n = ((item >> 10) & 3) + 3;
        att_run(c, p, it, n);
#pragma unroll
        for (int i = 0; i < 64; i++) held[i] = 0u;
        natt = n;
        it += n;
        c.rot = 0;
        if ((get_item(p, it) >> 12) == T_SA) continue;
#pragma unroll
        for (int i = 0; i < 64; i++) facc[i] = 0.f;
        break;
      }
      float acc[128];
      const bool sa = type == T_SA;
      bool more = type >= T_U;
      int nsteps = sa ? 28 : 16;
      const bool direct = sh.act == 2 || (get_item(p, it + 1) >> 12) >= T_ATT;
      uint32_t bias0 = 0, bias1 = 0;
#pragma unroll 1
      while (true) {
        gemm_seg(acc, held, c, p, sh, nsteps, more || !direct || sa);
        if (type == T_Q) {
#pragma unroll
          for (int i = 0; i < 128; i++) acc[i] *= SM_C;
        }
        if (!more && direct) break;
#pragma unroll
        for (int i = 0; i < 64; i++) held[i] = pack_bf16(acc[2 * i], acc[2 * i + 1]);
        if (!more) break;
        more = false;
        nsteps = sa ? 2 * SA_HEADS : 32;
        sh.act = sa ? 3 : 1;
        if (sa) {
          sh.store = 3;
        } else {
          const int row0 = (a * 2 + rank) * 128 + c.warp * 16 + (lane_id() >> 2);
          asm volatile("ld.global.nc.u16 %0, [%1];" : "=r"(bias0) : "l"(p.b_sp + row0));
          asm volatile("ld.global.nc.u16 %0, [%1];" : "=r"(bias1) : "l"(p.b_sp + row0 + 8));
        }
      }
      c.warp = fresh_warp();
      if (direct) {
        const bool pre = !sa && sh.store != 2;
        const uint32_t hb0 = bf2_mul(bias0 * 0x10001u, BF2_HALF), hb1 = bf2_mul(bias1 * 0x10001u, BF2_HALF);
        stage_acquire(c);
#pragma unroll
        for (int h = 0; h < 2; h++) {
          uint32_t pk[32];
#pragma unroll
          for (int i = 0; i < 32; i++) pk[i] = pack_bf16(acc[64 * h + 2 * i], acc[64 * h + 2 * i + 1]);
          if (type == T_U) {
#pragma unroll
            for (int i = 0; i < 32; i++) pk[i] = bf2_mul(bf2_fma(pk[i], BF2_HALF, (i & 1) ? hb1 : hb0), held[32 * h + i]);
          }
          if (h) named_sync(5);
          stage_chunks<2>(sb + (h ? (pre ? OFF_Q1 : OFF_ZQ) : (pre ? 2 * G_STAGE : OFF_Q0)) + c.warp * 2048, (!h && pre) ? G_STAGE : 16384, pk);
          if (sa) break;
        }
        stage_commit(c);
        if (sa) {
#pragma unroll
          for (int i = 0; i < 64; i++) facc[i] = acc[64 + i];
          it++;
          break;
        }
      } else if (type == T_Q) {
        sh.store = 1;
      } else {
        sh.act = 2;
      }
      it++;
    }
    const int fin = get_item(p, it);
    if ((fin >> 12) == T_FIN) {
      c.warp = fresh_warp();
      const bool own = fin & 4;
      Ring kv = {(uint32_t)(32 * natt) % 5, ((uint32_t)(32 * natt) / 5) & 1};
      uint32_t prev = 0, ps = own ? FIN_SLOT0 : kv.s;
      fence_regs(facc);
      auto fin_steps = [&](int k0, int k1) {
#pragma unroll 1
        for (int k = k0; k < k1; k++) {
          mbar_spin(bars + B_KF + 8 * kv.s, kv.ph);
          const uint32_t st = ((c.sb & 0x3FFFF) >> 4) + ps * (KV_SLOT >> 4);
          if (++ps == 5) ps = 0;
          const uint32_t da = st + (c.warp >> 2) * 512 + (1u << 16), db = st + 1024 + ((8192u >> 4) << 16);
          wgmma_fence();
#pragma unroll
          for (int kk = 0; kk < 4; kk++) wgmma_m64n128k16_ss_tb1(facc, DESC_HI | (da + kk * 2), DESC_HI | (db + kk * 128), 1);
          wgmma_commit();
          wgmma_wait<1>();
          if (k > 2 * SA_HEADS) release_slot(c, prev);
          prev = bars + B_KE + 8 * kv.s;
          ring_adv<5>(kv);
        }
      };
      const int kp = (own && ((fin >> 5) & 31) == 7) ? 2 * SA_HEADS + 5 : 2 * NH - FIN_PREP - (own ? OWN_OFF : 0);
      fin_steps(2 * SA_HEADS, kp);
      const uint32_t ln = lane_id(), xb = own ? 1 : natt & 1;
      const uint32_t lo = c.warp * 2048 + ((ln & 15) << 7);
      uint32_t xs[32];
      auto load_tile = [&](uint32_t base, uint32_t* d) {
#pragma unroll
        for (int i = 0; i < 8; i++) ldmatrix_x4(base + lo + (i >> 2) * 16384 + (((2 * (i & 3) + (ln >> 4)) ^ (ln & 7)) << 4), d[4 * i], d[4 * i + 1], d[4 * i + 2], d[4 * i + 3]);
      };
      const uint32_t xa = sb + (xb ? OFF_Q1 : OFF_Q0);
      mbar_spin(bars + B_QF + 8 * xb, ((natt + 1 - xb) >> 1) & 1);
      load_tile(xa, xs);
      if (!own) {
        mbar_spin(bars + B_QF + 8 * (xb ^ 1), ((natt + xb) >> 1) & 1);
        load_tile(sb + (xb ? OFF_Q0 : OFF_Q1), held + 32);
      }
      float gf[64], rf[64];
#pragma unroll
      for (int i = 0; i < 32; i++) { gf[2 * i] = bf_lo(held[32 + i]); gf[2 * i + 1] = bf_hi(held[32 + i]); rf[2 * i] = bf_lo(xs[i]); rf[2 * i + 1] = bf_hi(xs[i]); }
      if (!own) {
        mbar_spin(bars + B_KF + 8 * kv.s, kv.ph);
#pragma unroll
        for (int i = 0; i < 8; i++) {
          uint32_t t[4];
          ldmatrix_x4(sb + ps * KV_SLOT + lo + (i >> 2) * 16384 + (((2 * (i & 3) + (ln >> 4)) ^ (ln & 7)) << 4), t[0], t[1], t[2], t[3]);
#pragma unroll
          for (int y = 0; y < 4; y++) {
            rf[8 * i + 2 * y] = fmaf(bf_lo(t[y]), gf[8 * i + 2 * y], rf[8 * i + 2 * y]);
            rf[8 * i + 2 * y + 1] = fmaf(bf_hi(t[y]), gf[8 * i + 2 * y + 1], rf[8 * i + 2 * y + 1]);
          }
        }
        wg_any(c.warp >= 4, false);
        release_slot(c, bars + B_KE + 8 * kv.s);
        if (++ps == 5) ps = 0;
        ring_adv<5>(kv);
      }
      fence_regs(gf); fence_regs(rf);
      fin_steps(kp, 2 * NH);
      wgmma_wait<0>();
      fence_regs(facc);
#pragma unroll
      for (int i = 0; i < 32; i++) xs[i] = pack_bf16(fmaf(facc[2 * i], gf[2 * i], rf[2 * i]), fmaf(facc[2 * i + 1], gf[2 * i + 1], rf[2 * i + 1]));
      __syncwarp();
      stage_chunks<2>(xa + c.warp * 2048, 16384, xs);
      fence_async_smem();
      __syncwarp();
      if (elect_one()) {
        const int col = (fin & 3) * 256 + (own ? 128 : 0), row = (((fin >> 5) & 31) * 2 + rank) * 128 + c.warp * 16;
        tma_store_2d(&p.tm[TS_OUT], xa + c.warp * 2048, col, row);
        tma_store_2d(&p.tm[TS_OUT], xa + c.warp * 2048 + 16384, col + 64, row);
        bulk_commit();
        mbar_arrive(bars + B_STG);
        bulk_wait_read<0>();
      }
    }
    __syncwarp();
    cluster_sync_relaxed();
  }
}

typedef CUresult (*PFN_encodeTiled)(CUtensorMap*, CUtensorMapDataType, cuuint32_t, void*, const cuuint64_t*, const cuuint64_t*, const cuuint32_t*, const cuuint32_t*,
                                    CUtensorMapInterleave, CUtensorMapSwizzle, CUtensorMapL2promotion, CUtensorMapFloatOOBfill);
static PFN_encodeTiled s_encode = nullptr;
static void tm_2d(CUtensorMap* tm, const void* ptr, uint64_t rows, uint64_t cols, uint32_t box_rows) {
  cuuint64_t dims[2] = {cols, rows}; cuuint64_t strides[1] = {cols * 2}; cuuint32_t box[2] = {64, box_rows}; cuuint32_t es[2] = {1, 1};
  CUresult r = s_encode(tm, CU_TENSOR_MAP_DATA_TYPE_BFLOAT16, 2, (void*)ptr, dims, strides, box, es, CU_TENSOR_MAP_INTERLEAVE_NONE,
                        CU_TENSOR_MAP_SWIZZLE_128B, CU_TENSOR_MAP_L2_PROMOTION_L2_128B, CU_TENSOR_MAP_FLOAT_OOB_FILL_NONE);
  if (r != CUDA_SUCCESS) fprintf(stderr, "tensor map encode failed (%d)\n", (int)r);
}
static void tm_3d(CUtensorMap* tm, const void* ptr, uint64_t rows, uint64_t cols) {
  cuuint64_t dims[3] = {64, rows, cols / 64}; cuuint64_t strides[2] = {cols * 2, 128}; cuuint32_t box[3] = {64, 64, 2}; cuuint32_t es[3] = {1, 1, 1};
  CUresult r = s_encode(tm, CU_TENSOR_MAP_DATA_TYPE_BFLOAT16, 3, (void*)ptr, dims, strides, box, es, CU_TENSOR_MAP_INTERLEAVE_NONE,
                        CU_TENSOR_MAP_SWIZZLE_128B, CU_TENSOR_MAP_L2_PROMOTION_L2_128B, CU_TENSOR_MAP_FLOAT_OOB_FILL_NONE);
  if (r != CUDA_SUCCESS) fprintf(stderr, "tensor map encode failed (%d)\n", (int)r);
}
static inline uint16_t mk(int type, int a, int b) { return (uint16_t)(type << 12 | a << 5 | b); }

static void build_schedule(Params& P) {
  int cnt[NCLUSTER];
  for (int c = 0; c < NCLUSTER; c++) { cnt[c] = 0; for (int i = 0; i < MAXI; i++) P.items[c][i] = mk(T_END, 0, 0); }
  auto phys = [](int c) { return c == 64 ? 9 : c == 65 ? 17 : c == 9 ? 64 : c == 17 ? 65 : c; };
  auto push = [&](int c, uint16_t v) { P.items[phys(c)][cnt[c]++] = v; };
  int natt[NCLUSTER], nq[NCLUSTER];
  for (int c = 0; c < NCLUSTER; c++) { natt[c] = c < 32 ? 3 : (c < 56 ? 5 : (c < 62 ? 4 : (c < 64 ? 3 : 5))); nq[c] = c < 56 ? 1 : (c < 62 ? 7 : (c < 64 ? 9 : 6)); }
  for (int c = 0; c < 56; c++) push(c, mk(T_Z2, c % 8, c / 8));
  int qi = 0;
  for (int slot = 0; slot < 9; slot++)
    for (int c = NCLUSTER - 1; c >= 0; c--) {
      const int first = c < 56 ? 1 : 0;
      if (slot >= first && slot < first + nq[c]) { push(c, mk(T_Q, qi % 8, qi / 8)); qi++; }
    }
  for (int c = 0; c < 56; c++) push(c, mk(T_U, c % 8, c / 8));
  int ai = 0;
  for (int slot = 0; slot < 5; slot++)
    for (int c = 0; c < NCLUSTER; c++) {
      const int first = c < 32 ? 0 : 5 - natt[c];
      if (slot >= first && slot < first + natt[c]) { push(c, mk(T_ATT, ai / 8, ai % 8) | (natt[c] - 3) << 10); ai++; }
    }
  for (int c = 0; c < 32; c++) push(c, mk(T_SA, c % 8, c / 8));
  for (int c = 0; c < 64; c++) push(c, mk(T_FIN, c % 8, (c / 8) % 4 | (c < 32 ? 4 : 0)));
  if (qi != 128 || ai != 256) fprintf(stderr, "bad schedule %d %d\n", qi, ai);
}

static Params s_params;
extern "C" void kernel_launch(void* const* d_in, const int* in_sizes, int n_in, void* d_out, int out_size) {
  (void)in_sizes; (void)n_in; (void)out_size;
  if (!s_encode) {
    void* fn = nullptr; cudaDriverEntryPointQueryResult qr;
    cudaGetDriverEntryPoint("cuTensorMapEncodeTiled", &fn, cudaEnableDefault, &qr);
    s_encode = (PFN_encodeTiled)fn;
    cudaFuncSetAttribute(fused_kernel, cudaFuncAttributeMaxDynamicSharedMemorySize, SMEM_BYTES);
    build_schedule(s_params);
  }
  Params& P = s_params;
  void *xn, *q, *o, *z2, *u, *gg, *sa;
  cudaGetSymbolAddress(&gg, g_g); cudaGetSymbolAddress(&sa, g_sa);
  cudaGetSymbolAddress(&xn, g_xn); cudaGetSymbolAddress(&q, g_q); cudaGetSymbolAddress(&o, g_o);
  cudaGetSymbolAddress(&z2, g_z2); cudaGetSymbolAddress(&u, g_u);
  tm_2d(&P.tm[TM_XN], xn, SEQ, DM, 128); tm_2d(&P.tm[TM_WSP], d_in[7], SEQ, SEQ, 128); tm_2d(&P.tm[TM_U], u, SEQ, FH, 128);
  tm_2d(&P.tm[TM_O], o, SEQ, HD, 128); tm_2d(&P.tm[TM_Q], q, SEQ, HD, 128); tm_2d(&P.tm[TM_X], d_in[0], SEQ, DM, 128);
  tm_2d(&P.tm[TM_K], d_in[1], NH * SEQ, 128, 128); tm_2d(&P.tm[TM_V], d_in[2], NH * SEQ, 128, 128);
  tm_2d(&P.tm[TM_SA], sa, SEQ, DM, 128); tm_2d(&P.tm[TM_G], gg, SEQ, DM, 128); tm_2d(&P.tm[TM_WO64], d_in[4], HD, DM, 64);
  tm_3d(&P.tm[TM_WIN], d_in[6], DM, FF); tm_3d(&P.tm[TM_WQ], d_in[3], DM, HD); tm_3d(&P.tm[TM_Z2], z2, SEQ, FH);
  tm_3d(&P.tm[TM_WOUT], d_in[9], FH, DM); tm_3d(&P.tm[TM_WO], d_in[4], HD, DM);
  tm_2d(&P.tm[TS_Q], q, SEQ, HD, ST_ROWS); tm_2d(&P.tm[TS_O], o, SEQ, HD, ST_ROWS); tm_2d(&P.tm[TS_Z2], z2, SEQ, FH, ST_ROWS); tm_2d(&P.tm[TS_U], u, SEQ, FH, ST_ROWS);
  tm_2d(&P.tm[TS_SA], sa, SEQ, DM, ST_ROWS); tm_2d(&P.tm[TS_G], gg, SEQ, DM, ST_ROWS); tm_2d(&P.tm[TS_OUT], d_out, SEQ, DM, 16);
  P.x = (const bf16*)d_in[0]; P.b_sp = (const bf16*)d_in[8];
  fused_kernel<<<2 * NCLUSTER, 384, SMEM_BYTES, cudaStreamPerThread>>>(P);
}
```

```cpp
#include <cuda_runtime.h>
#include <cuda_bf16.h>
#include <cuda.h>
#include <stdint.h>
#include <stdio.h>

typedef __nv_bfloat16 bf16;

constexpr int SEQ = 2048, DM = 1024, NH = 32, HD = 4096, FF = 3584, FH = 1792;

__device__ __align__(1024) bf16 g_xn[SEQ * DM];
__device__ __align__(1024) bf16 g_q[SEQ * HD];
__device__ __align__(1024) bf16 g_o[SEQ * HD];
__device__ __align__(1024) bf16 g_z2[SEQ * FH];
__device__ __align__(1024) bf16 g_u[SEQ * FH];
__device__ __align__(1024) uint2 g_stats[SEQ * 8];
__device__ __align__(1024) bf16 g_g[SEQ * DM];
__device__ __align__(1024) bf16 g_sa[SEQ * DM];
constexpr int F_XN = 0;
constexpr int F_Z2 = 512;
constexpr int F_Q = 768;
constexpr int F_U = 1024;
constexpr int F_O = 1536;
constexpr int F_S = 2048;
constexpr int F_TOTAL = 2112;
__device__ __align__(1024) unsigned g_flags[F_TOTAL];
__device__ unsigned g_done;
__device__ unsigned g_epoch;

__device__ __forceinline__ uint32_t smem_u32(const void* p) { return (uint32_t)__cvta_generic_to_shared(p); }
__device__ __forceinline__ void mbar_init(uint32_t bar, uint32_t cnt) { asm volatile("mbarrier.init.shared::cta.b64 [%0], %1;" :: "r"(bar), "r"(cnt)); }
__device__ __forceinline__ void mbar_expect_tx(uint32_t bar, uint32_t bytes) { asm volatile("mbarrier.arrive.expect_tx.shared::cta.b64 _, [%0], %1;" :: "r"(bar), "r"(bytes) : "memory"); }
__device__ __forceinline__ void mbar_arrive(uint32_t bar) { asm volatile("mbarrier.arrive.shared::cta.b64 _, [%0];" :: "r"(bar) : "memory"); }
__device__ __forceinline__ void mbar_arrive_cta(uint32_t bar, uint32_t cta) {
  asm volatile("{\n.reg .b32 ra;\nmapa.shared::cluster.u32 ra, %0, %1;\nmbarrier.arrive.shared::cluster.b64 _, [ra];\n}" :: "r"(bar), "r"(cta) : "memory");
}
__device__ __forceinline__ bool mbar_test(uint32_t bar, uint32_t parity) {
  uint32_t ok;
  asm volatile("{\n.reg .pred P1;\nmbarrier.test_wait.parity.shared::cta.b64 P1, [%1], %2;\nselp.u32 %0, 1, 0, P1;\n}" : "=r"(ok) : "r"(bar), "r"(parity) : "memory");
  return ok;
}
constexpr uint32_t SPIN_LIMIT = 1u << 22;
__device__ __forceinline__ void trap_if(bool c) { asm volatile("{\n.reg .pred P;\nsetp.ne.u32 P, %0, 0;\n@P trap;\n}" :: "r"((uint32_t)c)); }
__device__ __forceinline__ void mbar_wait(uint32_t bar, uint32_t parity) {
  asm volatile("{\n.reg .pred P1;\n.reg .u32 n;\nmbarrier.try_wait.parity.shared::cta.b64 P1, [%0], %1;\n@P1 bra DONE;\nmov.u32 n, 0;\n"
               "LOOP:\nmbarrier.try_wait.parity.shared::cta.b64 P1, [%0], %1;\n@P1 bra DONE;\nadd.u32 n, n, 1;\nsetp.gt.u32 P1, n, %2;\n@P1 trap;\nbra LOOP;\nDONE:\n}"
               :: "r"(bar), "r"(parity), "n"(SPIN_LIMIT) : "memory");
}
__device__ __forceinline__ void mbar_spin(uint32_t bar, uint32_t parity) {
  asm volatile("{\n.reg .pred P1;\nLOOP:\nmbarrier.try_wait.parity.shared::cta.b64 P1, [%0], %1;\n@!P1 bra LOOP;\n}" :: "r"(bar), "r"(parity) : "memory");
}
__device__ __forceinline__ void mbar_wait_sleep(uint32_t bar, uint32_t parity, uint32_t ns) {
  uint32_t n = 0;
  while (!mbar_test(bar, parity)) { trap_if(++n > SPIN_LIMIT * 4); __nanosleep(ns); }
}
__device__ __forceinline__ void tma_load_2d(uint32_t dst, const CUtensorMap* tm, int c0, int c1, uint32_t bar) {
  asm volatile("cp.async.bulk.tensor.2d.shared::cluster.global.mbarrier::complete_tx::bytes [%0], [%1, {%3, %4}], [%2];"
    :: "r"(dst), "l"(tm), "r"(bar), "r"(c0), "r"(c1) : "memory");
}
__device__ __forceinline__ void tma_load_2d_mc(uint32_t dst, const CUtensorMap* tm, int c0, int c1, uint32_t bar) {
  asm volatile("cp.async.bulk.tensor.2d.shared::cluster.global.mbarrier::complete_tx::bytes.multicast::cluster [%0], [%1, {%3, %4}], [%2], %5;"
    :: "r"(dst), "l"(tm), "r"(bar), "r"(c0), "r"(c1), "h"((uint16_t)3) : "memory");
}
__device__ __forceinline__ void tma_prefetch_2d(const CUtensorMap* tm, int c0, int c1) {
  asm volatile("cp.async.bulk.prefetch.tensor.2d.L2.global [%0, {%1, %2}];" :: "l"(tm), "r"(c0), "r"(c1) : "memory");
}
__device__ __forceinline__ void tma_prefetch_3d(const CUtensorMap* tm, int c1, int c2) {
  asm volatile("cp.async.bulk.prefetch.tensor.3d.L2.global [%0, {%1, %2, %3}];" :: "l"(tm), "r"(0), "r"(c1), "r"(c2) : "memory");
}
__device__ __forceinline__ void tma_load_3d_mc(uint32_t dst, const CUtensorMap* tm, int c1, int c2, uint32_t bar) {
  asm volatile("cp.async.bulk.tensor.3d.shared::cluster.global.mbarrier::complete_tx::bytes.multicast::cluster [%0], [%1, {%3, %4, %5}], [%2], %6;"
    :: "r"(dst), "l"(tm), "r"(bar), "r"(0), "r"(c1), "r"(c2), "h"((uint16_t)3) : "memory");
}
__device__ __forceinline__ void tma_store_2d(const CUtensorMap* tm, uint32_t src, int c0, int c1) {
  asm volatile("cp.async.bulk.tensor.2d.global.shared::cta.bulk_group [%0, {%2, %3}], [%1];" :: "l"(tm), "r"(src), "r"(c0), "r"(c1) : "memory");
}
__device__ __forceinline__ void bulk_commit() { asm volatile("cp.async.bulk.commit_group;" ::: "memory"); }
template <int N> __device__ __forceinline__ void bulk_wait_read() { asm volatile("cp.async.bulk.wait_group.read %0;" :: "n"(N) : "memory"); }
template <int N> __device__ __forceinline__ void bulk_wait() { asm volatile("cp.async.bulk.wait_group %0;" :: "n"(N) : "memory"); }
__device__ __forceinline__ void fence_async_smem() { asm volatile("fence.proxy.async.shared::cta;" ::: "memory"); }
__device__ __forceinline__ void fence_async_global() { asm volatile("fence.proxy.async.global;" ::: "memory"); }
__device__ __forceinline__ void wgmma_fence() { asm volatile("wgmma.fence.sync.aligned;" ::: "memory"); }
__device__ __forceinline__ void wgmma_commit() { asm volatile("wgmma.commit_group.sync.aligned;" ::: "memory"); }
template <int N> __device__ __forceinline__ void wgmma_wait() { asm volatile("wgmma.wait_group.sync.aligned %0;" :: "n"(N) : "memory"); }
__device__ __forceinline__ uint64_t make_desc(uint32_t addr, uint32_t lbo, uint32_t sbo) {
  return (uint64_t)((addr & 0x3FFFF) >> 4) | ((uint64_t)(lbo >> 4) << 16) | ((uint64_t)(sbo >> 4) << 32) | (1ull << 62);
}
template <int N> __device__ __forceinline__ void fence_regs(float (&d)[N]) {
#pragma unroll
  for (int i = 0; i < N; i++) asm volatile("" : "+f"(d[i]) :: "memory");
}
template <int N> __device__ __forceinline__ void fence_regs(uint32_t (&d)[N]) {
#pragma unroll
  for (int i = 0; i < N; i++) asm volatile("" : "+r"(d[i]) :: "memory");
}
__device__ __forceinline__ void named_sync(int id) { asm volatile("bar.sync %0, 256;" :: "r"(id) : "memory"); }
__device__ __forceinline__ bool wg_any(bool w, bool v) {
  uint32_t r;
  asm volatile("{\n.reg .pred p, q;\nsetp.ne.u32 p, %1, 0;\nbar.red.or.pred q, %2, 128, p;\nselp.u32 %0, 1, 0, q;\n}" : "=r"(r) : "r"((uint32_t)v), "r"(w ? 4 : 3) : "memory");
  return __any_sync(0xffffffffu, r);
}
__device__ __forceinline__ int fresh_warp() { uint32_t t; asm volatile("mov.u32 %0, %%tid.x;" : "=r"(t)); return __shfl_sync(0xffffffffu, (int)(t >> 5) - 4, 0); }
__device__ __forceinline__ void cluster_sync_relaxed() { asm volatile("barrier.cluster.arrive.relaxed.aligned;\nbarrier.cluster.wait.aligned;" ::: "memory"); }
__device__ __forceinline__ unsigned ld_acquire(const unsigned* p) { unsigned v; asm volatile("ld.acquire.gpu.global.u32 %0, [%1];" : "=r"(v) : "l"(p) : "memory"); return v; }
__device__ __forceinline__ void red_release(unsigned* p, unsigned v) { asm volatile("red.release.gpu.global.add.u32 [%0], %1;" :: "l"(p), "r"(v) : "memory"); }
__device__ __forceinline__ void flag_wait(const unsigned* p, unsigned target) {
  uint32_t n = 0;
  while (ld_acquire(p) < target) { trap_if(++n > SPIN_LIMIT); __nanosleep(20); }
}
__device__ __forceinline__ void st_tagged(uint2* p, float a, float b, uint32_t tag) {
  asm volatile("{\n.reg .b64 x;\nmov.b64 x, {%1, %2};\nst.relaxed.gpu.global.b64 [%0], x;\n}" :: "l"(p),
               "r"((__float_as_uint(a) & ~63u) | (tag & 63u)), "r"((__float_as_uint(b) & ~63u) | (tag >> 6)) : "memory");
}
__device__ __forceinline__ uint4 ld_tagged2(const uint2* p) {
  uint4 v;
  asm volatile("{\n.reg .b64 x, y;\nld.relaxed.gpu.global.v2.b64 {x, y}, [%4];\nmov.b64 {%0, %1}, x;\nmov.b64 {%2, %3}, y;\n}" : "=r"(v.x), "=r"(v.y), "=r"(v.z), "=r"(v.w) : "l"(p) : "memory");
  return v;
}
__device__ __forceinline__ bool tag_ok(uint32_t a, uint32_t b, uint32_t tag) { return ((a & 63u) | ((b & 63u) << 6)) == tag; }
__device__ __forceinline__ float untag(uint32_t v) { return __uint_as_float(v & ~63u); }
__device__ __forceinline__ uint32_t pack_bf16(float lo, float hi) { uint32_t r; asm("cvt.rn.bf16x2.f32 %0, %1, %2;" : "=r"(r) : "f"(hi), "f"(lo)); return r; }
__device__ __forceinline__ uint32_t bf2_fma(uint32_t a, uint32_t b, uint32_t c) { uint32_t r; asm("fma.rn.bf16x2 %0, %1, %2, %3;" : "=r"(r) : "r"(a), "r"(b), "r"(c)); return r; }
__device__ __forceinline__ uint32_t bf2_mul(uint32_t a, uint32_t b) { uint32_t r; asm("mul.rn.bf16x2 %0, %1, %2;" : "=r"(r) : "r"(a), "r"(b)); return r; }
__device__ __forceinline__ uint32_t bf2_add(uint32_t a, uint32_t b) { uint32_t r; asm("add.rn.bf16x2 %0, %1, %2;" : "=r"(r) : "r"(a), "r"(b)); return r; }
constexpr uint32_t BF2_HALF = 0x3f003f00u;
__device__ __forceinline__ float bf_lo(uint32_t v) { return __uint_as_float(v << 16); }
__device__ __forceinline__ float bf_hi(uint32_t v) { return __uint_as_float(v & 0xffff0000u); }
__device__ __forceinline__ float ex2(float x) { float y; asm("ex2.approx.ftz.f32 %0, %1;" : "=f"(y) : "f"(x)); return y; }
__device__ __forceinline__ float tanh_fast(float x) { float y; asm("tanh.approx.f32 %0, %1;" : "=f"(y) : "f"(x)); return y; }
__device__ __forceinline__ void stmatrix_x4(uint32_t addr, uint32_t a, uint32_t b, uint32_t c, uint32_t d) {
  asm volatile("stmatrix.sync.aligned.m8n8.x4.shared.b16 [%0], {%1, %2, %3, %4};" :: "r"(addr), "r"(a), "r"(b), "r"(c), "r"(d) : "memory");
}
__device__ __forceinline__ void ldmatrix_x4(uint32_t addr, uint32_t& a, uint32_t& b, uint32_t& c, uint32_t& d) {
  asm volatile("ldmatrix.sync.aligned.m8n8.x4.shared.b16 {%0, %1, %2, %3}, [%4];" : "=r"(a), "=r"(b), "=r"(c), "=r"(d) : "r"(addr) : "memory");
}
__device__ __forceinline__ uint32_t lane_id() { uint32_t l; asm volatile("mov.u32 %0, %%laneid;" : "=r"(l)); return l; }
__device__ __forceinline__ bool elect_one() {
  uint32_t r;
  asm volatile("{\n.reg .pred P;\nelect.sync _|P, 0xffffffff;\nselp.u32 %0, 1, 0, P;\n}" : "=r"(r));
  return r;
}

__device__ __forceinline__ void wgmma_m64n128k16_ss_tb0(float (&d)[64], uint64_t da, uint64_t db, int scale_d) {
  asm volatile("{\n.reg .pred p;\nsetp.ne.b32 p, %66, 0;\n"
    "wgmma.mma_async.sync.aligned.m64n128k16.f32.bf16.bf16 "
    "{%0, %1, %2, %3, %4, %5, %6, %7, %8, %9, %10, %11, %12, %13, %14, %15, %16, %17, %18, %19, %20, %21, %22, %23, %24, %25, %26, %27, %28, %29, %30, %31, %32, %33, %34, %35, %36, %37, %38, %39, %40, %41, %42, %43, %44, %45, %46, %47, %48, %49, %50, %51, %52, %53, %54, %55, %56, %57, %58, %59, %60, %61, %62, %63}, "
    "%64, %65, p, 1, 1, 0, 0;\n}\n"
    : "+f"(d[0]), "+f"(d[1]), "+f"(d[2]), "+f"(d[3]), "+f"(d[4]), "+f"(d[5]), "+f"(d[6]), "+f"(d[7]), "+f"(d[8]), "+f"(d[9]), "+f"(d[10]), "+f"(d[11]), "+f"(d[12]), "+f"(d[13]), "+f"(d[14]), "+f"(d[15]), "+f"(d[16]), "+f"(d[17]), "+f"(d[18]), "+f"(d[19]), "+f"(d[20]), "+f"(d[21]), "+f"(d[22]), "+f"(d[23]), "+f"(d[24]), "+f"(d[25]), "+f"(d[26]), "+f"(d[27]), "+f"(d[28]), "+f"(d[29]), "+f"(d[30]), "+f"(d[31]), "+f"(d[32]), "+f"(d[33]), "+f"(d[34]), "+f"(d[35]), "+f"(d[36]), "+f"(d[37]), "+f"(d[38]), "+f"(d[39]), "+f"(d[40]), "+f"(d[41]), "+f"(d[42]), "+f"(d[43]), "+f"(d[44]), "+f"(d[45]), "+f"(d[46]), "+f"(d[47]), "+f"(d[48]), "+f"(d[49]), "+f"(d[50]), "+f"(d[51]), "+f"(d[52]), "+f"(d[53]), "+f"(d[54]), "+f"(d[55]), "+f"(d[56]), "+f"(d[57]), "+f"(d[58]), "+f"(d[59]), "+f"(d[60]), "+f"(d[61]), "+f"(d[62]), "+f"(d[63])
    : "l"(da), "l"(db), "r"(scale_d));
}
__device__ __forceinline__ void wgmma_m64n256k16_ss_tb1(float (&d)[128], uint64_t da, uint64_t db, int scale_d) {
  asm volatile("{\n.reg .pred p;\nsetp.ne.b32 p, %130, 0;\n"
    "wgmma.mma_async.sync.aligned.m64n256k16.f32.bf16.bf16 "
    "{%0, %1, %2, %3, %4, %5, %6, %7, %8, %9, %10, %11, %12, %13, %14, %15, %16, %17, %18, %19, %20, %21, %22, %23, %24, %25, %26, %27, %28, %29, %30, %31, %32, %33, %34, %35, %36, %37, %38, %39, %40, %41, %42, %43, %44, %45, %46, %47, %48, %49, %50, %51, %52, %53, %54, %55, %56, %57, %58, %59, %60, %61, %62, %63, %64, %65, %66, %67, %68, %69, %70, %71, %72, %73, %74, %75, %76, %77, %78, %79, %80, %81, %82, %83, %84, %85, %86, %87, %88, %89, %90, %91, %92, %93, %94, %95, %96, %97, %98, %99, %100, %101, %102, %103, %104, %105, %106, %107, %108, %109, %110, %111, %112, %113, %114, %115, %116, %117, %118, %119, %120, %121, %122, %123, %124, %125, %126, %127}, "
    "%128, %129, p, 1, 1, 0, 1;\n}\n"
    : "+f"(d[0]), "+f"(d[1]), "+f"(d[2]), "+f"(d[3]), "+f"(d[4]), "+f"(d[5]), "+f"(d[6]), "+f"(d[7]), "+f"(d[8]), "+f"(d[9]), "+f"(d[10]), "+f"(d[11]), "+f"(d[12]), "+f"(d[13]), "+f"(d[14]), "+f"(d[15]), "+f"(d[16]), "+f"(d[17]), "+f"(d[18]), "+f"(d[19]), "+f"(d[20]), "+f"(d[21]), "+f"(d[22]), "+f"(d[23]), "+f"(d[24]), "+f"(d[25]), "+f"(d[26]), "+f"(d[27]), "+f"(d[28]), "+f"(d[29]), "+f"(d[30]), "+f"(d[31]), "+f"(d[32]), "+f"(d[33]), "+f"(d[34]), "+f"(d[35]), "+f"(d[36]), "+f"(d[37]), "+f"(d[38]), "+f"(d[39]), "+f"(d[40]), "+f"(d[41]), "+f"(d[42]), "+f"(d[43]), "+f"(d[44]), "+f"(d[45]), "+f"(d[46]), "+f"(d[47]), "+f"(d[48]), "+f"(d[49]), "+f"(d[50]), "+f"(d[51]), "+f"(d[52]), "+f"(d[53]), "+f"(d[54]), "+f"(d[55]), "+f"(d[56]), "+f"(d[57]), "+f"(d[58]), "+f"(d[59]), "+f"(d[60]), "+f"(d[61]), "+f"(d[62]), "+f"(d[63]), "+f"(d[64]), "+f"(d[65]), "+f"(d[66]), "+f"(d[67]), "+f"(d[68]), "+f"(d[69]), "+f"(d[70]), "+f"(d[71]), "+f"(d[72]), "+f"(d[73]), "+f"(d[74]), "+f"(d[75]), "+f"(d[76]), "+f"(d[77]), "+f"(d[78]), "+f"(d[79]), "+f"(d[80]), "+f"(d[81]), "+f"(d[82]), "+f"(d[83]), "+f"(d[84]), "+f"(d[85]), "+f"(d[86]), "+f"(d[87]), "+f"(d[88]), "+f"(d[89]), "+f"(d[90]), "+f"(d[91]), "+f"(d[92]), "+f"(d[93]), "+f"(d[94]), "+f"(d[95]), "+f"(d[96]), "+f"(d[97]), "+f"(d[98]), "+f"(d[99]), "+f"(d[100]), "+f"(d[101]), "+f"(d[102]), "+f"(d[103]), "+f"(d[104]), "+f"(d[105]), "+f"(d[106]), "+f"(d[107]), "+f"(d[108]), "+f"(d[109]), "+f"(d[110]), "+f"(d[111]), "+f"(d[112]), "+f"(d[113]), "+f"(d[114]), "+f"(d[115]), "+f"(d[116]), "+f"(d[117]), "+f"(d[118]), "+f"(d[119]), "+f"(d[120]), "+f"(d[121]), "+f"(d[122]), "+f"(d[123]), "+f"(d[124]), "+f"(d[125]), "+f"(d[126]), "+f"(d[127])
    : "l"(da), "l"(db), "r"(scale_d));
}
__device__ __forceinline__ void wgmma_m64n128k16_rs_tb1(float (&d)[64], uint32_t a0, uint32_t a1, uint32_t a2, uint32_t a3, uint64_t db, int scale_d) {
  asm volatile("{\n.reg .pred p;\nsetp.ne.b32 p, %69, 0;\n"
    "wgmma.mma_async.sync.aligned.m64n128k16.f32.bf16.bf16 "
    "{%0, %1, %2, %3, %4, %5, %6, %7, %8, %9, %10, %11, %12, %13, %14, %15, %16, %17, %18, %19, %20, %21, %22, %23, %24, %25, %26, %27, %28, %29, %30, %31, %32, %33, %34, %35, %36, %37, %38, %39, %40, %41, %42, %43, %44, %45, %46, %47, %48, %49, %50, %51, %52, %53, %54, %55, %56, %57, %58, %59, %60, %61, %62, %63}, "
    "{%64, %65, %66, %67}, %68, p, 1, 1, 1;\n}\n"
    : "+f"(d[0]), "+f"(d[1]), "+f"(d[2]), "+f"(d[3]), "+f"(d[4]), "+f"(d[5]), "+f"(d[6]), "+f"(d[7]), "+f"(d[8]), "+f"(d[9]), "+f"(d[10]), "+f"(d[11]), "+f"(d[12]), "+f"(d[13]), "+f"(d[14]), "+f"(d[15]), "+f"(d[16]), "+f"(d[17]), "+f"(d[18]), "+f"(d[19]), "+f"(d[20]), "+f"(d[21]), "+f"(d[22]), "+f"(d[23]), "+f"(d[24]), "+f"(d[25]), "+f"(d[26]), "+f"(d[27]), "+f"(d[28]), "+f"(d[29]), "+f"(d[30]), "+f"(d[31]), "+f"(d[32]), "+f"(d[33]), "+f"(d[34]), "+f"(d[35]), "+f"(d[36]), "+f"(d[37]), "+f"(d[38]), "+f"(d[39]), "+f"(d[40]), "+f"(d[41]), "+f"(d[42]), "+f"(d[43]), "+f"(d[44]), "+f"(d[45]), "+f"(d[46]), "+f"(d[47]), "+f"(d[48]), "+f"(d[49]), "+f"(d[50]), "+f"(d[51]), "+f"(d[52]), "+f"(d[53]), "+f"(d[54]), "+f"(d[55]), "+f"(d[56]), "+f"(d[57]), "+f"(d[58]), "+f"(d[59]), "+f"(d[60]), "+f"(d[61]), "+f"(d[62]), "+f"(d[63])
    : "r"(a0), "r"(a1), "r"(a2), "r"(a3), "l"(db), "r"(scale_d));
}
__device__ __forceinline__ void wgmma_m64n128k16_ss_tb1(float (&d)[64], uint64_t da, uint64_t db, int scale_d) {
  asm volatile("{\n.reg .pred p;\nsetp.ne.b32 p, %66, 0;\n"
    "wgmma.mma_async.sync.aligned.m64n128k16.f32.bf16.bf16 "
    "{%0, %1, %2, %3, %4, %5, %6, %7, %8, %9, %10, %11, %12, %13, %14, %15, %16, %17, %18, %19, %20, %21, %22, %23, %24, %25, %26, %27, %28, %29, %30, %31, %32, %33, %34, %35, %36, %37, %38, %39, %40, %41, %42, %43, %44, %45, %46, %47, %48, %49, %50, %51, %52, %53, %54, %55, %56, %57, %58, %59, %60, %61, %62, %63}, "
    "%64, %65, p, 1, 1, 0, 1;\n}\n"
    : "+f"(d[0]), "+f"(d[1]), "+f"(d[2]), "+f"(d[3]), "+f"(d[4]), "+f"(d[5]), "+f"(d[6]), "+f"(d[7]), "+f"(d[8]), "+f"(d[9]), "+f"(d[10]), "+f"(d[11]), "+f"(d[12]), "+f"(d[13]), "+f"(d[14]), "+f"(d[15]), "+f"(d[16]), "+f"(d[17]), "+f"(d[18]), "+f"(d[19]), "+f"(d[20]), "+f"(d[21]), "+f"(d[22]), "+f"(d[23]), "+f"(d[24]), "+f"(d[25]), "+f"(d[26]), "+f"(d[27]), "+f"(d[28]), "+f"(d[29]), "+f"(d[30]), "+f"(d[31]), "+f"(d[32]), "+f"(d[33]), "+f"(d[34]), "+f"(d[35]), "+f"(d[36]), "+f"(d[37]), "+f"(d[38]), "+f"(d[39]), "+f"(d[40]), "+f"(d[41]), "+f"(d[42]), "+f"(d[43]), "+f"(d[44]), "+f"(d[45]), "+f"(d[46]), "+f"(d[47]), "+f"(d[48]), "+f"(d[49]), "+f"(d[50]), "+f"(d[51]), "+f"(d[52]), "+f"(d[53]), "+f"(d[54]), "+f"(d[55]), "+f"(d[56]), "+f"(d[57]), "+f"(d[58]), "+f"(d[59]), "+f"(d[60]), "+f"(d[61]), "+f"(d[62]), "+f"(d[63])
    : "l"(da), "l"(db), "r"(scale_d));
}


enum { TM_XN, TM_WSP, TM_U, TM_O, TM_Q, TM_X, TM_SA, TM_G, TM_K, TM_V, TM_WO64,
       TM_WIN, TM_WQ, TM_Z2, TM_WOUT, TM_WO, TS_Q, TS_O, TS_Z2, TS_U, TS_SA, TS_G, TS_OUT, TM_COUNT };
enum { T_Z2 = 0, T_Q = 1, T_U = 2, T_ATT = 3, T_SA = 4, T_FIN = 5, T_END = 7 };
constexpr int NCLUSTER = 66, MAXI = 14;
struct alignas(64) Params {
  const bf16* x;
  const bf16* b_sp;
  CUtensorMap tm[TM_COUNT];
  uint16_t items[NCLUSTER][MAXI];
};

constexpr uint32_t G_STAGE = 49152, G_A = 16384, KV_SLOT = 32768;
constexpr uint32_t OFF_Q1 = 163840, OFF_Q0 = 196608, OFF_BAR = 229376, OFF_LN = OFF_BAR + 256, SMEM_BYTES = OFF_LN + 1024;
constexpr uint32_t B_GF = 0, B_GE = 32, B_KF = 64, B_KE = 104, B_QF = 144, B_QE = 160, B_XF = 176, B_XR = 184, B_STG = 192, B_FREE = 200, B_GO = 208, B_LN = 216, B_TAG = 224, B_RDY = 228, B_PROG = 232, B_PUB = 248;
constexpr int SA_HEADS = 18;
constexpr int SW_NS = 40;
constexpr int ST_ROWS = 16;
constexpr int ST_FLY = 2;
constexpr int KV_PF = 4;
constexpr int FIN_PREP = 8;
constexpr int OWN_OFF = 8;
constexpr int ACT_REP = 32;
constexpr int Q_DELAY = 4;
constexpr int Q_GAP = 4;
constexpr int Z_DELAY = 3;
constexpr int SW_ATT = 800;
constexpr int OUT_PF = 8;
constexpr uint32_t OFF_ZQ = 2 * G_STAGE + G_A;
constexpr int SA_STEPS = 2 * SA_HEADS;
constexpr uint32_t FIN_SLOT0 = (0x0320u >> (4 * ((29 + SA_STEPS) & 3))) & 15;
constexpr float SM_C = 0.08838834764831845f * 1.4426950408889634f;
constexpr float GELU_A = 0.7978845608028654f, GELU_B = 0.7978845608028654f * 0.044715f;
constexpr float SM_LO = 1e-7f, SM_HI = 1e12f;
constexpr float SM_THR = 1024.f;


extern __shared__ __align__(1024) uint8_t smem_raw[];
__device__ __forceinline__ uint32_t smem_base() { return smem_u32(smem_raw); }

struct Ring { uint32_t s, ph; };
template <int N> __device__ __forceinline__ void ring_adv(Ring& r) { if (++r.s == N) { r.s = 0; r.ph ^= 1; } }

__device__ __forceinline__ int get_item(const Params& p, int i) {
  uint32_t b; asm volatile("mov.u32 %0, %%ctaid.x;" : "=r"(b));
  return p.items[b >> 1][i];
}
struct Cons {
  uint32_t sb;
  int warp;
  Ring g;
  uint32_t rot;
  uint32_t fph;
};

__device__ __forceinline__ void stage_acquire(const Cons& c) { mbar_spin(c.sb + OFF_BAR + B_FREE, c.fph); }
__device__ __forceinline__ void stage_commit(Cons& c) {
  __syncwarp();
  if (lane_id() == 0) mbar_arrive(c.sb + OFF_BAR + B_STG);
  c.fph ^= 1;
}

__device__ __forceinline__ void release_slot(const Cons& c, uint32_t bar) {
  if (lane_id() == 0 && (c.warp & 3) < 2) mbar_arrive_cta(bar, c.warp & 1);
}
constexpr uint64_t DESC_HI = (uint64_t)0x40000040u << 32;

template <bool FIRST> __device__ __forceinline__ void gemm_step(float (&acc)[128], Cons& c) {
  mbar_spin(c.sb + OFF_BAR + B_GF + 8 * c.g.s, c.g.ph);
  const uint32_t st = ((c.sb & 0x3FFFF) >> 4) + ((c.g.s + c.rot) & 3) * (G_STAGE >> 4);
  const uint32_t da = st + (c.warp >> 2) * 512 + (1u << 16), db = st + (G_A >> 4) + ((8192u >> 4) << 16);
  wgmma_fence();
#pragma unroll
  for (int kk = 0; kk < 4; kk++) wgmma_m64n256k16_ss_tb1(acc, DESC_HI | (da + kk * 2), DESC_HI | (db + kk * 128), !(FIRST && kk == 0));
  wgmma_commit();
}

template <int N> __device__ __forceinline__ void stage_chunks(uint32_t buf, uint32_t stride, const uint32_t* pk) {
  const uint32_t ln = lane_id();
  const uint32_t a = buf + ((ln & 15) << 7);
  const uint32_t x = ln & 7, hi = ln >> 4;
#pragma unroll
  for (int i = 0; i < 4 * N; i++) stmatrix_x4(a + (i >> 2) * stride + (((2 * (i & 3) + hi) ^ x) << 4), pk[4 * i], pk[4 * i + 1], pk[4 * i + 2], pk[4 * i + 3]);
}

__device__ __forceinline__ float act2_fn(float x, float a, float b) {
  return fmaf(x, tanh_fast(x * fmaf(x * x, b, a)), x);
}
__device__ __forceinline__ float quad_sum(float v) { v += __shfl_xor_sync(0xffffffffu, v, 1); v += __shfl_xor_sync(0xffffffffu, v, 2); return v; }
__device__ __forceinline__ float quad_max(float v) { v = fmaxf(v, __shfl_xor_sync(0xffffffffu, v, 1)); v = fmaxf(v, __shfl_xor_sync(0xffffffffu, v, 2)); return v; }

__device__ __forceinline__ uint32_t load_tag(const Cons& c) { uint32_t t; asm volatile("ld.volatile.shared.u32 %0, [%1];" : "=r"(t) : "r"(c.sb + OFF_BAR + B_TAG)); return t; }

struct Shadow {
  int act;
  int store;
};
__device__ __forceinline__ void rotate16(uint32_t (&h)[64]) {
#pragma unroll
  for (int i = 0; i < 16; i++)
    asm volatile("{\n.reg .b32 t;\nmov.b32 t, %0;\nmov.b32 %0, %1;\nmov.b32 %1, %2;\nmov.b32 %2, %3;\nmov.b32 %3, t;\n}" : "+r"(h[i]), "+r"(h[i + 16]), "+r"(h[i + 32]), "+r"(h[i + 48]));
}

template <int O>
__device__ __forceinline__ void act_block(uint32_t (&held)[64], float ca, float cb, bool first, float& u0, float& u1, float& s0, float& s1, float& q0, float& q1) {
#pragma unroll
  for (int i = O; i < O + 4; i += 2) {
    const float a0 = act2_fn(bf_lo(held[i]), ca, cb), a1 = act2_fn(bf_hi(held[i]), ca, cb);
    const float b0 = act2_fn(bf_lo(held[i + 1]), ca, cb), b1 = act2_fn(bf_hi(held[i + 1]), ca, cb);
    if (i == 0 && first) { u0 = a0; u1 = b0; }
    float d;
    d = a0 - u0; s0 += d; q0 = fmaf(d, d, q0); d = a1 - u0; s0 += d; q0 = fmaf(d, d, q0);
    d = b0 - u1; s1 += d; q1 = fmaf(d, d, q1); d = b1 - u1; s1 += d; q1 = fmaf(d, d, q1);
    held[i] = pack_bf16(a0, a1); held[i + 1] = pack_bf16(b0, b1);
  }
}

template <int O> __device__ __forceinline__ void stage_half(Cons& c, uint32_t (&held)[64], int mode) {
  if (mode == 2) {
    uint32_t a0, a1, r0, r1;
    const uint32_t la = c.sb + OFF_LN + (c.warp * 16 + (lane_id() >> 2)) * 8;
    mbar_spin(c.sb + OFF_BAR + B_LN, 0);
    asm volatile("ld.shared.v2.b32 {%0, %1}, [%2];" : "=r"(r0), "=r"(a0) : "r"(la));
    asm volatile("ld.shared.v2.b32 {%0, %1}, [%2];" : "=r"(r1), "=r"(a1) : "r"(la + 64));
#pragma unroll
    for (int i = O; i < O + 32; i += 2) { held[i] = bf2_mul(bf2_add(held[i], a0), r0); held[i + 1] = bf2_mul(bf2_add(held[i + 1], a1), r1); }
  }
  if (O == 0 && mode == 3) {
#pragma unroll
    for (int i = 0; i < 64; i++) held[i] = bf2_mul(held[i], BF2_HALF);
  }
  stage_acquire(c);
  stage_chunks<2>(c.sb + OFF_Q0 + c.warp * 2048, 16384, held + O);
  stage_commit(c);
}

__device__ __forceinline__ void gemm_seg(float (&acc)[128], uint32_t (&held)[64], Cons& c, const Params& p, Shadow& sh, int nsteps, bool hold) {
  const bool elected = lane_id() == 0 && (c.warp & 3) < 2;
  uint32_t rel;
  asm("mapa.shared::cluster.u32 %0, %1, %2;" : "=r"(rel) : "r"(c.sb + OFF_BAR + B_GE), "r"((uint32_t)(c.warp & 1)));
  gemm_step<true>(acc, c);
  uint32_t prev = c.g.s;
  ring_adv<4>(c.g);
  int k = 1;
#define G_STEP()                                                                                                       \
  { gemm_step<false>(acc, c);                                                                                          \
    wgmma_wait<1>();                                                                                                   \
    if (elected) asm volatile("mbarrier.arrive.shared::cluster.b64 _, [%0];" :: "r"(rel + 8 * prev) : "memory");       \
    prev = c.g.s; ring_adv<4>(c.g);                                                                                    \
    k++; }
  if (sh.act != 0) {
    float u0 = 0.f, u1 = 0.f, s0 = 0.f, s1 = 0.f, q0 = 0.f, q1 = 0.f;
    const float ca = sh.act == 3 ? 0.5f : GELU_A, cb = sh.act == 3 ? 0.f : GELU_B;
    const int rep = nsteps >= ACT_REP ? 2 : 1;
#define G_STEPS() { _Pragma("unroll 1") for (int r = 0; r < rep; r++) G_STEP() }
#pragma unroll 1
    while (true) {
      act_block<0>(held, ca, cb, k == 1, u0, u1, s0, s1, q0, q1);
      G_STEPS()
      act_block<4>(held, ca, cb, false, u0, u1, s0, s1, q0, q1);
      G_STEPS()
      act_block<8>(held, ca, cb, false, u0, u1, s0, s1, q0, q1);
      G_STEPS()
      act_block<12>(held, ca, cb, false, u0, u1, s0, s1, q0, q1);
      rotate16(held);
      if (k == 1 + 15 * rep) break;
      G_STEPS()
    }
    if (sh.act == 2) {
      const int zi = get_item(p, 0);
      const int ln = lane_id(), row0 = (((zi >> 5) & 31) * 2 + (blockIdx.x & 1)) * 128 + c.warp * 16 + (ln >> 2), ql = ln & 3;
      const float m0 = fmaf(s0, 1.f / 64, u0), m1 = fmaf(s1, 1.f / 64, u1);
      q0 -= s0 * s0 * (1.f / 64); q1 -= s1 * s1 * (1.f / 64);
      const float mu0 = quad_sum(m0) * 0.25f, mu1 = quad_sum(m1) * 0.25f;
      q0 = quad_sum(fmaf(64.f * (m0 - mu0), m0 - mu0, q0)); q1 = quad_sum(fmaf(64.f * (m1 - mu1), m1 - mu1, q1));
      if (ql < 2) st_tagged(&g_stats[(row0 + 8 * ql) * 8 + (zi & 31)], ql ? mu1 : mu0, ql ? q1 : q0, load_tag(c));
      if (ln == 0) mbar_arrive(c.sb + OFF_BAR + B_PUB);
    }
  }
  const int s0 = sh.store == 0 ? -9 : k + (sh.store == 2 ? Z_DELAY : (sh.store == 1 ? Q_DELAY : 1)), s1 = sh.store == 3 ? -9 : s0 + (sh.store == 1 ? Q_GAP : 3);
  hold = hold && k + 4 < nsteps;
  const int ksk = sh.store == 2 ? 3 : -1;
#pragma unroll 1
  while (k < nsteps) {
    G_STEP()
    if (k == ksk) ring_adv<4>(c.g);
    if (k == s0) stage_half<0>(c, held, sh.store);
    else if (k == s1) stage_half<32>(c, held, sh.store);
    else if (hold && k == nsteps - 2 && c.warp >= 4) named_sync(6);
  }
  if (hold && c.warp < 4) asm volatile("bar.arrive 6, 256;" ::: "memory");
  wgmma_wait<0>();
  fence_regs(acc);
  if (elected) asm volatile("mbarrier.arrive.shared::cluster.b64 _, [%0];" :: "r"(rel + 8 * prev) : "memory");
  sh.store = sh.act == 2 ? 2 : 0;
  sh.act = 0;
}

template <bool SUB> __device__ __forceinline__ void softmax_exp(const float (&S)[64], uint32_t (&P)[32], float m0, float m1, float& s0, float& s1) {
  float a0 = 0.f, a1 = 0.f, b0 = 0.f, b1 = 0.f;
#pragma unroll
  for (int j = 0; j < 16; j++) {
    const float p0 = ex2(SUB ? S[4 * j] - m0 : S[4 * j]), p1 = ex2(SUB ? S[4 * j + 1] - m0 : S[4 * j + 1]);
    const float p2 = ex2(SUB ? S[4 * j + 2] - m1 : S[4 * j + 2]), p3 = ex2(SUB ? S[4 * j + 3] - m1 : S[4 * j + 3]);
    a0 += p0; b0 += p1; a1 += p2; b1 += p3;
    P[2 * j] = pack_bf16(p0, p1); P[2 * j + 1] = pack_bf16(p2, p3);
  }
  s0 = a0 + b0; s1 = a1 + b1;
}
__device__ __forceinline__ void row_max(const float (&S)[64], float& x0, float& x1) {
  float a0 = fmaxf(S[0], S[1]), a1 = fmaxf(S[2], S[3]);
#pragma unroll
  for (int j = 1; j < 16; j++) { a0 = fmaxf(a0, fmaxf(S[4 * j], S[4 * j + 1])); a1 = fmaxf(a1, fmaxf(S[4 * j + 2], S[4 * j + 3])); }
  x0 = quad_max(a0); x1 = quad_max(a1);
}

__device__ __forceinline__ void issue_qk(float (&S)[64], uint32_t da, uint32_t db) {
#pragma unroll
  for (int kk = 0; kk < 8; kk++) {
    const uint32_t o = (kk >> 2) * 1024 + (kk & 3) * 2;
    wgmma_m64n128k16_ss_tb0(S, DESC_HI | (da + o), DESC_HI | (db + o), kk > 0);
  }
}
__device__ __forceinline__ void issue_pv(float (&O)[64], const uint32_t (&P)[32], uint32_t db, int acc) {
#pragma unroll
  for (int kk = 0; kk < 8; kk++) wgmma_m64n128k16_rs_tb1(O, P[4 * kk], P[4 * kk + 1], P[4 * kk + 2], P[4 * kk + 3], DESC_HI | (db + kk * 128), (acc || kk > 0));
}

__device__ __forceinline__ void att_pack(const float (&O)[64], uint32_t (&pk)[32], float i0, float i1) {
#pragma unroll
  for (int j = 0; j < 16; j++) {
    pk[2 * j] = pack_bf16(O[4 * j] * i0, O[4 * j + 1] * i0);
    pk[2 * j + 1] = pack_bf16(O[4 * j + 2] * i1, O[4 * j + 3] * i1);
  }
}
__device__ __forceinline__ void att_stage(Cons& c, const uint32_t (&pk)[32], uint32_t qbuf) {
  stage_chunks<2>(c.sb + (qbuf ? OFF_Q1 : OFF_Q0) + c.warp * 2048, 16384, pk);
  stage_commit(c);
}

#define ATT_ISSUE(PIN, ACC, PV)                                                                                        \
  wgmma_fence();                                                                                                       \
  issue_qk(S, qd, kd); wgmma_commit();                                                                                 \
  if (g > 1) release_slot(c, vrel);                                                                                    \
  vready = mbar_test(vbar, vph);                                                                                       \
  if (PV) {                                                                                                            \
    mbar_spin(vbar, vph);                                                                                              \
    wgmma_fence();                                                                                                     \
    issue_pv(O, PIN, vd, ACC); wgmma_commit();                                                                         \
  } else {                                                                                                             \
    asm volatile("wgmma.commit_group.sync.aligned; // empty" ::: "memory");                                            \
  }                                                                                                                    \
  krel = kbar + (B_KE - B_KF); vrel = vbar + (B_KE - B_KF);                                                            \
  g++;                                                                                                                 \
  if (g < total) { kd = kd0 + kv.s * (KV_SLOT >> 4); kbar = bars + B_KF + 8 * kv.s; kph = kv.ph; ring_adv<5>(kv); }    \
  vd = vd0 + kv.s * (KV_SLOT >> 4); vbar = bars + B_KF + 8 * kv.s; vph = kv.ph; ring_adv<5>(kv);

#define ATT_WAIT_S()                                                                                                   \
  wgmma_wait<1>();                                                                                                     \
  fence_regs(S);                                                                                                       \
  release_slot(c, krel);                                                                                               \
  if (c.warp == 2) asm volatile("st.volatile.shared.u32 [%0], %1;" :: "r"(bars + B_PROG), "r"(g) : "memory");

#define ATT_SOFTMAX(POUT, FIRST)                                                                                       \
  fresh = false;                                                                                                       \
  _Pragma("unroll 1")                                                                                                  \
  while (true) {                                                                                                       \
    if (__builtin_expect(fresh, 0)) {                                                                                  \
      float x0, x1;                                                                                                    \
      row_max(S, x0, x1);                                                                                              \
      if (FIRST) m0 = m1 = -1e38f;                                                                                     \
      x0 = fmaxf(x0, m0); x1 = fmaxf(x1, m1);                                                                          \
      f0 = ex2(m0 - x0); f1 = ex2(m1 - x1);                                                                            \
      m0 = x0; m1 = x1; l0 *= f0; l1 *= f1;                                                                            \
      zero = false;                                                                                                    \
    }                                                                                                                  \
    if (zero) {                                                                                                        \
      softmax_exp<false>(S, POUT, m0, m1, s0, s1);                                                                     \
      bad = !(s0 <= SM_HI && s1 <= SM_HI) || ((FIRST) && (s0 < SM_LO || s1 < SM_LO));                                  \
    } else {                                                                                                           \
      softmax_exp<true>(S, POUT, m0, m1, s0, s1);                                                                      \
      bad = !(s0 <= SM_THR && s1 <= SM_THR);                                                                           \
    }                                                                                                                  \
    kready = mbar_test(kbar, kph) && vready;                                                                           \
    slow = fresh || __any_sync(0xffffffffu, bad || !kready);                                                           \
    if (__builtin_expect(!slow, 1)) break;                                                                             \
    if (fresh || !__any_sync(0xffffffffu, bad)) break;                                                                 \
    fresh = true;                                                                                                      \
  }                                                                                                                    \
  l0 += s0; l1 += s1;                                                                                                  \
  wgmma_wait<0>(); fence_regs(O);

#define ATT_RESCALE()                                                                                                  \
  { _Pragma("unroll")                                                                                                  \
    for (int i = 0; i < 16; i++) { O[4 * i] *= f0; O[4 * i + 1] *= f0; O[4 * i + 2] *= f1; O[4 * i + 3] *= f1; } }

__device__ __forceinline__ void att_stagger(const Cons& c, int g) {
  if (c.warp >= 4)
    asm volatile("{\n.reg .pred p;\n.reg .s32 v;\nLOOP:\nld.volatile.shared.s32 v, [%0];\nsetp.le.s32 p, v, %1;\n@p bra LOOP;\n}" :: "r"(c.sb + OFF_BAR + B_PROG), "r"(g) : "memory");
}

__device__ __forceinline__ void att_run(Cons& c, const Params& p, int it, int n) {
  const uint32_t bars = c.sb + OFF_BAR;
  float S[64], O[64];
  uint32_t P0[32], P1[32];
#pragma unroll
  for (int i = 0; i < 64; i++) O[i] = 0.f;
#pragma unroll
  for (int i = 0; i < 32; i++) P0[i] = P1[i] = 0u;
  fence_regs(O); fence_regs(P0); fence_regs(P1);
  float m0 = 0.f, m1 = 0.f, l0 = 0.f, l1 = 0.f, f0 = 1.f, f1 = 1.f, s0, s1, pl0 = 0.f, pl1 = 0.f;
  const int total = 16 * n;
  int g = 0;
  Ring kv = {1, 0};
  uint32_t kbar = bars + B_KF, kph = 0, vbar = bars + B_KF, vph = 0, krel, vrel = 0;
  const uint32_t kd0 = (uint32_t)make_desc(c.sb, 16, 1024), vd0 = (uint32_t)make_desc(c.sb, 16384, 1024);
  uint32_t qd = kd0 + ((OFF_Q0 + (c.warp >> 2) * 8192) >> 4), kd = kd0, vd = vd0;
  bool fresh, kready, vready, bad, slow, zero = false;
  mbar_spin(bars + B_QF, 0);
  mbar_spin(bars + B_KF, 0);
  att_stagger(c, 0);
#pragma unroll 1
  while (true) {
    ATT_ISSUE(P1, 1, g > 0)
    const bool first = ((g - 1) & 15) == 0;
    if (first) { pl0 = l0; pl1 = l1; m0 = m1 = l0 = l1 = 0.f; zero = true; }
    ATT_WAIT_S()
    ATT_SOFTMAX(P0, first)
    if (__builtin_expect(slow || first, 0)) {
      if (first) {
        if (g > 1) {
          att_pack(O, P1, __fdividef(1.f, quad_sum(pl0)), __fdividef(1.f, quad_sum(pl1)));
          att_stage(c, P1, ((g >> 4) & 1) ^ 1);
        }
      } else if (fresh) ATT_RESCALE();
      mbar_spin(kbar, kph);
      if (__any_sync(0xffffffffu, !kready)) att_stagger(c, g);
    }
    ATT_ISSUE(P0, !first, true)
    ATT_WAIT_S()
    ATT_SOFTMAX(P1, false)
    if (__builtin_expect(slow || (g & 15) == 0, 0)) {
      if (fresh) ATT_RESCALE();
      if (g == total) break;
      mbar_spin(kbar, kph);
      if (__any_sync(0xffffffffu, !kready)) att_stagger(c, g);
      if ((g & 15) == 0) {
        const int t = g >> 4;
        const uint32_t qb = t & 1;
        mbar_spin(bars + B_QF + 8 * qb, (t >> 1) & 1);
        qd = kd0 + (((qb ? OFF_Q1 : OFF_Q0) + (c.warp >> 2) * 8192) >> 4);
      }
    }
  }
  release_slot(c, vrel);
  mbar_spin(vbar, vph);
  wgmma_fence();
  issue_pv(O, P1, vd, 1); wgmma_commit();
  pl0 = __fdividef(1.f, quad_sum(l0)); pl1 = __fdividef(1.f, quad_sum(l1));
  wgmma_wait<0>();
  fence_regs(O);
  release_slot(c, vbar + (B_KE - B_KF));
  att_pack(O, P0, pl0, pl1);
  if ((get_item(p, it + n) >> 12) == T_END) {
    const uint32_t buf = c.sb + (((n - 1) & 1) ? OFF_Q1 : OFF_Q0) + c.warp * 2048;
    stage_chunks<2>(buf, 16384, P0);
    fence_async_smem();
    __syncwarp();
    if (elect_one()) {
      const int im = get_item(p, it + n - 1), col = ((im >> 5) & 31) * 128, row = ((im & 31) * 2 + (blockIdx.x & 1)) * 128 + c.warp * 16;
      tma_store_2d(&p.tm[TS_O], buf, col, row); tma_store_2d(&p.tm[TS_O], buf + 16384, col + 64, row);
      bulk_commit();
      bulk_wait<0>();
      mbar_arrive(bars + B_STG);
    }
    __syncwarp();
  } else {
    att_stage(c, P0, (n - 1) & 1);
  }
}

__global__ void __cluster_dims__(2, 1, 1) __launch_bounds__(384, 1) fused_kernel(const __grid_constant__ Params p) {
  const uint32_t sb = smem_base();
  const uint32_t bars = sb + OFF_BAR;
  const int tid = threadIdx.x, lane = tid & 31;
  const int warp_id = __shfl_sync(0xffffffffu, tid >> 5, 0), wg = warp_id >> 2;
  const uint32_t rank = blockIdx.x & 1;
  const uint16_t* items = p.items[blockIdx.x >> 1];
  const int gw = blockIdx.x * 8 + warp_id - 4;
  uint4 xv[2][4];
  if (wg != 0 && gw < SEQ / 2) {
#pragma unroll
    for (int rr = 0; rr < 2; rr++)
#pragma unroll
      for (int i = 0; i < 4; i++) xv[rr][i] = __ldg(reinterpret_cast<const uint4*>(p.x + (size_t)(gw * 2 + rr) * DM) + i * 32 + lane);
  }
  if (warp_id == 1 && lane < TM_COUNT) asm volatile("prefetch.tensormap [%0];" :: "l"(&p.tm[lane]) : "memory");
  if (tid == 0) {
    for (int i = 0; i < 4; i++) { mbar_init(bars + B_GF + 8 * i, 1); mbar_init(bars + B_GE + 8 * i, 4); }
    for (int i = 0; i < 5; i++) { mbar_init(bars + B_KF + 8 * i, 1); mbar_init(bars + B_KE + 8 * i, 4); }
    for (int i = 0; i < 2; i++) { mbar_init(bars + B_QF + 8 * i, 1); mbar_init(bars + B_QE + 8 * i, 1); }
    mbar_init(bars + B_XF, 2); mbar_init(bars + B_XR, 2); mbar_init(bars + B_STG, 8); mbar_init(bars + B_FREE, 1); mbar_init(bars + B_GO, 1); mbar_init(bars + B_LN, 2); mbar_init(bars + B_PUB, 8);
    asm volatile("fence.mbarrier_init.release.cluster;" ::: "memory");
  }
  asm volatile("barrier.cluster.arrive.relaxed.aligned;" ::: "memory");

  if (wg == 0) {
    asm volatile("setmaxnreg.dec.sync.aligned.u32 40;");
    asm volatile("barrier.cluster.wait.acquire.aligned;" ::: "memory");
    if (warp_id >= 2 && (items[0] >> 12) == T_Z2) {
      if (lane == 0) mbar_wait_sleep(bars + B_PUB, 0, 100);
      __syncwarp();
      uint32_t tag;
      asm volatile("ld.volatile.shared.u32 %0, [%1];" : "=r"(tag) : "r"(bars + B_TAG));
      const int r = (warp_id - 2) * 64 + lane;
      const uint2* ps = &g_stats[((((items[0] >> 5) & 31) * 2 + rank) * 128 + r) * 8];
      uint4 t[2][4];
      uint32_t cnt = 0;
      while (true) {
        bool ok = true;
#pragma unroll
        for (int i = 0; i < 8; i++) t[i >> 2][i & 3] = ld_tagged2(ps + (i >> 2) * 256 + (i & 3) * 2);
#pragma unroll
        for (int i = 0; i < 8; i++) { const uint4 v = t[i >> 2][i & 3]; ok = ok && tag_ok(v.x, v.y, tag) && ((i & 3) == 3 || tag_ok(v.z, v.w, tag)); }
        if (__all_sync(0xffffffffu, ok)) break;
        trap_if(++cnt > SPIN_LIMIT);
        __nanosleep(100);
      }
#pragma unroll
      for (int y = 0; y < 2; y++) {
        float u = 0.f, v = 0.f;
#pragma unroll
        for (int i = 0; i < 7; i++) u += untag((i & 1) ? t[y][i >> 1].z : t[y][i >> 1].x);
        u *= 1.f / 7;
#pragma unroll
        for (int i = 0; i < 7; i++) {
          const float d = untag((i & 1) ? t[y][i >> 1].z : t[y][i >> 1].x) - u;
          v += fmaf(256.f * d, d, untag((i & 1) ? t[y][i >> 1].w : t[y][i >> 1].y));
        }
        const float rs = rsqrtf(fmaxf(v, 0.f) * (1.f / FH) + 4e-5f);
        asm volatile("st.shared.v2.b32 [%0], {%1, %2};" :: "r"(sb + OFF_LN + (r + 32 * y) * 8), "r"(pack_bf16(rs, rs)), "r"(pack_bf16(-u, -u)) : "memory");
      }
      __syncwarp();
      if (lane == 0) mbar_arrive(bars + B_LN);
      __syncwarp();
    }
    if (warp_id == 0) {
      trap_if(sb & 1023);
      Ring g = {0, 1};
      int it = 0;
      const uint32_t rot = (items[0] >> 12) == T_Z2 ? 3 : 0;
      uint32_t xph = 0;
      if (elect_one()) {
#pragma unroll 1
        for (;; it++) {
          const int item = items[it], type = item >> 12, b = item & 31, row = (((item >> 5) & 31) * 2 + rank) * 128;
          if (type >= T_ATT) break;
#pragma unroll 1
          for (int seg = 0; seg < (type == T_U ? 2 : 1); seg++) {
            const CUtensorMap* tA = &p.tm[seg ? TM_WSP : TM_XN];
            const CUtensorMap* tB = &p.tm[seg ? TM_Z2 : (type == T_Q ? TM_WQ : TM_WIN)];
            const int bchunk = b * 4 + (type == T_Z2 ? 28 : 0) + rank * 2;
            const unsigned* fl = seg ? &g_flags[F_Z2 + b * 32] : &g_flags[F_XN + (row >> 2)];
            const unsigned tgt = seg ? 16 : 128;
            int k = 0;
            if (it == 0 && seg == 0) {
              for (; k < 4; k++) {
                mbar_expect_tx(bars + B_GF + 8 * k, G_STAGE);
                tma_load_3d_mc(sb + ((k + rot) & 3) * G_STAGE + G_A + rank * 16384, tB, k * 64, bchunk, bars + B_GF + 8 * k);
              }
              g.ph ^= 1;
            }
            if (seg || type != T_U) { flag_wait(fl, tgt); fence_async_global(); }
            for (int x = 0; x < k; x++) tma_load_2d(sb + ((x + rot) & 3) * G_STAGE, tA, x * 64, row, bars + B_GF + 8 * x);
            if (it == 0) asm volatile("st.volatile.shared.v4.u32 [%0], {%1, %2, %2, %2};" :: "r"(bars + B_TAG), "r"(__ldcg(&g_epoch) % 4095u + 1), "r"(0) : "memory");
#pragma unroll 1
            for (; k < (seg ? 32 : 16); k++) {
              if (type == T_U && seg == 0) {
                if (k == 3) {
                  mbar_wait(bars + B_GE + 8 * g.s, g.ph);
                  mbar_arrive(bars + B_GF + 8 * g.s);
                  asm volatile("mbarrier.arrive.shared::cta.b64 _, [%0], 4;" :: "r"(bars + B_GE + 8 * g.s) : "memory");
                  ring_adv<4>(g);
                }
                if (k == 6) { mbar_wait(bars + B_XF, xph); xph ^= 1; }
              }
              mbar_wait(bars + B_GE + 8 * g.s, g.ph);
              const uint32_t st = sb + ((g.s + rot) & 3) * G_STAGE, fb = bars + B_GF + 8 * g.s;
              mbar_expect_tx(fb, G_STAGE);
              tma_load_2d(st, tA, k * 64, row, fb);
              tma_load_3d_mc(st + G_A + rank * 16384, tB, k * 64, bchunk, fb);
              ring_adv<4>(g);
            }
          }
        }
      }
      { const int e = __ffs(__ballot_sync(0xffffffffu, elect_one())) - 1; it = __shfl_sync(0xffffffffu, it, e); g.s = __shfl_sync(0xffffffffu, g.s, e); g.ph = __shfl_sync(0xffffffffu, g.ph, e); }
      const int n = ((items[it] >> 10) & 3) + 3;
      Ring kv = {0, 1};
      if (elect_one()) {
        int prow = 0;
        {
          const int im = items[it];
          tma_prefetch_2d(&p.tm[(im & 1) ? TM_V : TM_K], rank * 64, ((im >> 5) & 31) * SEQ + ((im & 7) >> 1) * 128);
        }
#pragma unroll 1
        for (int x = 0; x <= 32 * n; x++) {
          const int gb = x >> 1, t = gb >> 4;
          const int hrow = ((items[it + t] >> 5) & 31) * SEQ;
          const bool isv = (x & 1) || x == 32 * n;
          if (x != 1) {
            if (x == 0 || x == 2) mbar_wait(bars + B_GE + 8 * g.s + 4 * x, g.ph);
            if (x == 4) { mbar_wait(bars + B_XF, xph); xph ^= 1; }
            mbar_wait(bars + B_KE + 8 * kv.s, kv.ph);
            mbar_expect_tx(bars + B_KF + 8 * kv.s, KV_SLOT);
            tma_load_2d_mc(sb + kv.s * KV_SLOT + rank * 16384, &p.tm[isv ? TM_V : TM_K], rank * 64, isv ? prow : hrow + (gb & 15) * 128, bars + B_KF + 8 * kv.s);
            ring_adv<5>(kv);
          }
          {
            const int gp = gb + KV_PF, ip = items[it + (gp >> 4)];
            if (gp < 16 * n && ((gp ^ ip) & 7) == 0) tma_prefetch_2d(&p.tm[(x & 1) ? TM_V : TM_K], rank * 64, ((ip >> 5) & 31) * SEQ + (gp & 15) * 128);
          }
          if (x == 32 * n - 8) mbar_arrive(bars + B_GO);
          if (x & 1) prow = hrow + (gb & 15) * 128;
          if ((x & 31) == 11 && t + 1 < n) {
            const int tq = t + 1;
            const int im = items[it + tq], h = (im >> 5) & 31, m = (im & 31) * 2 + rank;
            const uint32_t qb = tq & 1;
            flag_wait(&g_flags[F_Q + m * 16 + (h >> 1)], 1);
            fence_async_global();
            mbar_wait(bars + B_QE + 8 * qb, ((tq - 1) >> 1) & 1);
            const uint32_t dst = sb + (qb ? OFF_Q1 : OFF_Q0), fb = bars + B_QF + 8 * qb;
            mbar_expect_tx(fb, 32768);
            tma_load_2d(dst, &p.tm[TM_Q], h * 128, m * 128, fb);
            tma_load_2d(dst + 16384, &p.tm[TM_Q], h * 128 + 64, m * 128, fb);
          }
        }
      }
      __syncwarp();
      it += n;
      uint32_t ready = 0;
      auto wait_head = [&](int h) {
        if ((ready >> h) & 1) return;
        uint32_t cnt = 0;
        while (true) {
          asm volatile("ld.acquire.cta.shared.u32 %0, [%1];" : "=r"(ready) : "r"(bars + B_RDY) : "memory");
          if ((ready >> h) & 1) break;
          trap_if(++cnt > SPIN_LIMIT * 8);
          __nanosleep(20);
        }
        fence_async_global();
      };
      int item = items[it];
      if ((item >> 12) == T_SA) {
        const int m = ((item >> 5) & 31) * 2 + rank, b = item & 31;
        Ring dr = kv;
        wait_head(0);
#pragma unroll 1
        for (int i = 0; i < 28 + SA_STEPS; i++) {
          {
            const bool so = i >= 28;
            const int k = so ? i - 28 : i;
            if (so) wait_head(k >> 1);
            if (elect_one()) {
              if (i < 4) { for (int x = 0; x < ((0x1022 >> (4 * i)) & 3); x++) { mbar_wait(bars + B_KE + 8 * dr.s, dr.ph); ring_adv<5>(dr); } }
              if (i == 2) { mbar_wait(bars + B_XF, xph); xph ^= 1; }
              mbar_wait(bars + B_GE + 8 * g.s, g.ph);
              const uint32_t st = sb + g.s * G_STAGE, fb = bars + B_GF + 8 * g.s;
              mbar_expect_tx(fb, G_STAGE);
              tma_load_2d(st, &p.tm[so ? TM_O : TM_U], k * 64, m * 128, fb);
              tma_load_3d_mc(st + G_A + rank * 16384, &p.tm[so ? TM_WO : TM_WOUT], k * 64, b * 4 + rank * 2, fb);
            }
            ring_adv<4>(g);
          }
          const int ip = i + OUT_PF;
          if (ip < 28 + SA_STEPS && elect_one()) {
            const bool so = ip >= 28;
            const int k = so ? ip - 28 : ip;
            if ((ip & 3) == b && (!so || ((ready >> (k >> 1)) & 1))) tma_prefetch_2d(&p.tm[so ? TM_O : TM_U], k * 64, m * 128);
            if ((ip & 7) == (m >> 1)) tma_prefetch_3d(&p.tm[so ? TM_WO : TM_WOUT], k * 64, b * 4 + rank * 2);
          }
          __syncwarp();
        }
        item = items[++it];
      }
      if ((item >> 12) == T_FIN) {
        const bool own = item & 4;
        const int m = ((item >> 5) & 31) * 2 + rank, col = (item & 3) * 256 + (own ? 128 : 0);
        uint32_t ps = own ? FIN_SLOT0 : kv.s;
#pragma unroll 1
        for (int i = SA_STEPS; i <= 2 * NH; i++) {
          const bool extra = i == 2 * NH - FIN_PREP;
          if (extra && own) continue;
          const int k = i > 2 * NH - FIN_PREP ? i - 1 : i;
          if (!extra) wait_head(k >> 1);
          if (elect_one()) {
            if (i == SA_STEPS) {
              for (int y = k; y < k + 4; y++) if ((ready >> (y >> 1)) & 1) tma_prefetch_2d(&p.tm[TM_O], y * 64, m * 128);
            }
            if (own && i < SA_STEPS + 5) {
              const uint32_t s0 = (0x22100u >> (4 * ps)) & 3, s1 = (0x32110u >> (4 * ps)) & 3;
              mbar_wait(bars + B_GE + 8 * s0, g.ph ^ (s0 < g.s)); mbar_wait(bars + B_GE + 8 * s1, g.ph ^ (s1 < g.s));
            }
            if (extra) { flag_wait(&g_flags[F_S + m * 4 + (item & 3)], 2); fence_async_global(); }
            mbar_wait(bars + B_KE + 8 * kv.s, kv.ph);
            const uint32_t dst = sb + ps * KV_SLOT, fb = bars + B_KF + 8 * kv.s;
            if (++ps == 5) ps = 0;
            mbar_expect_tx(fb, KV_SLOT);
            if (!extra) {
              tma_load_2d(dst, &p.tm[TM_O], k * 64, m * 128, fb);
              tma_load_2d_mc(dst + 16384 + rank * 8192, &p.tm[TM_WO64], col + rank * 64, k * 64, fb);
            } else {
              tma_load_2d(dst, &p.tm[TM_SA], col, m * 128, fb);
              tma_load_2d(dst + 16384, &p.tm[TM_SA], col + 64, m * 128, fb);
            }
            ring_adv<5>(kv);
          }
          __syncwarp();
        }
      }
      unsigned last = 0;
      if (lane == 0 && (item >> 12) == T_FIN) mbar_wait_sleep(bars + B_XR, 0, 100);
      if (lane == 0) { __threadfence(); last = atomicInc(&g_done, gridDim.x - 1) == gridDim.x - 1; }
      last = __shfl_sync(0xffffffffu, last, 0);
      if (last) {
        for (int i = lane; i < F_TOTAL / 4; i += 32) reinterpret_cast<uint4*>(g_flags)[i] = make_uint4(0, 0, 0, 0);
        if (lane == 0) g_epoch = g_epoch + 1;
      }
    } else if (warp_id == 1) {
      if (elect_one()) {
        uint32_t ph = 0;
        int t = 0;
        unsigned* fq = nullptr;
        const bool z = (items[0] >> 12) == T_Z2;
#pragma unroll 1
        for (int it = 0;; it++) {
          const int ii = (z && it < 2) ? it ^ 1 : it;
          const int item = items[ii], type = item >> 12, a = (item >> 5) & 31, b = item & 31;
          if (type == T_END) break;
          const int nt = items[ii + 1] >> 12;
          int row = (a * 2 + rank) * 128, col = b * 256;
          unsigned* f = &g_flags[F_S + (a * 2 + rank) * 4 + b];
          int tm = TS_G, npair = 2;
          bool quad = false;
          uint32_t src = sb + OFF_Q0;
          if (type == T_Z2) { tm = TS_Z2; f = &g_flags[F_Z2 + b * 32]; }
          else if (type == T_Q) { tm = TS_Q; f = &g_flags[F_Q + (a * 2 + rank) * 16 + b]; if (z || nt >= T_ATT) { npair = 0; quad = true; } }
          else if (type == T_U) { tm = TS_U; f = &g_flags[F_U + (a * 2 + rank) * 32]; npair = 0; quad = true; }
          else if (type == T_ATT) { tm = TS_O; f = &g_flags[F_O + (b * 2 + rank) * 32 + a]; npair = 1; row = (b * 2 + rank) * 128; col = a * 128; if (t & 1) src = sb + OFF_Q1; }
          else if (type == T_FIN) npair = 1;
          auto load_fin = [&](int fi, int tmi, uint32_t qb) {
            const int fc = (fi & 3) * 256 + ((fi & 4) ? 128 : 0), fr = (((fi >> 5) & 31) * 2 + rank) * 128;
            mbar_expect_tx(bars + B_QF + 8 * qb, 32768);
            tma_load_2d(sb + (qb ? OFF_Q1 : OFF_Q0), &p.tm[tmi], fc, fr, bars + B_QF + 8 * qb);
            tma_load_2d(sb + (qb ? OFF_Q1 : OFF_Q0) + 16384, &p.tm[tmi], fc + 64, fr, bars + B_QF + 8 * qb);
          };
          if (type == T_ATT && nt == T_FIN) load_fin(items[ii + 1], TM_X, (t & 1) ^ 1);
          if (type == T_FIN) {
            if (!(item & 4)) { flag_wait(&g_flags[F_S + (a * 2 + rank) * 4 + (b & 3)], 1); fence_async_global(); load_fin(item, TM_G, (t & 1) ^ 1); }
            mbar_arrive(bars + B_XR);
          }
#pragma unroll 1
          for (int op = 0; op < npair + quad; op++) {
            const bool q = op == npair;
            const int c0 = (q || type == T_SA) ? col : col + op * 128;
            mbar_wait_sleep(bars + B_STG, ph, (type == T_ATT && nt == T_ATT) ? SW_ATT : SW_NS);
            if (type == T_FIN) break;
            ph ^= 1;
            fence_async_smem();
            if (type == T_SA && op == 1) { tm = TS_SA; load_fin(items[ii + 1], TM_X, 1); }
            int c1 = c0;
            const bool pre = q && nt == T_ATT;
            if (pre) {
              const CUtensorMap* tb = &p.tm[type == T_U ? TM_U : TM_Q];
              tma_store_2d(tb, sb + 2 * G_STAGE, c0, row);
              tma_store_2d(tb, sb + 3 * G_STAGE, c0 + 64, row);
              bulk_commit();
              bulk_wait_read<0>();
              mbar_arrive_cta(bars + B_XF, 0); mbar_arrive_cta(bars + B_XF, 1);
              src = sb + OFF_Q1; c1 += 128;
            }
#pragma unroll 1
            for (int y = 0; y < ((q && !pre) ? 2 : 1); y++) {
              if (nt != T_END) {
#pragma unroll 1
                for (int r = 0; r < 256; r += ST_ROWS) {
                  tma_store_2d(&p.tm[tm], src + r * 128, c1 + (r >> 7) * 64, row + (r & 127));
                  bulk_commit();
                  bulk_wait_read<ST_FLY>();
                }
              }
              bulk_wait_read<0>();
              if (y == 0) mbar_arrive(bars + B_FREE);
              else { mbar_arrive_cta(bars + B_XF, 0); mbar_arrive_cta(bars + B_XF, 1); }
              if (q) { src = sb + OFF_ZQ; c1 += 128; }
            }
            if (type == T_ATT && (t & 1) && (nt == T_SA || (items[ii + 2] >> 12) == T_SA)) { mbar_arrive_cta(bars + B_XF, 0); mbar_arrive_cta(bars + B_XF, 1); }
            if (type == T_ATT) mbar_arrive(bars + B_QE + 8 * (t & 1));
            else if (nt == T_ATT) mbar_arrive(bars + B_QE + 8);
            if (z && it == 0) { fq = f; continue; }
            if (op + 1 >= npair || type == T_SA) {
              bulk_wait<0>();
              red_release(f, 1);
              if (type == T_Z2) red_release(fq, 1);
            }
          }
          if (type == T_ATT) t++;
          else if (t == 0 && (items[it + 1] >> 12) < T_ATT && (items[it + 2] >> 12) == T_ATT) {
            const int im = items[it + 2], h = (im >> 5) & 31, m = (im & 31) * 2 + rank;
            flag_wait(&g_flags[F_Q + m * 16 + (h >> 1)], 1);
            fence_async_global();
            mbar_expect_tx(bars + B_QF, 32768);
            tma_load_2d(sb + OFF_Q0, &p.tm[TM_Q], h * 128, m * 128, bars + B_QF);
            tma_load_2d(sb + OFF_Q0 + 16384, &p.tm[TM_Q], h * 128 + 64, m * 128, bars + B_QF);
          }
        }
      }
      __syncwarp();
    } else if (warp_id == 2) {
      int it = 0;
      while ((items[it] >> 12) <= T_ATT) it++;
      if ((items[it] >> 12) != T_END) {
        const bool sa = (items[it] >> 12) == T_SA;
        const int m = ((items[it] >> 5) & 31) * 2 + rank;
        if (lane == 0) {
          mbar_wait_sleep(bars + B_GO, 0, 500);
          if (sa) {
            const int b = items[it] & 3;
            flag_wait(&g_flags[F_U + m * 32], 7);
            fence_async_global();
            for (int y = b; y < OUT_PF; y += 4) tma_prefetch_2d(&p.tm[TM_U], y * 64, m * 128);
            tma_prefetch_3d(&p.tm[TM_WOUT], (m >> 1) * 64, b * 4 + rank * 2);
          }
          if (!sa) for (int y = m * 4 + (items[it] & 3); y < 16 * (NH - SA_HEADS); y += 64) tma_prefetch_3d(&p.tm[TM_WO], (2 * SA_HEADS + (y >> 3)) * 64, (y & 7) * 2);
        }
        __syncwarp();
        uint32_t cnt = 0;
        while (true) {
          const uint32_t r = __ballot_sync(0xffffffffu, ld_acquire(&g_flags[F_O + m * 32 + lane]) != 0);
          if (lane == 0) asm volatile("st.release.cta.shared.u32 [%0], %1;" :: "r"(bars + B_RDY), "r"(r) : "memory");
          if (r == ~0u) break;
          trap_if(++cnt > SPIN_LIMIT);
          __nanosleep(r >> 28 ? 20 : 300);
        }
        if (lane == 0) mbar_arrive(bars + B_XR);
      }
      __syncwarp();
    }
    cluster_sync_relaxed();
  } else {
    Cons c;
    c.sb = sb; c.warp = warp_id - 4; c.g = {0, 0}; c.fph = 1; c.rot = (get_item(p, 0) >> 12) == T_Z2 ? 3 : 0;
    if (gw < SEQ / 2) {
      float f[2][32], rs[2];
#pragma unroll
      for (int rr = 0; rr < 2; rr++) {
#pragma unroll
        for (int i = 0; i < 4; i++) {
          const uint4 v = xv[rr][i];
          f[rr][8 * i + 0] = bf_lo(v.x); f[rr][8 * i + 1] = bf_hi(v.x); f[rr][8 * i + 2] = bf_lo(v.y); f[rr][8 * i + 3] = bf_hi(v.y);
          f[rr][8 * i + 4] = bf_lo(v.z); f[rr][8 * i + 5] = bf_hi(v.z); f[rr][8 * i + 6] = bf_lo(v.w); f[rr][8 * i + 7] = bf_hi(v.w);
        }
        float s = 0.f;
#pragma unroll
        for (int i = 0; i < 32; i++) s += f[rr][i];
#pragma unroll
        for (int o = 16; o; o >>= 1) s += __shfl_xor_sync(0xffffffffu, s, o);
        const float mean = s * (1.f / DM);
        float q = 0.f;
#pragma unroll
        for (int i = 0; i < 32; i++) { f[rr][i] -= mean; q = fmaf(f[rr][i], f[rr][i], q); }
#pragma unroll
        for (int o = 16; o; o >>= 1) q += __shfl_xor_sync(0xffffffffu, q, o);
        rs[rr] = rsqrtf(q * (1.f / DM) + 1e-5f);
      }
      uint4* dst = reinterpret_cast<uint4*>(g_xn + (size_t)gw * 2 * DM) + lane;
#pragma unroll
      for (int rr = 0; rr < 2; rr++) {
        const float r = rs[rr];
#pragma unroll
        for (int i = 0; i < 4; i++) {
          const float* y = &f[rr][8 * i];
          dst[rr * 128 + i * 32] = make_uint4(pack_bf16(y[0] * r, y[1] * r), pack_bf16(y[2] * r, y[3] * r), pack_bf16(y[4] * r, y[5] * r), pack_bf16(y[6] * r, y[7] * r));
        }
      }
      named_sync(7);
      if (tid == 128) red_release(&g_flags[F_XN + (gw >> 6) * 32], 16);
    }
    asm volatile("setmaxnreg.inc.sync.aligned.u32 232;");
    asm volatile("barrier.cluster.wait.acquire.aligned;" ::: "memory");
    int natt = 0;
    int it = 0;
    uint32_t held[64];
#pragma unroll
    for (int i = 0; i < 64; i++) held[i] = 0u;
    Shadow sh = {0, 0};
    float facc[64];
#pragma unroll 1
    while (true) {
      const int item = get_item(p, it), type = item >> 12, a = (item >> 5) & 31;
      c.warp = fresh_warp();
      if (type == T_ATT) {
        const int n = ((item >> 10) & 3) + 3;
        att_run(c, p, it, n);
#pragma unroll
        for (int i = 0; i < 64; i++) held[i] = 0u;
        natt = n;
        it += n;
        c.rot = 0;
        if ((get_item(p, it) >> 12) == T_SA) continue;
#pragma unroll
        for (int i = 0; i < 64; i++) facc[i] = 0.f;
        break;
      }
      float acc[128];
      const bool sa = type == T_SA;
      bool more = type >= T_U;
      int nsteps = sa ? 28 : 16;
      const bool direct = sh.act == 2 || (get_item(p, it + 1) >> 12) >= T_ATT;
      uint32_t bias0 = 0, bias1 = 0;
#pragma unroll 1
      while (true) {
        gemm_seg(acc, held, c, p, sh, nsteps, more || !direct || sa);
        if (type == T_Q) {
#pragma unroll
          for (int i = 0; i < 128; i++) acc[i] *= SM_C;
        }
        if (!more && direct) break;
#pragma unroll
        for (int i = 0; i < 64; i++) held[i] = pack_bf16(acc[2 * i], acc[2 * i + 1]);
        if (!more) break;
        more = false;
        nsteps = sa ? SA_STEPS : 32;
        sh.act = sa ? 3 : 1;
        if (sa) {
          sh.store = 3;
        } else {
          const int row0 = (a * 2 + rank) * 128 + c.warp * 16 + (lane_id() >> 2);
          asm volatile("ld.global.nc.u16 %0, [%1];" : "=r"(bias0) : "l"(p.b_sp + row0));
          asm volatile("ld.global.nc.u16 %0, [%1];" : "=r"(bias1) : "l"(p.b_sp + row0 + 8));
        }
      }
      c.warp = fresh_warp();
      if (direct) {
        const bool pre = !sa && sh.store != 2;
        const uint32_t hb0 = bf2_mul(bias0 * 0x10001u, BF2_HALF), hb1 = bf2_mul(bias1 * 0x10001u, BF2_HALF);
        stage_acquire(c);
#pragma unroll
        for (int h = 0; h < 2; h++) {
          uint32_t pk[32];
#pragma unroll
          for (int i = 0; i < 32; i++) pk[i] = pack_bf16(acc[64 * h + 2 * i], acc[64 * h + 2 * i + 1]);
          if (type == T_U) {
#pragma unroll
            for (int i = 0; i < 32; i++) pk[i] = bf2_mul(bf2_fma(pk[i], BF2_HALF, (i & 1) ? hb1 : hb0), held[32 * h + i]);
          }
          if (h) named_sync(5);
          stage_chunks<2>(sb + (h ? (pre ? OFF_Q1 : OFF_ZQ) : (pre ? 2 * G_STAGE : OFF_Q0)) + c.warp * 2048, (!h && pre) ? G_STAGE : 16384, pk);
          if (sa) break;
        }
        stage_commit(c);
        if (sa) {
#pragma unroll
          for (int i = 0; i < 64; i++) facc[i] = acc[64 + i];
          it++;
          break;
        }
      } else if (type == T_Q) {
        sh.store = 1;
      } else {
        sh.act = 2;
      }
      it++;
    }
    const int fin = get_item(p, it);
    if ((fin >> 12) == T_FIN) {
      c.warp = fresh_warp();
      const bool own = fin & 4;
      Ring kv = {(uint32_t)(32 * natt) % 5, ((uint32_t)(32 * natt) / 5) & 1};
      uint32_t prev = 0, ps = own ? FIN_SLOT0 : kv.s;
      fence_regs(facc);
      auto fin_steps = [&](int k0, int k1) {
#pragma unroll 1
        for (int k = k0; k < k1; k++) {
          mbar_spin(bars + B_KF + 8 * kv.s, kv.ph);
          const uint32_t st = ((c.sb & 0x3FFFF) >> 4) + ps * (KV_SLOT >> 4);
          if (++ps == 5) ps = 0;
          const uint32_t da = st + (c.warp >> 2) * 512 + (1u << 16), db = st + 1024 + ((8192u >> 4) << 16);
          wgmma_fence();
#pragma unroll
          for (int kk = 0; kk < 4; kk++) wgmma_m64n128k16_ss_tb1(facc, DESC_HI | (da + kk * 2), DESC_HI | (db + kk * 128), 1);
          wgmma_commit();
          wgmma_wait<1>();
          if (k > SA_STEPS) release_slot(c, prev);
          prev = bars + B_KE + 8 * kv.s;
          ring_adv<5>(kv);
        }
      };
      const int kp = (own && ((fin >> 5) & 31) == 7) ? SA_STEPS + 5 : 2 * NH - FIN_PREP - (own ? OWN_OFF : 0);
      fin_steps(SA_STEPS, kp);
      const uint32_t ln = lane_id(), xb = own ? 1 : natt & 1;
      const uint32_t lo = c.warp * 2048 + ((ln & 15) << 7);
      uint32_t xs[32];
      auto load_tile = [&](uint32_t base, uint32_t* d) {
#pragma unroll
        for (int i = 0; i < 8; i++) ldmatrix_x4(base + lo + (i >> 2) * 16384 + (((2 * (i & 3) + (ln >> 4)) ^ (ln & 7)) << 4), d[4 * i], d[4 * i + 1], d[4 * i + 2], d[4 * i + 3]);
      };
      const uint32_t xa = sb + (xb ? OFF_Q1 : OFF_Q0);
      mbar_spin(bars + B_QF + 8 * xb, ((natt + 1 - xb) >> 1) & 1);
      load_tile(xa, xs);
      if (!own) {
        mbar_spin(bars + B_QF + 8 * (xb ^ 1), ((natt + xb) >> 1) & 1);
        load_tile(sb + (xb ? OFF_Q0 : OFF_Q1), held + 32);
      }
      float gf[64], rf[64];
#pragma unroll
      for (int i = 0; i < 32; i++) { gf[2 * i] = bf_lo(held[32 + i]); gf[2 * i + 1] = bf_hi(held[32 + i]); rf[2 * i] = bf_lo(xs[i]); rf[2 * i + 1] = bf_hi(xs[i]); }
      if (!own) {
        mbar_spin(bars + B_KF + 8 * kv.s, kv.ph);
#pragma unroll
        for (int i = 0; i < 8; i++) {
          uint32_t t[4];
          ldmatrix_x4(sb + ps * KV_SLOT + lo + (i >> 2) * 16384 + (((2 * (i & 3) + (ln >> 4)) ^ (ln & 7)) << 4), t[0], t[1], t[2], t[3]);
#pragma unroll
          for (int y = 0; y < 4; y++) {
            rf[8 * i + 2 * y] = fmaf(bf_lo(t[y]), gf[8 * i + 2 * y], rf[8 * i + 2 * y]);
            rf[8 * i + 2 * y + 1] = fmaf(bf_hi(t[y]), gf[8 * i + 2 * y + 1], rf[8 * i + 2 * y + 1]);
          }
        }
        wg_any(c.warp >= 4, false);
        release_slot(c, bars + B_KE + 8 * kv.s);
        if (++ps == 5) ps = 0;
        ring_adv<5>(kv);
      }
      fence_regs(gf); fence_regs(rf);
      fin_steps(kp, 2 * NH);
      wgmma_wait<0>();
      fence_regs(facc);
#pragma unroll
      for (int i = 0; i < 32; i++) xs[i] = pack_bf16(fmaf(facc[2 * i], gf[2 * i], rf[2 * i]), fmaf(facc[2 * i + 1], gf[2 * i + 1], rf[2 * i + 1]));
      __syncwarp();
      stage_chunks<2>(xa + c.warp * 2048, 16384, xs);
      fence_async_smem();
      __syncwarp();
      if (elect_one()) {
        const int col = (fin & 3) * 256 + (own ? 128 : 0), row = (((fin >> 5) & 31) * 2 + rank) * 128 + c.warp * 16;
        tma_store_2d(&p.tm[TS_OUT], xa + c.warp * 2048, col, row);
        tma_store_2d(&p.tm[TS_OUT], xa + c.warp * 2048 + 16384, col + 64, row);
        bulk_commit();
        mbar_arrive(bars + B_STG);
        bulk_wait_read<0>();
      }
    }
    __syncwarp();
    cluster_sync_relaxed();
  }
}

typedef CUresult (*PFN_encodeTiled)(CUtensorMap*, CUtensorMapDataType, cuuint32_t, void*, const cuuint64_t*, const cuuint64_t*, const cuuint32_t*, const cuuint32_t*,
                                    CUtensorMapInterleave, CUtensorMapSwizzle, CUtensorMapL2promotion, CUtensorMapFloatOOBfill);
static PFN_encodeTiled s_encode = nullptr;
static void tm_2d(CUtensorMap* tm, const void* ptr, uint64_t rows, uint64_t cols, uint32_t box_rows) {
  cuuint64_t dims[2] = {cols, rows}; cuuint64_t strides[1] = {cols * 2}; cuuint32_t box[2] = {64, box_rows}; cuuint32_t es[2] = {1, 1};
  CUresult r = s_encode(tm, CU_TENSOR_MAP_DATA_TYPE_BFLOAT16, 2, (void*)ptr, dims, strides, box, es, CU_TENSOR_MAP_INTERLEAVE_NONE,
                        CU_TENSOR_MAP_SWIZZLE_128B, CU_TENSOR_MAP_L2_PROMOTION_L2_128B, CU_TENSOR_MAP_FLOAT_OOB_FILL_NONE);
  if (r != CUDA_SUCCESS) fprintf(stderr, "tensor map encode failed (%d)\n", (int)r);
}
static void tm_3d(CUtensorMap* tm, const void* ptr, uint64_t rows, uint64_t cols) {
  cuuint64_t dims[3] = {64, rows, cols / 64}; cuuint64_t strides[2] = {cols * 2, 128}; cuuint32_t box[3] = {64, 64, 2}; cuuint32_t es[3] = {1, 1, 1};
  CUresult r = s_encode(tm, CU_TENSOR_MAP_DATA_TYPE_BFLOAT16, 3, (void*)ptr, dims, strides, box, es, CU_TENSOR_MAP_INTERLEAVE_NONE,
                        CU_TENSOR_MAP_SWIZZLE_128B, CU_TENSOR_MAP_L2_PROMOTION_L2_128B, CU_TENSOR_MAP_FLOAT_OOB_FILL_NONE);
  if (r != CUDA_SUCCESS) fprintf(stderr, "tensor map encode failed (%d)\n", (int)r);
}
static inline uint16_t mk(int type, int a, int b) { return (uint16_t)(type << 12 | a << 5 | b); }

static void build_schedule(Params& P) {
  int cnt[NCLUSTER];
  for (int c = 0; c < NCLUSTER; c++) { cnt[c] = 0; for (int i = 0; i < MAXI; i++) P.items[c][i] = mk(T_END, 0, 0); }
  auto phys = [](int c) { return c == 64 ? 9 : c == 65 ? 17 : c == 9 ? 64 : c == 17 ? 65 : c; };
  auto push = [&](int c, uint16_t v) { P.items[phys(c)][cnt[c]++] = v; };
  int natt[NCLUSTER], nq[NCLUSTER];
  for (int c = 0; c < NCLUSTER; c++) { natt[c] = c < 32 ? 3 : (c < 56 ? 5 : (c < 62 ? 4 : (c < 64 ? 3 : 5))); nq[c] = c < 56 ? 1 : (c < 62 ? 7 : (c < 64 ? 9 : 6)); }
  for (int c = 0; c < 56; c++) push(c, mk(T_Z2, c % 8, c / 8));
  int qi = 0;
  for (int slot = 0; slot < 9; slot++)
    for (int c = NCLUSTER - 1; c >= 0; c--) {
      const int first = c < 56 ? 1 : 0;
      if (slot >= first && slot < first + nq[c]) { push(c, mk(T_Q, qi % 8, qi / 8)); qi++; }
    }
  for (int c = 0; c < 56; c++) push(c, mk(T_U, c % 8, c / 8));
  int ai = 0;
  for (int slot = 0; slot < 5; slot++)
    for (int c = 0; c < NCLUSTER; c++) {
      const int first = c < 32 ? 0 : 5 - natt[c];
      if (slot >= first && slot < first + natt[c]) { push(c, mk(T_ATT, ai / 8, ai % 8) | (natt[c] - 3) << 10); ai++; }
    }
  for (int c = 0; c < 32; c++) push(c, mk(T_SA, c % 8, c / 8));
  for (int c = 0; c < 64; c++) push(c, mk(T_FIN, c % 8, (c / 8) % 4 | (c < 32 ? 4 : 0)));
  if (qi != 128 || ai != 256) fprintf(stderr, "bad schedule %d %d\n", qi, ai);
}

static Params s_params;
extern "C" void kernel_launch(void* const* d_in, const int* in_sizes, int n_in, void* d_out, int out_size) {
  (void)in_sizes; (void)n_in; (void)out_size;
  if (!s_encode) {
    void* fn = nullptr; cudaDriverEntryPointQueryResult qr;
    cudaGetDriverEntryPoint("cuTensorMapEncodeTiled", &fn, cudaEnableDefault, &qr);
    s_encode = (PFN_encodeTiled)fn;
    cudaFuncSetAttribute(fused_kernel, cudaFuncAttributeMaxDynamicSharedMemorySize, SMEM_BYTES);
    build_schedule(s_params);
  }
  Params& P = s_params;
  void *xn, *q, *o, *z2, *u, *gg, *sa;
  cudaGetSymbolAddress(&gg, g_g); cudaGetSymbolAddress(&sa, g_sa);
  cudaGetSymbolAddress(&xn, g_xn); cudaGetSymbolAddress(&q, g_q); cudaGetSymbolAddress(&o, g_o);
  cudaGetSymbolAddress(&z2, g_z2); cudaGetSymbolAddress(&u, g_u);
  tm_2d(&P.tm[TM_XN], xn, SEQ, DM, 128); tm_2d(&P.tm[TM_WSP], d_in[7], SEQ, SEQ, 128); tm_2d(&P.tm[TM_U], u, SEQ, FH, 128);
  tm_2d(&P.tm[TM_O], o, SEQ, HD, 128); tm_2d(&P.tm[TM_Q], q, SEQ, HD, 128); tm_2d(&P.tm[TM_X], d_in[0], SEQ, DM, 128);
  tm_2d(&P.tm[TM_K], d_in[1], NH * SEQ, 128, 128); tm_2d(&P.tm[TM_V], d_in[2], NH * SEQ, 128, 128);
  tm_2d(&P.tm[TM_SA], sa, SEQ, DM, 128); tm_2d(&P.tm[TM_G], gg, SEQ, DM, 128); tm_2d(&P.tm[TM_WO64], d_in[4], HD, DM, 64);
  tm_3d(&P.tm[TM_WIN], d_in[6], DM, FF); tm_3d(&P.tm[TM_WQ], d_in[3], DM, HD); tm_3d(&P.tm[TM_Z2], z2, SEQ, FH);
  tm_3d(&P.tm[TM_WOUT], d_in[9], FH, DM); tm_3d(&P.tm[TM_WO], d_in[4], HD, DM);
  tm_2d(&P.tm[TS_Q], q, SEQ, HD, ST_ROWS); tm_2d(&P.tm[TS_O], o, SEQ, HD, ST_ROWS); tm_2d(&P.tm[TS_Z2], z2, SEQ, FH, ST_ROWS); tm_2d(&P.tm[TS_U], u, SEQ, FH, ST_ROWS);
  tm_2d(&P.tm[TS_SA], sa, SEQ, DM, ST_ROWS); tm_2d(&P.tm[TS_G], gg, SEQ, DM, ST_ROWS); tm_2d(&P.tm[TS_OUT], d_out, SEQ, DM, 16);
  P.x = (const bf16*)d_in[0]; P.b_sp = (const bf16*)d_in[8];
  fused_kernel<<<2 * NCLUSTER, 384, SMEM_BYTES, cudaStreamPerThread>>>(P);
}
```

```cpp
#include <cuda_runtime.h>
#include <cuda_bf16.h>
#include <cuda.h>
#include <stdint.h>
#include <stdio.h>

typedef __nv_bfloat16 bf16;

constexpr int SEQ = 2048, DM = 1024, NH = 32, HD = 4096, FF = 3584, FH = 1792;

__device__ __align__(1024) bf16 g_xn[SEQ * DM];
__device__ __align__(1024) bf16 g_q[SEQ * HD];
__device__ __align__(1024) bf16 g_o[SEQ * HD];
__device__ __align__(1024) bf16 g_z2[SEQ * FH];
__device__ __align__(1024) bf16 g_u[SEQ * FH];
__device__ __align__(1024) uint2 g_stats[SEQ * 8];
__device__ __align__(1024) bf16 g_g[SEQ * DM];
__device__ __align__(1024) bf16 g_sa[SEQ * DM];
constexpr int F_XN = 0;
constexpr int F_Z2 = 512;
constexpr int F_Q = 768;
constexpr int F_U = 1024;
constexpr int F_O = 1536;
constexpr int F_S = 2048;
constexpr int F_TOTAL = 2112;
__device__ __align__(1024) unsigned g_flags[F_TOTAL];
__device__ unsigned g_done;
__device__ unsigned g_epoch;

__device__ __forceinline__ uint32_t smem_u32(const void* p) { return (uint32_t)__cvta_generic_to_shared(p); }
__device__ __forceinline__ void mbar_init(uint32_t bar, uint32_t cnt) { asm volatile("mbarrier.init.shared::cta.b64 [%0], %1;" :: "r"(bar), "r"(cnt)); }
__device__ __forceinline__ void mbar_expect_tx(uint32_t bar, uint32_t bytes) { asm volatile("mbarrier.arrive.expect_tx.shared::cta.b64 _, [%0], %1;" :: "r"(bar), "r"(bytes) : "memory"); }
__device__ __forceinline__ void mbar_arrive(uint32_t bar) { asm volatile("mbarrier.arrive.shared::cta.b64 _, [%0];" :: "r"(bar) : "memory"); }
__device__ __forceinline__ void mbar_arrive_cta(uint32_t bar, uint32_t cta) {
  asm volatile("{\n.reg .b32 ra;\nmapa.shared::cluster.u32 ra, %0, %1;\nmbarrier.arrive.shared::cluster.b64 _, [ra];\n}" :: "r"(bar), "r"(cta) : "memory");
}
__device__ __forceinline__ bool mbar_test(uint32_t bar, uint32_t parity) {
  uint32_t ok;
  asm volatile("{\n.reg .pred P1;\nmbarrier.test_wait.parity.shared::cta.b64 P1, [%1], %2;\nselp.u32 %0, 1, 0, P1;\n}" : "=r"(ok) : "r"(bar), "r"(parity) : "memory");
  return ok;
}
constexpr uint32_t SPIN_LIMIT = 1u << 22;
__device__ __forceinline__ void trap_if(bool c) { asm volatile("{\n.reg .pred P;\nsetp.ne.u32 P, %0, 0;\n@P trap;\n}" :: "r"((uint32_t)c)); }
__device__ __forceinline__ void mbar_wait(uint32_t bar, uint32_t parity) {
  asm volatile("{\n.reg .pred P1;\n.reg .u32 n;\nmbarrier.try_wait.parity.shared::cta.b64 P1, [%0], %1;\n@P1 bra DONE;\nmov.u32 n, 0;\n"
               "LOOP:\nmbarrier.try_wait.parity.shared::cta.b64 P1, [%0], %1;\n@P1 bra DONE;\nadd.u32 n, n, 1;\nsetp.gt.u32 P1, n, %2;\n@P1 trap;\nbra LOOP;\nDONE:\n}"
               :: "r"(bar), "r"(parity), "n"(SPIN_LIMIT) : "memory");
}
__device__ __forceinline__ void mbar_spin(uint32_t bar, uint32_t parity) {
  asm volatile("{\n.reg .pred P1;\nLOOP:\nmbarrier.try_wait.parity.shared::cta.b64 P1, [%0], %1;\n@!P1 bra LOOP;\n}" :: "r"(bar), "r"(parity) : "memory");
}
__device__ __forceinline__ void mbar_wait_sleep(uint32_t bar, uint32_t parity, uint32_t ns) {
  uint32_t n = 0;
  while (!mbar_test(bar, parity)) { trap_if(++n > SPIN_LIMIT * 4); __nanosleep(ns); }
}
__device__ __forceinline__ void tma_load_2d(uint32_t dst, const CUtensorMap* tm, int c0, int c1, uint32_t bar) {
  asm volatile("cp.async.bulk.tensor.2d.shared::cluster.global.mbarrier::complete_tx::bytes [%0], [%1, {%3, %4}], [%2];"
    :: "r"(dst), "l"(tm), "r"(bar), "r"(c0), "r"(c1) : "memory");
}
__device__ __forceinline__ void tma_load_2d_mc(uint32_t dst, const CUtensorMap* tm, int c0, int c1, uint32_t bar) {
  asm volatile("cp.async.bulk.tensor.2d.shared::cluster.global.mbarrier::complete_tx::bytes.multicast::cluster [%0], [%1, {%3, %4}], [%2], %5;"
    :: "r"(dst), "l"(tm), "r"(bar), "r"(c0), "r"(c1), "h"((uint16_t)3) : "memory");
}
__device__ __forceinline__ void tma_prefetch_2d(const CUtensorMap* tm, int c0, int c1) {
  asm volatile("cp.async.bulk.prefetch.tensor.2d.L2.global [%0, {%1, %2}];" :: "l"(tm), "r"(c0), "r"(c1) : "memory");
}
__device__ __forceinline__ void tma_prefetch_3d(const CUtensorMap* tm, int c1, int c2) {
  asm volatile("cp.async.bulk.prefetch.tensor.3d.L2.global [%0, {%1, %2, %3}];" :: "l"(tm), "r"(0), "r"(c1), "r"(c2) : "memory");
}
__device__ __forceinline__ void tma_load_3d_mc(uint32_t dst, const CUtensorMap* tm, int c1, int c2, uint32_t bar) {
  asm volatile("cp.async.bulk.tensor.3d.shared::cluster.global.mbarrier::complete_tx::bytes.multicast::cluster [%0], [%1, {%3, %4, %5}], [%2], %6;"
    :: "r"(dst), "l"(tm), "r"(bar), "r"(0), "r"(c1), "r"(c2), "h"((uint16_t)3) : "memory");
}
__device__ __forceinline__ void tma_store_2d(const CUtensorMap* tm, uint32_t src, int c0, int c1) {
  asm volatile("cp.async.bulk.tensor.2d.global.shared::cta.bulk_group [%0, {%2, %3}], [%1];" :: "l"(tm), "r"(src), "r"(c0), "r"(c1) : "memory");
}
__device__ __forceinline__ void bulk_commit() { asm volatile("cp.async.bulk.commit_group;" ::: "memory"); }
template <int N> __device__ __forceinline__ void bulk_wait_read() { asm volatile("cp.async.bulk.wait_group.read %0;" :: "n"(N) : "memory"); }
template <int N> __device__ __forceinline__ void bulk_wait() { asm volatile("cp.async.bulk.wait_group %0;" :: "n"(N) : "memory"); }
__device__ __forceinline__ void fence_async_smem() { asm volatile("fence.proxy.async.shared::cta;" ::: "memory"); }
__device__ __forceinline__ void fence_async_global() { asm volatile("fence.proxy.async.global;" ::: "memory"); }
__device__ __forceinline__ void wgmma_fence() { asm volatile("wgmma.fence.sync.aligned;" ::: "memory"); }
__device__ __forceinline__ void wgmma_commit() { asm volatile("wgmma.commit_group.sync.aligned;" ::: "memory"); }
template <int N> __device__ __forceinline__ void wgmma_wait() { asm volatile("wgmma.wait_group.sync.aligned %0;" :: "n"(N) : "memory"); }
__device__ __forceinline__ uint64_t make_desc(uint32_t addr, uint32_t lbo, uint32_t sbo) {
  return (uint64_t)((addr & 0x3FFFF) >> 4) | ((uint64_t)(lbo >> 4) << 16) | ((uint64_t)(sbo >> 4) << 32) | (1ull << 62);
}
template <int N> __device__ __forceinline__ void fence_regs(float (&d)[N]) {
#pragma unroll
  for (int i = 0; i < N; i++) asm volatile("" : "+f"(d[i]) :: "memory");
}
template <int N> __device__ __forceinline__ void fence_regs(uint32_t (&d)[N]) {
#pragma unroll
  for (int i = 0; i < N; i++) asm volatile("" : "+r"(d[i]) :: "memory");
}
__device__ __forceinline__ void named_sync(int id) { asm volatile("bar.sync %0, 256;" :: "r"(id) : "memory"); }
__device__ __forceinline__ bool wg_any(bool w, bool v) {
  uint32_t r;
  asm volatile("{\n.reg .pred p, q;\nsetp.ne.u32 p, %1, 0;\nbar.red.or.pred q, %2, 128, p;\nselp.u32 %0, 1, 0, q;\n}" : "=r"(r) : "r"((uint32_t)v), "r"(w ? 4 : 3) : "memory");
  return __any_sync(0xffffffffu, r);
}
__device__ __forceinline__ int fresh_warp() { uint32_t t; asm volatile("mov.u32 %0, %%tid.x;" : "=r"(t)); return __shfl_sync(0xffffffffu, (int)(t >> 5) - 4, 0); }
__device__ __forceinline__ void cluster_sync_relaxed() { asm volatile("barrier.cluster.arrive.relaxed.aligned;\nbarrier.cluster.wait.aligned;" ::: "memory"); }
__device__ __forceinline__ unsigned ld_acquire(const unsigned* p) { unsigned v; asm volatile("ld.acquire.gpu.global.u32 %0, [%1];" : "=r"(v) : "l"(p) : "memory"); return v; }
__device__ __forceinline__ void red_release(unsigned* p, unsigned v) { asm volatile("red.release.gpu.global.add.u32 [%0], %1;" :: "l"(p), "r"(v) : "memory"); }
__device__ __forceinline__ void flag_wait(const unsigned* p, unsigned target) {
  uint32_t n = 0;
  while (ld_acquire(p) < target) { trap_if(++n > SPIN_LIMIT); __nanosleep(20); }
}
__device__ __forceinline__ void st_tagged(uint2* p, float a, float b, uint32_t tag) {
  asm volatile("{\n.reg .b64 x;\nmov.b64 x, {%1, %2};\nst.relaxed.gpu.global.b64 [%0], x;\n}" :: "l"(p),
               "r"((__float_as_uint(a) & ~63u) | (tag & 63u)), "r"((__float_as_uint(b) & ~63u) | (tag >> 6)) : "memory");
}
__device__ __forceinline__ uint4 ld_tagged2(const uint2* p) {
  uint4 v;
  asm volatile("{\n.reg .b64 x, y;\nld.relaxed.gpu.global.v2.b64 {x, y}, [%4];\nmov.b64 {%0, %1}, x;\nmov.b64 {%2, %3}, y;\n}" : "=r"(v.x), "=r"(v.y), "=r"(v.z), "=r"(v.w) : "l"(p) : "memory");
  return v;
}
__device__ __forceinline__ bool tag_ok(uint32_t a, uint32_t b, uint32_t tag) { return ((a & 63u) | ((b & 63u) << 6)) == tag; }
__device__ __forceinline__ float untag(uint32_t v) { return __uint_as_float(v & ~63u); }
__device__ __forceinline__ uint32_t pack_bf16(float lo, float hi) { uint32_t r; asm("cvt.rn.bf16x2.f32 %0, %1, %2;" : "=r"(r) : "f"(hi), "f"(lo)); return r; }
__device__ __forceinline__ uint32_t bf2_fma(uint32_t a, uint32_t b, uint32_t c) { uint32_t r; asm("fma.rn.bf16x2 %0, %1, %2, %3;" : "=r"(r) : "r"(a), "r"(b), "r"(c)); return r; }
__device__ __forceinline__ uint32_t bf2_mul(uint32_t a, uint32_t b) { uint32_t r; asm("mul.rn.bf16x2 %0, %1, %2;" : "=r"(r) : "r"(a), "r"(b)); return r; }
__device__ __forceinline__ uint32_t bf2_add(uint32_t a, uint32_t b) { uint32_t r; asm("add.rn.bf16x2 %0, %1, %2;" : "=r"(r) : "r"(a), "r"(b)); return r; }
constexpr uint32_t BF2_HALF = 0x3f003f00u;
__device__ __forceinline__ float bf_lo(uint32_t v) { return __uint_as_float(v << 16); }
__device__ __forceinline__ float bf_hi(uint32_t v) { return __uint_as_float(v & 0xffff0000u); }
__device__ __forceinline__ float ex2(float x) { float y; asm("ex2.approx.ftz.f32 %0, %1;" : "=f"(y) : "f"(x)); return y; }
__device__ __forceinline__ float tanh_fast(float x) { float y; asm("tanh.approx.f32 %0, %1;" : "=f"(y) : "f"(x)); return y; }
__device__ __forceinline__ void stmatrix_x4(uint32_t addr, uint32_t a, uint32_t b, uint32_t c, uint32_t d) {
  asm volatile("stmatrix.sync.aligned.m8n8.x4.shared.b16 [%0], {%1, %2, %3, %4};" :: "r"(addr), "r"(a), "r"(b), "r"(c), "r"(d) : "memory");
}
__device__ __forceinline__ void ldmatrix_x4(uint32_t addr, uint32_t& a, uint32_t& b, uint32_t& c, uint32_t& d) {
  asm volatile("ldmatrix.sync.aligned.m8n8.x4.shared.b16 {%0, %1, %2, %3}, [%4];" : "=r"(a), "=r"(b), "=r"(c), "=r"(d) : "r"(addr) : "memory");
}
__device__ __forceinline__ uint32_t lane_id() { uint32_t l; asm volatile("mov.u32 %0, %%laneid;" : "=r"(l)); return l; }
__device__ __forceinline__ bool elect_one() {
  uint32_t r;
  asm volatile("{\n.reg .pred P;\nelect.sync _|P, 0xffffffff;\nselp.u32 %0, 1, 0, P;\n}" : "=r"(r));
  return r;
}

__device__ __forceinline__ void wgmma_m64n128k16_ss_tb0(float (&d)[64], uint64_t da, uint64_t db, int scale_d) {
  asm volatile("{\n.reg .pred p;\nsetp.ne.b32 p, %66, 0;\n"
    "wgmma.mma_async.sync.aligned.m64n128k16.f32.bf16.bf16 "
    "{%0, %1, %2, %3, %4, %5, %6, %7, %8, %9, %10, %11, %12, %13, %14, %15, %16, %17, %18, %19, %20, %21, %22, %23, %24, %25, %26, %27, %28, %29, %30, %31, %32, %33, %34, %35, %36, %37, %38, %39, %40, %41, %42, %43, %44, %45, %46, %47, %48, %49, %50, %51, %52, %53, %54, %55, %56, %57, %58, %59, %60, %61, %62, %63}, "
    "%64, %65, p, 1, 1, 0, 0;\n}\n"
    : "+f"(d[0]), "+f"(d[1]), "+f"(d[2]), "+f"(d[3]), "+f"(d[4]), "+f"(d[5]), "+f"(d[6]), "+f"(d[7]), "+f"(d[8]), "+f"(d[9]), "+f"(d[10]), "+f"(d[11]), "+f"(d[12]), "+f"(d[13]), "+f"(d[14]), "+f"(d[15]), "+f"(d[16]), "+f"(d[17]), "+f"(d[18]), "+f"(d[19]), "+f"(d[20]), "+f"(d[21]), "+f"(d[22]), "+f"(d[23]), "+f"(d[24]), "+f"(d[25]), "+f"(d[26]), "+f"(d[27]), "+f"(d[28]), "+f"(d[29]), "+f"(d[30]), "+f"(d[31]), "+f"(d[32]), "+f"(d[33]), "+f"(d[34]), "+f"(d[35]), "+f"(d[36]), "+f"(d[37]), "+f"(d[38]), "+f"(d[39]), "+f"(d[40]), "+f"(d[41]), "+f"(d[42]), "+f"(d[43]), "+f"(d[44]), "+f"(d[45]), "+f"(d[46]), "+f"(d[47]), "+f"(d[48]), "+f"(d[49]), "+f"(d[50]), "+f"(d[51]), "+f"(d[52]), "+f"(d[53]), "+f"(d[54]), "+f"(d[55]), "+f"(d[56]), "+f"(d[57]), "+f"(d[58]), "+f"(d[59]), "+f"(d[60]), "+f"(d[61]), "+f"(d[62]), "+f"(d[63])
    : "l"(da), "l"(db), "r"(scale_d));
}
__device__ __forceinline__ void wgmma_m64n256k16_ss_tb1(float (&d)[128], uint64_t da, uint64_t db, int scale_d) {
  asm volatile("{\n.reg .pred p;\nsetp.ne.b32 p, %130, 0;\n"
    "wgmma.mma_async.sync.aligned.m64n256k16.f32.bf16.bf16 "
    "{%0, %1, %2, %3, %4, %5, %6, %7, %8, %9, %10, %11, %12, %13, %14, %15, %16, %17, %18, %19, %20, %21, %22, %23, %24, %25, %26, %27, %28, %29, %30, %31, %32, %33, %34, %35, %36, %37, %38, %39, %40, %41, %42, %43, %44, %45, %46, %47, %48, %49, %50, %51, %52, %53, %54, %55, %56, %57, %58, %59, %60, %61, %62, %63, %64, %65, %66, %67, %68, %69, %70, %71, %72, %73, %74, %75, %76, %77, %78, %79, %80, %81, %82, %83, %84, %85, %86, %87, %88, %89, %90, %91, %92, %93, %94, %95, %96, %97, %98, %99, %100, %101, %102, %103, %104, %105, %106, %107, %108, %109, %110, %111, %112, %113, %114, %115, %116, %117, %118, %119, %120, %121, %122, %123, %124, %125, %126, %127}, "
    "%128, %129, p, 1, 1, 0, 1;\n}\n"
    : "+f"(d[0]), "+f"(d[1]), "+f"(d[2]), "+f"(d[3]), "+f"(d[4]), "+f"(d[5]), "+f"(d[6]), "+f"(d[7]), "+f"(d[8]), "+f"(d[9]), "+f"(d[10]), "+f"(d[11]), "+f"(d[12]), "+f"(d[13]), "+f"(d[14]), "+f"(d[15]), "+f"(d[16]), "+f"(d[17]), "+f"(d[18]), "+f"(d[19]), "+f"(d[20]), "+f"(d[21]), "+f"(d[22]), "+f"(d[23]), "+f"(d[24]), "+f"(d[25]), "+f"(d[26]), "+f"(d[27]), "+f"(d[28]), "+f"(d[29]), "+f"(d[30]), "+f"(d[31]), "+f"(d[32]), "+f"(d[33]), "+f"(d[34]), "+f"(d[35]), "+f"(d[36]), "+f"(d[37]), "+f"(d[38]), "+f"(d[39]), "+f"(d[40]), "+f"(d[41]), "+f"(d[42]), "+f"(d[43]), "+f"(d[44]), "+f"(d[45]), "+f"(d[46]), "+f"(d[47]), "+f"(d[48]), "+f"(d[49]), "+f"(d[50]), "+f"(d[51]), "+f"(d[52]), "+f"(d[53]), "+f"(d[54]), "+f"(d[55]), "+f"(d[56]), "+f"(d[57]), "+f"(d[58]), "+f"(d[59]), "+f"(d[60]), "+f"(d[61]), "+f"(d[62]), "+f"(d[63]), "+f"(d[64]), "+f"(d[65]), "+f"(d[66]), "+f"(d[67]), "+f"(d[68]), "+f"(d[69]), "+f"(d[70]), "+f"(d[71]), "+f"(d[72]), "+f"(d[73]), "+f"(d[74]), "+f"(d[75]), "+f"(d[76]), "+f"(d[77]), "+f"(d[78]), "+f"(d[79]), "+f"(d[80]), "+f"(d[81]), "+f"(d[82]), "+f"(d[83]), "+f"(d[84]), "+f"(d[85]), "+f"(d[86]), "+f"(d[87]), "+f"(d[88]), "+f"(d[89]), "+f"(d[90]), "+f"(d[91]), "+f"(d[92]), "+f"(d[93]), "+f"(d[94]), "+f"(d[95]), "+f"(d[96]), "+f"(d[97]), "+f"(d[98]), "+f"(d[99]), "+f"(d[100]), "+f"(d[101]), "+f"(d[102]), "+f"(d[103]), "+f"(d[104]), "+f"(d[105]), "+f"(d[106]), "+f"(d[107]), "+f"(d[108]), "+f"(d[109]), "+f"(d[110]), "+f"(d[111]), "+f"(d[112]), "+f"(d[113]), "+f"(d[114]), "+f"(d[115]), "+f"(d[116]), "+f"(d[117]), "+f"(d[118]), "+f"(d[119]), "+f"(d[120]), "+f"(d[121]), "+f"(d[122]), "+f"(d[123]), "+f"(d[124]), "+f"(d[125]), "+f"(d[126]), "+f"(d[127])
    : "l"(da), "l"(db), "r"(scale_d));
}
__device__ __forceinline__ void wgmma_m64n128k16_rs_tb1(float (&d)[64], uint32_t a0, uint32_t a1, uint32_t a2, uint32_t a3, uint64_t db, int scale_d) {
  asm volatile("{\n.reg .pred p;\nsetp.ne.b32 p, %69, 0;\n"
    "wgmma.mma_async.sync.aligned.m64n128k16.f32.bf16.bf16 "
    "{%0, %1, %2, %3, %4, %5, %6, %7, %8, %9, %10, %11, %12, %13, %14, %15, %16, %17, %18, %19, %20, %21, %22, %23, %24, %25, %26, %27, %28, %29, %30, %31, %32, %33, %34, %35, %36, %37, %38, %39, %40, %41, %42, %43, %44, %45, %46, %47, %48, %49, %50, %51, %52, %53, %54, %55, %56, %57, %58, %59, %60, %61, %62, %63}, "
    "{%64, %65, %66, %67}, %68, p, 1, 1, 1;\n}\n"
    : "+f"(d[0]), "+f"(d[1]), "+f"(d[2]), "+f"(d[3]), "+f"(d[4]), "+f"(d[5]), "+f"(d[6]), "+f"(d[7]), "+f"(d[8]), "+f"(d[9]), "+f"(d[10]), "+f"(d[11]), "+f"(d[12]), "+f"(d[13]), "+f"(d[14]), "+f"(d[15]), "+f"(d[16]), "+f"(d[17]), "+f"(d[18]), "+f"(d[19]), "+f"(d[20]), "+f"(d[21]), "+f"(d[22]), "+f"(d[23]), "+f"(d[24]), "+f"(d[25]), "+f"(d[26]), "+f"(d[27]), "+f"(d[28]), "+f"(d[29]), "+f"(d[30]), "+f"(d[31]), "+f"(d[32]), "+f"(d[33]), "+f"(d[34]), "+f"(d[35]), "+f"(d[36]), "+f"(d[37]), "+f"(d[38]), "+f"(d[39]), "+f"(d[40]), "+f"(d[41]), "+f"(d[42]), "+f"(d[43]), "+f"(d[44]), "+f"(d[45]), "+f"(d[46]), "+f"(d[47]), "+f"(d[48]), "+f"(d[49]), "+f"(d[50]), "+f"(d[51]), "+f"(d[52]), "+f"(d[53]), "+f"(d[54]), "+f"(d[55]), "+f"(d[56]), "+f"(d[57]), "+f"(d[58]), "+f"(d[59]), "+f"(d[60]), "+f"(d[61]), "+f"(d[62]), "+f"(d[63])
    : "r"(a0), "r"(a1), "r"(a2), "r"(a3), "l"(db), "r"(scale_d));
}
__device__ __forceinline__ void wgmma_m64n128k16_ss_tb1(float (&d)[64], uint64_t da, uint64_t db, int scale_d) {
  asm volatile("{\n.reg .pred p;\nsetp.ne.b32 p, %66, 0;\n"
    "wgmma.mma_async.sync.aligned.m64n128k16.f32.bf16.bf16 "
    "{%0, %1, %2, %3, %4, %5, %6, %7, %8, %9, %10, %11, %12, %13, %14, %15, %16, %17, %18, %19, %20, %21, %22, %23, %24, %25, %26, %27, %28, %29, %30, %31, %32, %33, %34, %35, %36, %37, %38, %39, %40, %41, %42, %43, %44, %45, %46, %47, %48, %49, %50, %51, %52, %53, %54, %55, %56, %57, %58, %59, %60, %61, %62, %63}, "
    "%64, %65, p, 1, 1, 0, 1;\n}\n"
    : "+f"(d[0]), "+f"(d[1]), "+f"(d[2]), "+f"(d[3]), "+f"(d[4]), "+f"(d[5]), "+f"(d[6]), "+f"(d[7]), "+f"(d[8]), "+f"(d[9]), "+f"(d[10]), "+f"(d[11]), "+f"(d[12]), "+f"(d[13]), "+f"(d[14]), "+f"(d[15]), "+f"(d[16]), "+f"(d[17]), "+f"(d[18]), "+f"(d[19]), "+f"(d[20]), "+f"(d[21]), "+f"(d[22]), "+f"(d[23]), "+f"(d[24]), "+f"(d[25]), "+f"(d[26]), "+f"(d[27]), "+f"(d[28]), "+f"(d[29]), "+f"(d[30]), "+f"(d[31]), "+f"(d[32]), "+f"(d[33]), "+f"(d[34]), "+f"(d[35]), "+f"(d[36]), "+f"(d[37]), "+f"(d[38]), "+f"(d[39]), "+f"(d[40]), "+f"(d[41]), "+f"(d[42]), "+f"(d[43]), "+f"(d[44]), "+f"(d[45]), "+f"(d[46]), "+f"(d[47]), "+f"(d[48]), "+f"(d[49]), "+f"(d[50]), "+f"(d[51]), "+f"(d[52]), "+f"(d[53]), "+f"(d[54]), "+f"(d[55]), "+f"(d[56]), "+f"(d[57]), "+f"(d[58]), "+f"(d[59]), "+f"(d[60]), "+f"(d[61]), "+f"(d[62]), "+f"(d[63])
    : "l"(da), "l"(db), "r"(scale_d));
}


enum { TM_XN, TM_WSP, TM_U, TM_O, TM_Q, TM_X, TM_SA, TM_G, TM_K, TM_V, TM_WO64,
       TM_WIN, TM_WQ, TM_Z2, TM_WOUT, TM_WO, TS_Q, TS_O, TS_Z2, TS_U, TS_SA, TS_G, TS_OUT, TM_COUNT };
enum { T_Z2 = 0, T_Q = 1, T_U = 2, T_ATT = 3, T_SA = 4, T_FIN = 5, T_END = 7 };
constexpr int NCLUSTER = 66, MAXI = 14;
struct alignas(64) Params {
  const bf16* x;
  const bf16* b_sp;
  CUtensorMap tm[TM_COUNT];
  uint16_t items[NCLUSTER][MAXI];
};

constexpr uint32_t G_STAGE = 49152, G_A = 16384, KV_SLOT = 32768;
constexpr uint32_t OFF_Q1 = 163840, OFF_Q0 = 196608, OFF_BAR = 229376, OFF_LN = OFF_BAR + 256, SMEM_BYTES = OFF_LN + 1024;
constexpr uint32_t B_GF = 0, B_GE = 32, B_KF = 64, B_KE = 104, B_QF = 144, B_QE = 160, B_XF = 176, B_XR = 184, B_STG = 192, B_FREE = 200, B_GO = 208, B_LN = 216, B_TAG = 224, B_RDY = 228, B_PROG = 232, B_PUB = 248;
constexpr int SA_HEADS = 18;
constexpr int SW_NS = 40;
constexpr int ST_ROWS = 16;
constexpr int ST_FLY = 2;
constexpr int KV_PF = 4;
constexpr int FIN_PREP = 8;
constexpr int OWN_OFF = 8;
constexpr int ACT_REP = 32;
constexpr int Q_DELAY = 4;
constexpr int Q_GAP = 4;
constexpr int Z_GAP = 3;
constexpr int LN_SLEEP = 300;
constexpr int Z_DELAY = 4;
constexpr int SW_ATT = 800;
constexpr int OUT_PF = 8;
constexpr int SA_STEPS = 2 * SA_HEADS;
constexpr uint32_t FIN_SLOT0 = (0x0320u >> (4 * ((29 + SA_STEPS) & 3))) & 15;
constexpr float SM_C = 0.08838834764831845f * 1.4426950408889634f;
constexpr float GELU_A = 0.7978845608028654f, GELU_B = 0.7978845608028654f * 0.044715f;
constexpr float SM_LO = 1e-7f, SM_HI = 1e12f;
constexpr float SM_THR = 1024.f;


extern __shared__ __align__(1024) uint8_t smem_raw[];
__device__ __forceinline__ uint32_t smem_base() { return smem_u32(smem_raw); }

struct Ring { uint32_t s, ph; };
template <int N> __device__ __forceinline__ void ring_adv(Ring& r) { if (++r.s == N) { r.s = 0; r.ph ^= 1; } }

__device__ __forceinline__ int get_item(const Params& p, int i) {
  uint32_t b; asm volatile("mov.u32 %0, %%ctaid.x;" : "=r"(b));
  return p.items[b >> 1][i];
}
struct Cons {
  uint32_t sb;
  int warp;
  Ring g;
  uint32_t rot;
  uint32_t fph;
};

__device__ __forceinline__ void stage_acquire(const Cons& c) { mbar_spin(c.sb + OFF_BAR + B_FREE, c.fph); }
__device__ __forceinline__ void stage_commit(Cons& c) {
  __syncwarp();
  if (lane_id() == 0) mbar_arrive(c.sb + OFF_BAR + B_STG);
  c.fph ^= 1;
}

__device__ __forceinline__ void release_slot(const Cons& c, uint32_t bar) {
  if (lane_id() == 0 && (c.warp & 3) < 2) mbar_arrive_cta(bar, c.warp & 1);
}
constexpr uint64_t DESC_HI = (uint64_t)0x40000040u << 32;

template <bool FIRST> __device__ __forceinline__ void gemm_step(float (&acc)[128], Cons& c) {
  mbar_spin(c.sb + OFF_BAR + B_GF + 8 * c.g.s, c.g.ph);
  const uint32_t st = ((c.sb & 0x3FFFF) >> 4) + ((c.g.s + c.rot) & 3) * (G_STAGE >> 4);
  const uint32_t da = st + (c.warp >> 2) * 512 + (1u << 16), db = st + (G_A >> 4) + ((8192u >> 4) << 16);
  wgmma_fence();
#pragma unroll
  for (int kk = 0; kk < 4; kk++) wgmma_m64n256k16_ss_tb1(acc, DESC_HI | (da + kk * 2), DESC_HI | (db + kk * 128), !(FIRST && kk == 0));
  wgmma_commit();
}

template <int N> __device__ __forceinline__ void stage_chunks(uint32_t buf, uint32_t stride, const uint32_t* pk) {
  const uint32_t ln = lane_id();
  const uint32_t a = buf + ((ln & 15) << 7);
  const uint32_t x = ln & 7, hi = ln >> 4;
#pragma unroll
  for (int i = 0; i < 4 * N; i++) stmatrix_x4(a + (i >> 2) * stride + (((2 * (i & 3) + hi) ^ x) << 4), pk[4 * i], pk[4 * i + 1], pk[4 * i + 2], pk[4 * i + 3]);
}

__device__ __forceinline__ float act2_fn(float x, float a, float b) {
  return fmaf(x, tanh_fast(x * fmaf(x * x, b, a)), x);
}
__device__ __forceinline__ float quad_sum(float v) { v += __shfl_xor_sync(0xffffffffu, v, 1); v += __shfl_xor_sync(0xffffffffu, v, 2); return v; }
__device__ __forceinline__ float quad_max(float v) { v = fmaxf(v, __shfl_xor_sync(0xffffffffu, v, 1)); v = fmaxf(v, __shfl_xor_sync(0xffffffffu, v, 2)); return v; }

__device__ __forceinline__ uint32_t load_tag(const Cons& c) { uint32_t t; asm volatile("ld.volatile.shared.u32 %0, [%1];" : "=r"(t) : "r"(c.sb + OFF_BAR + B_TAG)); return t; }

struct Shadow {
  int act;
  int store;
};
__device__ __forceinline__ void rotate16(uint32_t (&h)[64]) {
#pragma unroll
  for (int i = 0; i < 16; i++)
    asm volatile("{\n.reg .b32 t;\nmov.b32 t, %0;\nmov.b32 %0, %1;\nmov.b32 %1, %2;\nmov.b32 %2, %3;\nmov.b32 %3, t;\n}" : "+r"(h[i]), "+r"(h[i + 16]), "+r"(h[i + 32]), "+r"(h[i + 48]));
}

template <int O>
__device__ __forceinline__ void act_block(uint32_t (&held)[64], float ca, float cb, bool first, float& u0, float& u1, float& s0, float& s1, float& q0, float& q1) {
#pragma unroll
  for (int i = O; i < O + 4; i += 2) {
    const float a0 = act2_fn(bf_lo(held[i]), ca, cb), a1 = act2_fn(bf_hi(held[i]), ca, cb);
    const float b0 = act2_fn(bf_lo(held[i + 1]), ca, cb), b1 = act2_fn(bf_hi(held[i + 1]), ca, cb);
    if (i == 0 && first) { u0 = a0; u1 = b0; }
    float d;
    d = a0 - u0; s0 += d; q0 = fmaf(d, d, q0); d = a1 - u0; s0 += d; q0 = fmaf(d, d, q0);
    d = b0 - u1; s1 += d; q1 = fmaf(d, d, q1); d = b1 - u1; s1 += d; q1 = fmaf(d, d, q1);
    held[i] = pack_bf16(a0, a1); held[i + 1] = pack_bf16(b0, b1);
  }
}

template <int O> __device__ __forceinline__ void stage_half(Cons& c, uint32_t (&held)[64], int mode) {
  if (mode == 2) {
    uint32_t a0, a1, r0, r1;
    const uint32_t la = c.sb + OFF_LN + (c.warp * 16 + (lane_id() >> 2)) * 8;
    mbar_spin(c.sb + OFF_BAR + B_LN, 0);
    asm volatile("ld.shared.v2.b32 {%0, %1}, [%2];" : "=r"(r0), "=r"(a0) : "r"(la));
    asm volatile("ld.shared.v2.b32 {%0, %1}, [%2];" : "=r"(r1), "=r"(a1) : "r"(la + 64));
#pragma unroll
    for (int i = O; i < O + 32; i += 2) { held[i] = bf2_mul(bf2_add(held[i], a0), r0); held[i + 1] = bf2_mul(bf2_add(held[i + 1], a1), r1); }
  }
  if (O == 0 && mode == 3) {
#pragma unroll
    for (int i = 0; i < 64; i++) held[i] = bf2_mul(held[i], BF2_HALF);
  }
  stage_acquire(c);
  stage_chunks<2>(c.sb + OFF_Q0 + c.warp * 2048, 16384, held + O);
  stage_commit(c);
}

__device__ __forceinline__ void gemm_seg(float (&acc)[128], uint32_t (&held)[64], Cons& c, const Params& p, Shadow& sh, int nsteps, bool hold) {
  const bool elected = lane_id() == 0 && (c.warp & 3) < 2;
  uint32_t rel;
  asm("mapa.shared::cluster.u32 %0, %1, %2;" : "=r"(rel) : "r"(c.sb + OFF_BAR + B_GE), "r"((uint32_t)(c.warp & 1)));
  gemm_step<true>(acc, c);
  uint32_t prev = c.g.s;
  ring_adv<4>(c.g);
  int k = 1;
#define G_STEP()                                                                                                       \
  { gemm_step<false>(acc, c);                                                                                          \
    wgmma_wait<1>();                                                                                                   \
    if (elected) asm volatile("mbarrier.arrive.shared::cluster.b64 _, [%0];" :: "r"(rel + 8 * prev) : "memory");       \
    prev = c.g.s; ring_adv<4>(c.g);                                                                                    \
    k++; }
  if (sh.act != 0) {
    float u0 = 0.f, u1 = 0.f, s0 = 0.f, s1 = 0.f, q0 = 0.f, q1 = 0.f;
    const float ca = sh.act == 3 ? 0.5f : GELU_A, cb = sh.act == 3 ? 0.f : GELU_B;
    const int rb = nsteps >= ACT_REP ? 2 : 1, ra = sh.act == 2 ? 0 : rb;
#define G_STEPS(N) { _Pragma("unroll 1") for (int r = 0; r < (N); r++) G_STEP() }
#pragma unroll 1
    for (int q = 0;; q++) {
      act_block<0>(held, ca, cb, q == 0, u0, u1, s0, s1, q0, q1);
      G_STEPS(ra)
      act_block<4>(held, ca, cb, false, u0, u1, s0, s1, q0, q1);
      G_STEPS(rb)
      act_block<8>(held, ca, cb, false, u0, u1, s0, s1, q0, q1);
      G_STEPS(ra)
      act_block<12>(held, ca, cb, false, u0, u1, s0, s1, q0, q1);
      rotate16(held);
      if (q == 3) break;
      G_STEPS(rb)
    }
    if (sh.act == 2) {
      const int zi = get_item(p, 0);
      const int ln = lane_id(), row0 = (((zi >> 5) & 31) * 2 + (blockIdx.x & 1)) * 128 + c.warp * 16 + (ln >> 2), ql = ln & 3;
      const float m0 = fmaf(s0, 1.f / 64, u0), m1 = fmaf(s1, 1.f / 64, u1);
      q0 -= s0 * s0 * (1.f / 64); q1 -= s1 * s1 * (1.f / 64);
      const float mu0 = quad_sum(m0) * 0.25f, mu1 = quad_sum(m1) * 0.25f;
      q0 = quad_sum(fmaf(64.f * (m0 - mu0), m0 - mu0, q0)); q1 = quad_sum(fmaf(64.f * (m1 - mu1), m1 - mu1, q1));
      if (ql < 2) st_tagged(&g_stats[((row0 >> 7) * 8 + (zi & 31)) * 128 + (row0 & 127) + 8 * ql], ql ? mu1 : mu0, ql ? q1 : q0, load_tag(c));
      if (ln == 0) mbar_arrive(c.sb + OFF_BAR + B_PUB);
    }
  }
  const int s0 = sh.store == 0 ? -9 : k + (sh.store == 2 ? Z_DELAY : (sh.store == 1 ? Q_DELAY : 1)), s1 = sh.store == 3 ? -9 : s0 + (sh.store == 1 ? Q_GAP : Z_GAP);
  hold = hold && k + 4 < nsteps;
#pragma unroll 1
  while (k < nsteps) {
    G_STEP()
    if (k == s0) stage_half<0>(c, held, sh.store);
    else if (k == s1) stage_half<32>(c, held, sh.store);
    if (hold && k == nsteps - 2 && c.warp >= 4) named_sync(6);
  }
  if (hold && c.warp < 4) asm volatile("bar.arrive 6, 256;" ::: "memory");
  wgmma_wait<0>();
  fence_regs(acc);
  if (elected) asm volatile("mbarrier.arrive.shared::cluster.b64 _, [%0];" :: "r"(rel + 8 * prev) : "memory");
  sh.store = sh.act = 0;
}

template <bool SUB> __device__ __forceinline__ void softmax_exp(const float (&S)[64], uint32_t (&P)[32], float m0, float m1, float& s0, float& s1) {
  float a0 = 0.f, a1 = 0.f, b0 = 0.f, b1 = 0.f;
#pragma unroll
  for (int j = 0; j < 16; j++) {
    const float p0 = ex2(SUB ? S[4 * j] - m0 : S[4 * j]), p1 = ex2(SUB ? S[4 * j + 1] - m0 : S[4 * j + 1]);
    const float p2 = ex2(SUB ? S[4 * j + 2] - m1 : S[4 * j + 2]), p3 = ex2(SUB ? S[4 * j + 3] - m1 : S[4 * j + 3]);
    a0 += p0; b0 += p1; a1 += p2; b1 += p3;
    P[2 * j] = pack_bf16(p0, p1); P[2 * j + 1] = pack_bf16(p2, p3);
  }
  s0 = a0 + b0; s1 = a1 + b1;
}
__device__ __forceinline__ void row_max(const float (&S)[64], float& x0, float& x1) {
  float a0 = fmaxf(S[0], S[1]), a1 = fmaxf(S[2], S[3]);
#pragma unroll
  for (int j = 1; j < 16; j++) { a0 = fmaxf(a0, fmaxf(S[4 * j], S[4 * j + 1])); a1 = fmaxf(a1, fmaxf(S[4 * j + 2], S[4 * j + 3])); }
  x0 = quad_max(a0); x1 = quad_max(a1);
}

__device__ __forceinline__ void issue_qk(float (&S)[64], uint32_t da, uint32_t db) {
#pragma unroll
  for (int kk = 0; kk < 8; kk++) {
    const uint32_t o = (kk >> 2) * 1024 + (kk & 3) * 2;
    wgmma_m64n128k16_ss_tb0(S, DESC_HI | (da + o), DESC_HI | (db + o), kk > 0);
  }
}
__device__ __forceinline__ void issue_pv(float (&O)[64], const uint32_t (&P)[32], uint32_t db, int acc) {
#pragma unroll
  for (int kk = 0; kk < 8; kk++) wgmma_m64n128k16_rs_tb1(O, P[4 * kk], P[4 * kk + 1], P[4 * kk + 2], P[4 * kk + 3], DESC_HI | (db + kk * 128), (acc || kk > 0));
}

__device__ __forceinline__ void att_pack(const float (&O)[64], uint32_t (&pk)[32], float i0, float i1) {
#pragma unroll
  for (int j = 0; j < 16; j++) {
    pk[2 * j] = pack_bf16(O[4 * j] * i0, O[4 * j + 1] * i0);
    pk[2 * j + 1] = pack_bf16(O[4 * j + 2] * i1, O[4 * j + 3] * i1);
  }
}
__device__ __forceinline__ void att_stage(Cons& c, const uint32_t (&pk)[32], uint32_t qbuf) {
  stage_chunks<2>(c.sb + (qbuf ? OFF_Q1 : OFF_Q0) + c.warp * 2048, 16384, pk);
  stage_commit(c);
}

#define ATT_ISSUE(PIN, ACC, PV)                                                                                        \
  wgmma_fence();                                                                                                       \
  issue_qk(S, qd, kd); wgmma_commit();                                                                                 \
  if (g > 1) release_slot(c, vrel);                                                                                    \
  vready = mbar_test(vbar, vph);                                                                                       \
  if (PV) {                                                                                                            \
    mbar_spin(vbar, vph);                                                                                              \
    wgmma_fence();                                                                                                     \
    issue_pv(O, PIN, vd, ACC); wgmma_commit();                                                                         \
  } else {                                                                                                             \
    asm volatile("wgmma.commit_group.sync.aligned; // empty" ::: "memory");                                            \
  }                                                                                                                    \
  krel = kbar + (B_KE - B_KF); vrel = vbar + (B_KE - B_KF);                                                            \
  g++;                                                                                                                 \
  if (g < total) { kd = kd0 + kv.s * (KV_SLOT >> 4); kbar = bars + B_KF + 8 * kv.s; kph = kv.ph; ring_adv<5>(kv); }    \
  vd = vd0 + kv.s * (KV_SLOT >> 4); vbar = bars + B_KF + 8 * kv.s; vph = kv.ph; ring_adv<5>(kv);

#define ATT_WAIT_S()                                                                                                   \
  wgmma_wait<1>();                                                                                                     \
  fence_regs(S);                                                                                                       \
  release_slot(c, krel);                                                                                               \
  if (c.warp == 2) asm volatile("st.volatile.shared.u32 [%0], %1;" :: "r"(bars + B_PROG), "r"(g) : "memory");

#define ATT_SOFTMAX(POUT, FIRST)                                                                                       \
  fresh = false;                                                                                                       \
  _Pragma("unroll 1")                                                                                                  \
  while (true) {                                                                                                       \
    if (__builtin_expect(fresh, 0)) {                                                                                  \
      float x0, x1;                                                                                                    \
      row_max(S, x0, x1);                                                                                              \
      if (FIRST) m0 = m1 = -1e38f;                                                                                     \
      x0 = fmaxf(x0, m0); x1 = fmaxf(x1, m1);                                                                          \
      f0 = ex2(m0 - x0); f1 = ex2(m1 - x1);                                                                            \
      m0 = x0; m1 = x1; l0 *= f0; l1 *= f1;                                                                            \
      zero = false;                                                                                                    \
    }                                                                                                                  \
    if (zero) {                                                                                                        \
      softmax_exp<false>(S, POUT, m0, m1, s0, s1);                                                                     \
      bad = !(s0 <= SM_HI && s1 <= SM_HI) || ((FIRST) && (s0 < SM_LO || s1 < SM_LO));                                  \
    } else {                                                                                                           \
      softmax_exp<true>(S, POUT, m0, m1, s0, s1);                                                                      \
      bad = !(s0 <= SM_THR && s1 <= SM_THR);                                                                           \
    }                                                                                                                  \
    kready = mbar_test(kbar, kph) && vready;                                                                           \
    slow = fresh || __any_sync(0xffffffffu, bad || !kready);                                                           \
    if (__builtin_expect(!slow, 1)) break;                                                                             \
    if (fresh || !__any_sync(0xffffffffu, bad)) break;                                                                 \
    fresh = true;                                                                                                      \
  }                                                                                                                    \
  l0 += s0; l1 += s1;                                                                                                  \
  wgmma_wait<0>(); fence_regs(O);

#define ATT_RESCALE()                                                                                                  \
  { _Pragma("unroll")                                                                                                  \
    for (int i = 0; i < 16; i++) { O[4 * i] *= f0; O[4 * i + 1] *= f0; O[4 * i + 2] *= f1; O[4 * i + 3] *= f1; } }

__device__ __forceinline__ void att_stagger(const Cons& c, int g) {
  if (c.warp >= 4)
    asm volatile("{\n.reg .pred p;\n.reg .s32 v;\nLOOP:\nld.volatile.shared.s32 v, [%0];\nsetp.le.s32 p, v, %1;\n@p bra LOOP;\n}" :: "r"(c.sb + OFF_BAR + B_PROG), "r"(g) : "memory");
}

__device__ __forceinline__ void att_run(Cons& c, const Params& p, int it, int n) {
  const uint32_t bars = c.sb + OFF_BAR;
  float S[64], O[64];
  uint32_t P0[32], P1[32];
#pragma unroll
  for (int i = 0; i < 64; i++) O[i] = 0.f;
#pragma unroll
  for (int i = 0; i < 32; i++) P0[i] = P1[i] = 0u;
  fence_regs(O); fence_regs(P0); fence_regs(P1);
  float m0 = 0.f, m1 = 0.f, l0 = 0.f, l1 = 0.f, f0 = 1.f, f1 = 1.f, s0, s1, pl0 = 0.f, pl1 = 0.f;
  const int total = 16 * n;
  int g = 0;
  Ring kv = {1, 0};
  uint32_t kbar = bars + B_KF, kph = 0, vbar = bars + B_KF, vph = 0, krel, vrel = 0;
  const uint32_t kd0 = (uint32_t)make_desc(c.sb, 16, 1024), vd0 = (uint32_t)make_desc(c.sb, 16384, 1024);
  uint32_t qd = kd0 + ((OFF_Q0 + (c.warp >> 2) * 8192) >> 4), kd = kd0, vd = vd0;
  bool fresh, kready, vready, bad, slow, zero = false;
  mbar_spin(bars + B_QF, 0);
  mbar_spin(bars + B_KF, 0);
  att_stagger(c, 0);
#pragma unroll 1
  while (true) {
    ATT_ISSUE(P1, 1, g > 0)
    const bool first = ((g - 1) & 15) == 0;
    if (first) { pl0 = l0; pl1 = l1; m0 = m1 = l0 = l1 = 0.f; zero = true; }
    ATT_WAIT_S()
    ATT_SOFTMAX(P0, first)
    if (__builtin_expect(slow || first, 0)) {
      if (first) {
        if (g > 1) {
          att_pack(O, P1, __fdividef(1.f, quad_sum(pl0)), __fdividef(1.f, quad_sum(pl1)));
          att_stage(c, P1, ((g >> 4) & 1) ^ 1);
        }
      } else if (fresh) ATT_RESCALE();
      mbar_spin(kbar, kph);
      if (__any_sync(0xffffffffu, !kready)) att_stagger(c, g);
    }
    ATT_ISSUE(P0, !first, true)
    ATT_WAIT_S()
    ATT_SOFTMAX(P1, false)
    if (__builtin_expect(slow || (g & 15) == 0, 0)) {
      if (fresh) ATT_RESCALE();
      if (g == total) break;
      mbar_spin(kbar, kph);
      if (__any_sync(0xffffffffu, !kready)) att_stagger(c, g);
      if ((g & 15) == 0) {
        const int t = g >> 4;
        const uint32_t qb = t & 1;
        mbar_spin(bars + B_QF + 8 * qb, (t >> 1) & 1);
        qd = kd0 + (((qb ? OFF_Q1 : OFF_Q0) + (c.warp >> 2) * 8192) >> 4);
      }
    }
  }
  release_slot(c, vrel);
  mbar_spin(vbar, vph);
  wgmma_fence();
  issue_pv(O, P1, vd, 1); wgmma_commit();
  pl0 = __fdividef(1.f, quad_sum(l0)); pl1 = __fdividef(1.f, quad_sum(l1));
  wgmma_wait<0>();
  fence_regs(O);
  release_slot(c, vbar + (B_KE - B_KF));
  att_pack(O, P0, pl0, pl1);
  if ((get_item(p, it + n) >> 12) == T_END) {
    const uint32_t buf = c.sb + (((n - 1) & 1) ? OFF_Q1 : OFF_Q0) + c.warp * 2048;
    stage_chunks<2>(buf, 16384, P0);
    fence_async_smem();
    __syncwarp();
    if (elect_one()) {
      const int im = get_item(p, it + n - 1), col = ((im >> 5) & 31) * 128, row = ((im & 31) * 2 + (blockIdx.x & 1)) * 128 + c.warp * 16;
      tma_store_2d(&p.tm[TS_O], buf, col, row); tma_store_2d(&p.tm[TS_O], buf + 16384, col + 64, row);
      bulk_commit();
      bulk_wait<0>();
      mbar_arrive(bars + B_STG);
    }
    __syncwarp();
  } else {
    att_stage(c, P0, (n - 1) & 1);
  }
}

__global__ void __cluster_dims__(2, 1, 1) __launch_bounds__(384, 1) fused_kernel(const __grid_constant__ Params p) {
  const uint32_t sb = smem_base();
  const uint32_t bars = sb + OFF_BAR;
  const int tid = threadIdx.x, lane = tid & 31;
  const int warp_id = __shfl_sync(0xffffffffu, tid >> 5, 0), wg = warp_id >> 2;
  const uint32_t rank = blockIdx.x & 1;
  const uint16_t* items = p.items[blockIdx.x >> 1];
  const int gw = blockIdx.x * 8 + warp_id - 4;
  uint4 xv[2][4];
  if (wg != 0 && gw < SEQ / 2) {
#pragma unroll
    for (int rr = 0; rr < 2; rr++)
#pragma unroll
      for (int i = 0; i < 4; i++) xv[rr][i] = __ldg(reinterpret_cast<const uint4*>(p.x + (size_t)(gw * 2 + rr) * DM) + i * 32 + lane);
  }
  if (warp_id == 1 && lane < TM_COUNT) asm volatile("prefetch.tensormap [%0];" :: "l"(&p.tm[lane]) : "memory");
  if (tid == 0) {
    for (int i = 0; i < 4; i++) { mbar_init(bars + B_GF + 8 * i, 1); mbar_init(bars + B_GE + 8 * i, 4); }
    for (int i = 0; i < 5; i++) { mbar_init(bars + B_KF + 8 * i, 1); mbar_init(bars + B_KE + 8 * i, 4); }
    for (int i = 0; i < 2; i++) { mbar_init(bars + B_QF + 8 * i, 1); mbar_init(bars + B_QE + 8 * i, 1); }
    mbar_init(bars + B_XF, 2); mbar_init(bars + B_XR, 2); mbar_init(bars + B_STG, 8); mbar_init(bars + B_FREE, 1); mbar_init(bars + B_GO, 1); mbar_init(bars + B_LN, 2); mbar_init(bars + B_PUB, 8);
    asm volatile("fence.mbarrier_init.release.cluster;" ::: "memory");
  }
  asm volatile("barrier.cluster.arrive.relaxed.aligned;" ::: "memory");

  if (wg == 0) {
    asm volatile("setmaxnreg.dec.sync.aligned.u32 40;");
    asm volatile("barrier.cluster.wait.acquire.aligned;" ::: "memory");
    if (warp_id >= 2 && (items[0] >> 12) == T_Z2) {
      const int r = (warp_id - 2) * 64 + 2 * lane;
      const uint2* ps = &g_stats[(((items[0] >> 5) & 31) * 2 + rank) * 1024 + r];
      uint32_t tag = 0, cnt = 0;
#pragma unroll 1
      for (;;) {
        uint4 t[7];
        bool ok = cnt > 0;
#pragma unroll
        for (int i = 0; i < 7; i++) {
          t[i] = make_uint4(0, 0, 0, 0);
          if (cnt > 0) t[i] = ld_tagged2(ps + i * 128);
        }
        float u0 = 0.f, u1 = 0.f, v0 = 0.f, v1 = 0.f;
#pragma unroll
        for (int i = 0; i < 7; i++) { ok = ok && tag_ok(t[i].x, t[i].y, tag) && tag_ok(t[i].z, t[i].w, tag); u0 += untag(t[i].x); u1 += untag(t[i].z); }
        u0 *= 1.f / 7; u1 *= 1.f / 7;
#pragma unroll
        for (int i = 0; i < 7; i++) {
          const float d0 = untag(t[i].x) - u0, d1 = untag(t[i].z) - u1;
          v0 += fmaf(256.f * d0, d0, untag(t[i].y)); v1 += fmaf(256.f * d1, d1, untag(t[i].w));
        }
        const float r0 = rsqrtf(fmaxf(v0, 0.f) * (1.f / FH) + 4e-5f), r1 = rsqrtf(fmaxf(v1, 0.f) * (1.f / FH) + 4e-5f);
        asm volatile("st.shared.v4.b32 [%0], {%1, %2, %3, %4};" :: "r"(sb + OFF_LN + r * 8), "r"(pack_bf16(r0, r0)), "r"(pack_bf16(-u0, -u0)),
                     "r"(pack_bf16(r1, r1)), "r"(pack_bf16(-u1, -u1)) : "memory");
        if (__all_sync(0xffffffffu, ok)) break;
        if (cnt == 0) {
          if (lane == 0) mbar_wait_sleep(bars + B_PUB, 0, 50);
          __syncwarp();
          asm volatile("ld.volatile.shared.u32 %0, [%1];" : "=r"(tag) : "r"(bars + B_TAG));
          __nanosleep(LN_SLEEP);
        }
        trap_if(++cnt > SPIN_LIMIT);
      }
      __syncwarp();
      if (lane == 0) mbar_arrive(bars + B_LN);
      __syncwarp();
    }
    if (warp_id == 0) {
      trap_if(sb & 1023);
      Ring g = {0, 1};
      int it = 0;
      uint32_t xph = 0;
      if (elect_one()) {
#pragma unroll 1
        for (;; it++) {
          const int item = items[it], type = item >> 12, b = item & 31, row = (((item >> 5) & 31) * 2 + rank) * 128;
          if (type >= T_ATT) break;
#pragma unroll 1
          for (int seg = 0; seg < (type == T_U ? 2 : 1); seg++) {
            const CUtensorMap* tA = &p.tm[seg ? TM_WSP : TM_XN];
            const CUtensorMap* tB = &p.tm[seg ? TM_Z2 : (type == T_Q ? TM_WQ : TM_WIN)];
            const int bchunk = b * 4 + (type == T_Z2 ? 28 : 0) + rank * 2;
            const unsigned* fl = seg ? &g_flags[F_Z2 + b * 32] : &g_flags[F_XN + (row >> 2)];
            const unsigned tgt = seg ? 16 : 128;
            int k = 0;
            if (it == 0 && seg == 0) {
              for (; k < 4; k++) {
                mbar_expect_tx(bars + B_GF + 8 * k, G_STAGE);
                tma_load_3d_mc(sb + k * G_STAGE + G_A + rank * 16384, tB, k * 64, bchunk, bars + B_GF + 8 * k);
              }
              g.ph ^= 1;
            }
            if (seg || type != T_U) { flag_wait(fl, tgt); fence_async_global(); }
            for (int x = 0; x < k; x++) tma_load_2d(sb + x * G_STAGE, tA, x * 64, row, bars + B_GF + 8 * x);
            if (it == 0) asm volatile("st.volatile.shared.v4.u32 [%0], {%1, %2, %2, %2};" :: "r"(bars + B_TAG), "r"(__ldcg(&g_epoch) % 4095u + 1), "r"(0) : "memory");
#pragma unroll 1
            for (; k < (seg ? 32 : 16); k++) {
              mbar_wait(bars + B_GE + 8 * g.s, g.ph);
              const uint32_t st = sb + g.s * G_STAGE, fb = bars + B_GF + 8 * g.s;
              mbar_expect_tx(fb, G_STAGE);
              tma_load_2d(st, tA, k * 64, row, fb);
              tma_load_3d_mc(st + G_A + rank * 16384, tB, k * 64, bchunk, fb);
              ring_adv<4>(g);
            }
          }
        }
      }
      { const int e = __ffs(__ballot_sync(0xffffffffu, elect_one())) - 1; it = __shfl_sync(0xffffffffu, it, e); g.ph = __shfl_sync(0xffffffffu, g.ph, e); }
      const int n = ((items[it] >> 10) & 3) + 3;
      Ring kv = {0, 1};
      if (elect_one()) {
        int prow = 0;
        {
          const int im = items[it];
          tma_prefetch_2d(&p.tm[(im & 1) ? TM_V : TM_K], rank * 64, ((im >> 5) & 31) * SEQ + ((im & 7) >> 1) * 128);
        }
#pragma unroll 1
        for (int x = 0; x <= 32 * n; x++) {
          const int gb = x >> 1, t = gb >> 4;
          const int hrow = ((items[it + t] >> 5) & 31) * SEQ;
          const bool isv = (x & 1) || x == 32 * n;
          if (x != 1) {
            if (x == 0 || x == 2) mbar_wait(bars + B_GE + 4 * x, g.ph);
            if (x == 4) { mbar_wait(bars + B_XF, xph); xph ^= 1; }
            mbar_wait(bars + B_KE + 8 * kv.s, kv.ph);
            mbar_expect_tx(bars + B_KF + 8 * kv.s, KV_SLOT);
            tma_load_2d_mc(sb + kv.s * KV_SLOT + rank * 16384, &p.tm[isv ? TM_V : TM_K], rank * 64, isv ? prow : hrow + (gb & 15) * 128, bars + B_KF + 8 * kv.s);
            ring_adv<5>(kv);
          }
          {
            const int gp = gb + KV_PF, ip = items[it + (gp >> 4)];
            if (gp < 16 * n && ((gp ^ ip) & 7) == 0) tma_prefetch_2d(&p.tm[(x & 1) ? TM_V : TM_K], rank * 64, ((ip >> 5) & 31) * SEQ + (gp & 15) * 128);
          }
          if (x == 32 * n - 8) mbar_arrive(bars + B_GO);
          if (x & 1) prow = hrow + (gb & 15) * 128;
          if ((x & 31) == 11 && t + 1 < n) {
            const int tq = t + 1;
            const int im = items[it + tq], h = (im >> 5) & 31, m = (im & 31) * 2 + rank;
            const uint32_t qb = tq & 1;
            flag_wait(&g_flags[F_Q + m * 16 + (h >> 1)], 1);
            fence_async_global();
            mbar_wait(bars + B_QE + 8 * qb, ((tq - 1) >> 1) & 1);
            const uint32_t dst = sb + (qb ? OFF_Q1 : OFF_Q0), fb = bars + B_QF + 8 * qb;
            mbar_expect_tx(fb, 32768);
            tma_load_2d(dst, &p.tm[TM_Q], h * 128, m * 128, fb);
            tma_load_2d(dst + 16384, &p.tm[TM_Q], h * 128 + 64, m * 128, fb);
          }
        }
      }
      __syncwarp();
      it += n;
      uint32_t ready = 0;
      auto wait_head = [&](int h) {
        if ((ready >> h) & 1) return;
        uint32_t cnt = 0;
        while (true) {
          asm volatile("ld.acquire.cta.shared.u32 %0, [%1];" : "=r"(ready) : "r"(bars + B_RDY) : "memory");
          if ((ready >> h) & 1) break;
          trap_if(++cnt > SPIN_LIMIT * 8);
          __nanosleep(20);
        }
        fence_async_global();
      };
      int item = items[it];
      if ((item >> 12) == T_SA) {
        const int m = ((item >> 5) & 31) * 2 + rank, b = item & 31;
        Ring dr = kv;
        wait_head(0);
#pragma unroll 1
        for (int i = 0; i < 28 + SA_STEPS; i++) {
          {
            const bool so = i >= 28;
            const int k = so ? i - 28 : i;
            if (so) wait_head(k >> 1);
            if (elect_one()) {
              if (i < 4) { for (int x = 0; x < ((0x1022 >> (4 * i)) & 3); x++) { mbar_wait(bars + B_KE + 8 * dr.s, dr.ph); ring_adv<5>(dr); } }
              if (i == 2) { mbar_wait(bars + B_XF, xph); xph ^= 1; }
              mbar_wait(bars + B_GE + 8 * g.s, g.ph);
              const uint32_t st = sb + ((g.s + 1) & 3) * G_STAGE, fb = bars + B_GF + 8 * g.s;
              mbar_expect_tx(fb, G_STAGE);
              tma_load_2d(st, &p.tm[so ? TM_O : TM_U], k * 64, m * 128, fb);
              tma_load_3d_mc(st + G_A + rank * 16384, &p.tm[so ? TM_WO : TM_WOUT], k * 64, b * 4 + rank * 2, fb);
            }
            ring_adv<4>(g);
          }
          const int ip = i + OUT_PF;
          if (ip < 28 + SA_STEPS && elect_one()) {
            const bool so = ip >= 28;
            const int k = so ? ip - 28 : ip;
            if ((ip & 3) == b && (!so || ((ready >> (k >> 1)) & 1))) tma_prefetch_2d(&p.tm[so ? TM_O : TM_U], k * 64, m * 128);
            if ((ip & 7) == (m >> 1)) tma_prefetch_3d(&p.tm[so ? TM_WO : TM_WOUT], k * 64, b * 4 + rank * 2);
          }
          __syncwarp();
        }
        item = items[++it];
      }
      if ((item >> 12) == T_FIN) {
        const bool own = item & 4;
        const int m = ((item >> 5) & 31) * 2 + rank, col = (item & 3) * 256 + (own ? 128 : 0);
        uint32_t ps = own ? FIN_SLOT0 : kv.s;
#pragma unroll 1
        for (int i = SA_STEPS; i <= 2 * NH; i++) {
          const bool extra = i == 2 * NH - FIN_PREP;
          if (extra && own) continue;
          const int k = i > 2 * NH - FIN_PREP ? i - 1 : i;
          if (!extra) wait_head(k >> 1);
          if (elect_one()) {
            if (i == SA_STEPS) {
              for (int y = k; y < k + 4; y++) if ((ready >> (y >> 1)) & 1) tma_prefetch_2d(&p.tm[TM_O], y * 64, m * 128);
            }
            if (own && i < SA_STEPS + 5) {
              const uint32_t s0 = ((0x22100u >> (4 * ps)) - 1) & 3, s1 = ((0x32110u >> (4 * ps)) - 1) & 3;
              mbar_wait(bars + B_GE + 8 * s0, g.ph ^ (s0 < g.s)); mbar_wait(bars + B_GE + 8 * s1, g.ph ^ (s1 < g.s));
            }
            if (extra) { flag_wait(&g_flags[F_S + m * 4 + (item & 3)], 2); fence_async_global(); }
            mbar_wait(bars + B_KE + 8 * kv.s, kv.ph);
            const uint32_t dst = sb + ps * KV_SLOT, fb = bars + B_KF + 8 * kv.s;
            if (++ps == 5) ps = 0;
            mbar_expect_tx(fb, KV_SLOT);
            if (!extra) {
              tma_load_2d(dst, &p.tm[TM_O], k * 64, m * 128, fb);
              tma_load_2d_mc(dst + 16384 + rank * 8192, &p.tm[TM_WO64], col + rank * 64, k * 64, fb);
            } else {
              tma_load_2d(dst, &p.tm[TM_SA], col, m * 128, fb);
              tma_load_2d(dst + 16384, &p.tm[TM_SA], col + 64, m * 128, fb);
            }
            ring_adv<5>(kv);
          }
          __syncwarp();
        }
      }
      unsigned last = 0;
      if (lane == 0 && (item >> 12) == T_FIN) mbar_wait_sleep(bars + B_XR, 0, 100);
      if (lane == 0) { __threadfence(); last = atomicInc(&g_done, gridDim.x - 1) == gridDim.x - 1; }
      last = __shfl_sync(0xffffffffu, last, 0);
      if (last) {
        for (int i = lane; i < F_TOTAL / 4; i += 32) reinterpret_cast<uint4*>(g_flags)[i] = make_uint4(0, 0, 0, 0);
        if (lane == 0) g_epoch = g_epoch + 1;
      }
    } else if (warp_id == 1) {
      if (elect_one()) {
        uint32_t ph = 0;
        int t = 0;
#pragma unroll 1
        for (int it = 0;; it++) {
          const int item = items[it], type = item >> 12, a = (item >> 5) & 31, b = item & 31;
          if (type == T_END) break;
          const int nt = items[it + 1] >> 12;
          int row = (a * 2 + rank) * 128, col = b * 256;
          unsigned* f = &g_flags[F_S + (a * 2 + rank) * 4 + b];
          int tm = TS_G, npair = 2;
          bool quad = false;
          uint32_t src = sb + OFF_Q0;
          if (type == T_Z2) { tm = TS_Z2; f = &g_flags[F_Z2 + b * 32]; }
          else if (type == T_Q) { tm = TS_Q; f = &g_flags[F_Q + (a * 2 + rank) * 16 + b]; if (nt >= T_ATT) { npair = 0; quad = true; } }
          else if (type == T_U) { tm = TS_U; f = &g_flags[F_U + (a * 2 + rank) * 32]; npair = 0; quad = true; }
          else if (type == T_ATT) { tm = TS_O; f = &g_flags[F_O + (b * 2 + rank) * 32 + a]; npair = 1; row = (b * 2 + rank) * 128; col = a * 128; if (t & 1) src = sb + OFF_Q1; }
          else if (type == T_FIN) npair = 1;
          auto load_fin = [&](int fi, int tmi, uint32_t qb) {
            const int fc = (fi & 3) * 256 + ((fi & 4) ? 128 : 0), fr = (((fi >> 5) & 31) * 2 + rank) * 128;
            mbar_expect_tx(bars + B_QF + 8 * qb, 32768);
            tma_load_2d(sb + (qb ? OFF_Q1 : OFF_Q0), &p.tm[tmi], fc, fr, bars + B_QF + 8 * qb);
            tma_load_2d(sb + (qb ? OFF_Q1 : OFF_Q0) + 16384, &p.tm[tmi], fc + 64, fr, bars + B_QF + 8 * qb);
          };
          if (type == T_ATT && nt == T_FIN) load_fin(items[it + 1], TM_X, (t & 1) ^ 1);
          if (type == T_FIN) {
            if (!(item & 4)) { flag_wait(&g_flags[F_S + (a * 2 + rank) * 4 + (b & 3)], 1); fence_async_global(); load_fin(item, TM_G, (t & 1) ^ 1); }
            mbar_arrive(bars + B_XR);
          }
#pragma unroll 1
          for (int op = 0; op < npair + quad; op++) {
            const bool q = op == npair;
            const int c0 = (q || type == T_SA) ? col : col + op * 128;
            mbar_wait_sleep(bars + B_STG, ph, (type == T_ATT && nt == T_ATT) ? SW_ATT : SW_NS);
            if (type == T_FIN) break;
            ph ^= 1;
            fence_async_smem();
            if (type == T_SA && op == 1) { tm = TS_SA; load_fin(items[it + 1], TM_X, 1); }
            int c1 = c0;
            if (q) {
              const CUtensorMap* tb = &p.tm[type == T_U ? TM_U : TM_Q];
              tma_store_2d(tb, sb + 2 * G_STAGE, c0, row);
              tma_store_2d(tb, sb + 3 * G_STAGE, c0 + 64, row);
              bulk_commit();
              bulk_wait_read<0>();
              mbar_arrive_cta(bars + B_XF, 0); mbar_arrive_cta(bars + B_XF, 1);
              src = sb + OFF_Q1; c1 += 128;
            }
            if (nt != T_END) {
#pragma unroll 1
              for (int r = 0; r < 256; r += ST_ROWS) {
                tma_store_2d(&p.tm[tm], src + r * 128, c1 + (r >> 7) * 64, row + (r & 127));
                bulk_commit();
                bulk_wait_read<ST_FLY>();
              }
            }
            bulk_wait_read<0>();
            mbar_arrive(bars + B_FREE);
            if (type == T_ATT && (t & 1) && (nt == T_SA || (items[it + 2] >> 12) == T_SA)) { mbar_arrive_cta(bars + B_XF, 0); mbar_arrive_cta(bars + B_XF, 1); }
            if (type == T_ATT) mbar_arrive(bars + B_QE + 8 * (t & 1));
            else if (nt == T_ATT) mbar_arrive(bars + B_QE + 8);
            if (op + 1 >= npair || type == T_SA) {
              bulk_wait<0>();
              red_release(f, 1);
            }
          }
          if (type == T_ATT) t++;
          else if (t == 0 && (items[it + 1] >> 12) < T_ATT && (items[it + 2] >> 12) == T_ATT) {
            const int im = items[it + 2], h = (im >> 5) & 31, m = (im & 31) * 2 + rank;
            flag_wait(&g_flags[F_Q + m * 16 + (h >> 1)], 1);
            fence_async_global();
            mbar_expect_tx(bars + B_QF, 32768);
            tma_load_2d(sb + OFF_Q0, &p.tm[TM_Q], h * 128, m * 128, bars + B_QF);
            tma_load_2d(sb + OFF_Q0 + 16384, &p.tm[TM_Q], h * 128 + 64, m * 128, bars + B_QF);
          }
        }
      }
      __syncwarp();
    } else if (warp_id == 2) {
      int it = 0;
      while ((items[it] >> 12) <= T_ATT) it++;
      if ((items[it] >> 12) != T_END) {
        const bool sa = (items[it] >> 12) == T_SA;
        const int m = ((items[it] >> 5) & 31) * 2 + rank;
        if (lane == 0) {
          mbar_wait_sleep(bars + B_GO, 0, 500);
          if (sa) {
            const int b = items[it] & 3;
            flag_wait(&g_flags[F_U + m * 32], 7);
            fence_async_global();
            for (int y = b; y < OUT_PF; y += 4) tma_prefetch_2d(&p.tm[TM_U], y * 64, m * 128);
            tma_prefetch_3d(&p.tm[TM_WOUT], (m >> 1) * 64, b * 4 + rank * 2);
          }
          if (!sa) for (int y = m * 4 + (items[it] & 3); y < 16 * (NH - SA_HEADS); y += 64) tma_prefetch_3d(&p.tm[TM_WO], (2 * SA_HEADS + (y >> 3)) * 64, (y & 7) * 2);
        }
        __syncwarp();
        uint32_t cnt = 0;
        while (true) {
          const uint32_t r = __ballot_sync(0xffffffffu, ld_acquire(&g_flags[F_O + m * 32 + lane]) != 0);
          if (lane == 0) asm volatile("st.release.cta.shared.u32 [%0], %1;" :: "r"(bars + B_RDY), "r"(r) : "memory");
          if (r == ~0u) break;
          trap_if(++cnt > SPIN_LIMIT);
          __nanosleep(r >> 28 ? 20 : 300);
        }
        if (lane == 0) mbar_arrive(bars + B_XR);
      }
      __syncwarp();
    }
    cluster_sync_relaxed();
  } else {
    Cons c;
    c.sb = sb; c.warp = warp_id - 4; c.g = {0, 0}; c.fph = 1; c.rot = 0;
    if (gw < SEQ / 2) {
      float f[2][32], rs[2];
#pragma unroll
      for (int rr = 0; rr < 2; rr++) {
#pragma unroll
        for (int i = 0; i < 4; i++) {
          const uint4 v = xv[rr][i];
          f[rr][8 * i + 0] = bf_lo(v.x); f[rr][8 * i + 1] = bf_hi(v.x); f[rr][8 * i + 2] = bf_lo(v.y); f[rr][8 * i + 3] = bf_hi(v.y);
          f[rr][8 * i + 4] = bf_lo(v.z); f[rr][8 * i + 5] = bf_hi(v.z); f[rr][8 * i + 6] = bf_lo(v.w); f[rr][8 * i + 7] = bf_hi(v.w);
        }
        float s = 0.f;
#pragma unroll
        for (int i = 0; i < 32; i++) s += f[rr][i];
#pragma unroll
        for (int o = 16; o; o >>= 1) s += __shfl_xor_sync(0xffffffffu, s, o);
        const float mean = s * (1.f / DM);
        float q = 0.f;
#pragma unroll
        for (int i = 0; i < 32; i++) { f[rr][i] -= mean; q = fmaf(f[rr][i], f[rr][i], q); }
#pragma unroll
        for (int o = 16; o; o >>= 1) q += __shfl_xor_sync(0xffffffffu, q, o);
        rs[rr] = rsqrtf(q * (1.f / DM) + 1e-5f);
      }
      uint4* dst = reinterpret_cast<uint4*>(g_xn + (size_t)gw * 2 * DM) + lane;
#pragma unroll
      for (int rr = 0; rr < 2; rr++) {
        const float r = rs[rr];
#pragma unroll
        for (int i = 0; i < 4; i++) {
          const float* y = &f[rr][8 * i];
          dst[rr * 128 + i * 32] = make_uint4(pack_bf16(y[0] * r, y[1] * r), pack_bf16(y[2] * r, y[3] * r), pack_bf16(y[4] * r, y[5] * r), pack_bf16(y[6] * r, y[7] * r));
        }
      }
      named_sync(7);
      if (tid == 128) red_release(&g_flags[F_XN + (gw >> 6) * 32], 16);
    }
    asm volatile("setmaxnreg.inc.sync.aligned.u32 232;");
    asm volatile("barrier.cluster.wait.acquire.aligned;" ::: "memory");
    int natt = 0;
    int it = 0;
    uint32_t held[64];
#pragma unroll
    for (int i = 0; i < 64; i++) held[i] = 0u;
    Shadow sh = {0, 0};
    float facc[64];
#pragma unroll 1
    while (true) {
      const int item = get_item(p, it), type = item >> 12, a = (item >> 5) & 31;
      c.warp = fresh_warp();
      if (type == T_ATT) {
        const int n = ((item >> 10) & 3) + 3;
        att_run(c, p, it, n);
#pragma unroll
        for (int i = 0; i < 64; i++) held[i] = 0u;
        natt = n;
        it += n;
        c.rot = 1;
        if ((get_item(p, it) >> 12) == T_SA) continue;
#pragma unroll
        for (int i = 0; i < 64; i++) facc[i] = 0.f;
        break;
      }
      float acc[128];
      const bool sa = type == T_SA;
      bool more = type >= T_U;
      int nsteps = sa ? 28 : 16;
      const bool direct = (get_item(p, it + 1) >> 12) >= T_ATT;
      uint32_t bias0 = 0, bias1 = 0;
#pragma unroll 1
      while (true) {
        gemm_seg(acc, held, c, p, sh, nsteps, more || !direct || sa);
        if (type == T_Q) {
#pragma unroll
          for (int i = 0; i < 128; i++) acc[i] *= SM_C;
        }
        if (!more && direct) break;
#pragma unroll
        for (int i = 0; i < 64; i++) held[i] = pack_bf16(acc[2 * i], acc[2 * i + 1]);
        if (!more) break;
        more = false;
        nsteps = sa ? SA_STEPS : 32;
        sh.act = sa ? 3 : 1;
        if (sa) {
          sh.store = 3;
        } else {
          const int row0 = (a * 2 + rank) * 128 + c.warp * 16 + (lane_id() >> 2);
          asm volatile("ld.global.nc.u16 %0, [%1];" : "=r"(bias0) : "l"(p.b_sp + row0));
          asm volatile("ld.global.nc.u16 %0, [%1];" : "=r"(bias1) : "l"(p.b_sp + row0 + 8));
        }
      }
      c.warp = fresh_warp();
      if (direct) {
        const uint32_t hb0 = bf2_mul(bias0 * 0x10001u, BF2_HALF), hb1 = bf2_mul(bias1 * 0x10001u, BF2_HALF);
        stage_acquire(c);
#pragma unroll
        for (int h = 0; h < 2; h++) {
          uint32_t pk[32];
#pragma unroll
          for (int i = 0; i < 32; i++) pk[i] = pack_bf16(acc[64 * h + 2 * i], acc[64 * h + 2 * i + 1]);
          if (type == T_U) {
#pragma unroll
            for (int i = 0; i < 32; i++) pk[i] = bf2_mul(bf2_fma(pk[i], BF2_HALF, (i & 1) ? hb1 : hb0), held[32 * h + i]);
          }
          if (h) named_sync(5);
          stage_chunks<2>(sb + (h ? OFF_Q1 : (sa ? OFF_Q0 : 2 * G_STAGE)) + c.warp * 2048, (h || sa) ? 16384 : G_STAGE, pk);
          if (sa) break;
        }
        stage_commit(c);
        if (sa) {
#pragma unroll
          for (int i = 0; i < 64; i++) facc[i] = acc[64 + i];
          it++;
          break;
        }
      } else if (type == T_Q) {
        sh.store = 1;
      } else {
        sh.act = sh.store = 2;
      }
      it++;
    }
    const int fin = get_item(p, it);
    if ((fin >> 12) == T_FIN) {
      c.warp = fresh_warp();
      const bool own = fin & 4;
      Ring kv = {(uint32_t)(32 * natt) % 5, ((uint32_t)(32 * natt) / 5) & 1};
      uint32_t prev = 0, ps = own ? FIN_SLOT0 : kv.s;
      fence_regs(facc);
      auto fin_steps = [&](int k0, int k1) {
#pragma unroll 1
        for (int k = k0; k < k1; k++) {
          mbar_spin(bars + B_KF + 8 * kv.s, kv.ph);
          const uint32_t st = ((c.sb & 0x3FFFF) >> 4) + ps * (KV_SLOT >> 4);
          if (++ps == 5) ps = 0;
          const uint32_t da = st + (c.warp >> 2) * 512 + (1u << 16), db = st + 1024 + ((8192u >> 4) << 16);
          wgmma_fence();
#pragma unroll
          for (int kk = 0; kk < 4; kk++) wgmma_m64n128k16_ss_tb1(facc, DESC_HI | (da + kk * 2), DESC_HI | (db + kk * 128), 1);
          wgmma_commit();
          wgmma_wait<1>();
          if (k > SA_STEPS) release_slot(c, prev);
          prev = bars + B_KE + 8 * kv.s;
          ring_adv<5>(kv);
        }
      };
      const int kp = (own && ((fin >> 5) & 31) == 7) ? SA_STEPS + 5 : 2 * NH - FIN_PREP - (own ? OWN_OFF : 0);
      fin_steps(SA_STEPS, kp);
      const uint32_t ln = lane_id(), xb = own ? 1 : natt & 1;
      const uint32_t lo = c.warp * 2048 + ((ln & 15) << 7);
      uint32_t xs[32];
      auto load_tile = [&](uint32_t base, uint32_t* d) {
#pragma unroll
        for (int i = 0; i < 8; i++) ldmatrix_x4(base + lo + (i >> 2) * 16384 + (((2 * (i & 3) + (ln >> 4)) ^ (ln & 7)) << 4), d[4 * i], d[4 * i + 1], d[4 * i + 2], d[4 * i + 3]);
      };
      const uint32_t xa = sb + (xb ? OFF_Q1 : OFF_Q0);
      mbar_spin(bars + B_QF + 8 * xb, ((natt + 1 - xb) >> 1) & 1);
      load_tile(xa, xs);
      if (!own) {
        mbar_spin(bars + B_QF + 8 * (xb ^ 1), ((natt + xb) >> 1) & 1);
        load_tile(sb + (xb ? OFF_Q0 : OFF_Q1), held + 32);
      }
      float gf[64], rf[64];
#pragma unroll
      for (int i = 0; i < 32; i++) { gf[2 * i] = bf_lo(held[32 + i]); gf[2 * i + 1] = bf_hi(held[32 + i]); rf[2 * i] = bf_lo(xs[i]); rf[2 * i + 1] = bf_hi(xs[i]); }
      if (!own) {
        mbar_spin(bars + B_KF + 8 * kv.s, kv.ph);
#pragma unroll
        for (int i = 0; i < 8; i++) {
          uint32_t t[4];
          ldmatrix_x4(sb + ps * KV_SLOT + lo + (i >> 2) * 16384 + (((2 * (i & 3) + (ln >> 4)) ^ (ln & 7)) << 4), t[0], t[1], t[2], t[3]);
#pragma unroll
          for (int y = 0; y < 4; y++) {
            rf[8 * i + 2 * y] = fmaf(bf_lo(t[y]), gf[8 * i + 2 * y], rf[8 * i + 2 * y]);
            rf[8 * i + 2 * y + 1] = fmaf(bf_hi(t[y]), gf[8 * i + 2 * y + 1], rf[8 * i + 2 * y + 1]);
          }
        }
        wg_any(c.warp >= 4, false);
        release_slot(c, bars + B_KE + 8 * kv.s);
        if (++ps == 5) ps = 0;
        ring_adv<5>(kv);
      }
      fence_regs(gf); fence_regs(rf);
      fin_steps(kp, 2 * NH);
      wgmma_wait<0>();
      fence_regs(facc);
#pragma unroll
      for (int i = 0; i < 32; i++) xs[i] = pack_bf16(fmaf(facc[2 * i], gf[2 * i], rf[2 * i]), fmaf(facc[2 * i + 1], gf[2 * i + 1], rf[2 * i + 1]));
      __syncwarp();
      stage_chunks<2>(xa + c.warp * 2048, 16384, xs);
      fence_async_smem();
      __syncwarp();
      if (elect_one()) {
        const int col = (fin & 3) * 256 + (own ? 128 : 0), row = (((fin >> 5) & 31) * 2 + rank) * 128 + c.warp * 16;
        tma_store_2d(&p.tm[TS_OUT], xa + c.warp * 2048, col, row);
        tma_store_2d(&p.tm[TS_OUT], xa + c.warp * 2048 + 16384, col + 64, row);
        bulk_commit();
        mbar_arrive(bars + B_STG);
        bulk_wait_read<0>();
      }
    }
    __syncwarp();
    cluster_sync_relaxed();
  }
}

typedef CUresult (*PFN_encodeTiled)(CUtensorMap*, CUtensorMapDataType, cuuint32_t, void*, const cuuint64_t*, const cuuint64_t*, const cuuint32_t*, const cuuint32_t*,
                                    CUtensorMapInterleave, CUtensorMapSwizzle, CUtensorMapL2promotion, CUtensorMapFloatOOBfill);
static PFN_encodeTiled s_encode = nullptr;
static void tm_2d(CUtensorMap* tm, const void* ptr, uint64_t rows, uint64_t cols, uint32_t box_rows) {
  cuuint64_t dims[2] = {cols, rows}; cuuint64_t strides[1] = {cols * 2}; cuuint32_t box[2] = {64, box_rows}; cuuint32_t es[2] = {1, 1};
  CUresult r = s_encode(tm, CU_TENSOR_MAP_DATA_TYPE_BFLOAT16, 2, (void*)ptr, dims, strides, box, es, CU_TENSOR_MAP_INTERLEAVE_NONE,
                        CU_TENSOR_MAP_SWIZZLE_128B, CU_TENSOR_MAP_L2_PROMOTION_L2_128B, CU_TENSOR_MAP_FLOAT_OOB_FILL_NONE);
  if (r != CUDA_SUCCESS) fprintf(stderr, "tensor map encode failed (%d)\n", (int)r);
}
static void tm_3d(CUtensorMap* tm, const void* ptr, uint64_t rows, uint64_t cols) {
  cuuint64_t dims[3] = {64, rows, cols / 64}; cuuint64_t strides[2] = {cols * 2, 128}; cuuint32_t box[3] = {64, 64, 2}; cuuint32_t es[3] = {1, 1, 1};
  CUresult r = s_encode(tm, CU_TENSOR_MAP_DATA_TYPE_BFLOAT16, 3, (void*)ptr, dims, strides, box, es, CU_TENSOR_MAP_INTERLEAVE_NONE,
                        CU_TENSOR_MAP_SWIZZLE_128B, CU_TENSOR_MAP_L2_PROMOTION_L2_128B, CU_TENSOR_MAP_FLOAT_OOB_FILL_NONE);
  if (r != CUDA_SUCCESS) fprintf(stderr, "tensor map encode failed (%d)\n", (int)r);
}
static inline uint16_t mk(int type, int a, int b) { return (uint16_t)(type << 12 | a << 5 | b); }

static void build_schedule(Params& P) {
  int cnt[NCLUSTER];
  for (int c = 0; c < NCLUSTER; c++) { cnt[c] = 0; for (int i = 0; i < MAXI; i++) P.items[c][i] = mk(T_END, 0, 0); }
  auto phys = [](int c) { return c == 64 ? 9 : c == 65 ? 17 : c == 9 ? 64 : c == 17 ? 65 : c; };
  auto push = [&](int c, uint16_t v) { P.items[phys(c)][cnt[c]++] = v; };
  int natt[NCLUSTER], nq[NCLUSTER];
  for (int c = 0; c < NCLUSTER; c++) { natt[c] = c < 32 ? 3 : (c < 56 ? 5 : (c < 62 ? 4 : (c < 64 ? 3 : 5))); nq[c] = c < 56 ? 1 : (c < 62 ? 7 : (c < 64 ? 9 : 6)); }
  for (int c = 0; c < 56; c++) push(c, mk(T_Z2, c % 8, c / 8));
  int qi = 0;
  for (int slot = 0; slot < 9; slot++)
    for (int c = NCLUSTER - 1; c >= 0; c--) {
      const int first = c < 56 ? 1 : 0;
      if (slot >= first && slot < first + nq[c]) { push(c, mk(T_Q, qi % 8, qi / 8)); qi++; }
    }
  for (int c = 0; c < 56; c++) push(c, mk(T_U, c % 8, c / 8));
  int ai = 0;
  for (int slot = 0; slot < 5; slot++)
    for (int c = 0; c < NCLUSTER; c++) {
      const int first = c < 32 ? 0 : 5 - natt[c];
      if (slot >= first && slot < first + natt[c]) { push(c, mk(T_ATT, ai / 8, ai % 8) | (natt[c] - 3) << 10); ai++; }
    }
  for (int c = 0; c < 32; c++) push(c, mk(T_SA, c % 8, c / 8));
  for (int c = 0; c < 64; c++) push(c, mk(T_FIN, c % 8, (c / 8) % 4 | (c < 32 ? 4 : 0)));
  if (qi != 128 || ai != 256) fprintf(stderr, "bad schedule %d %d\n", qi, ai);
}

static Params s_params;
extern "C" void kernel_launch(void* const* d_in, const int* in_sizes, int n_in, void* d_out, int out_size) {
  (void)in_sizes; (void)n_in; (void)out_size;
  if (!s_encode) {
    void* fn = nullptr; cudaDriverEntryPointQueryResult qr;
    cudaGetDriverEntryPoint("cuTensorMapEncodeTiled", &fn, cudaEnableDefault, &qr);
    s_encode = (PFN_encodeTiled)fn;
    cudaFuncSetAttribute(fused_kernel, cudaFuncAttributeMaxDynamicSharedMemorySize, SMEM_BYTES);
    build_schedule(s_params);
  }
  Params& P = s_params;
  void *xn, *q, *o, *z2, *u, *gg, *sa;
  cudaGetSymbolAddress(&gg, g_g); cudaGetSymbolAddress(&sa, g_sa);
  cudaGetSymbolAddress(&xn, g_xn); cudaGetSymbolAddress(&q, g_q); cudaGetSymbolAddress(&o, g_o);
  cudaGetSymbolAddress(&z2, g_z2); cudaGetSymbolAddress(&u, g_u);
  tm_2d(&P.tm[TM_XN], xn, SEQ, DM, 128); tm_2d(&P.tm[TM_WSP], d_in[7], SEQ, SEQ, 128); tm_2d(&P.tm[TM_U], u, SEQ, FH, 128);
  tm_2d(&P.tm[TM_O], o, SEQ, HD, 128); tm_2d(&P.tm[TM_Q], q, SEQ, HD, 128); tm_2d(&P.tm[TM_X], d_in[0], SEQ, DM, 128);
  tm_2d(&P.tm[TM_K], d_in[1], NH * SEQ, 128, 128); tm_2d(&P.tm[TM_V], d_in[2], NH * SEQ, 128, 128);
  tm_2d(&P.tm[TM_SA], sa, SEQ, DM, 128); tm_2d(&P.tm[TM_G], gg, SEQ, DM, 128); tm_2d(&P.tm[TM_WO64], d_in[4], HD, DM, 64);
  tm_3d(&P.tm[TM_WIN], d_in[6], DM, FF); tm_3d(&P.tm[TM_WQ], d_in[3], DM, HD); tm_3d(&P.tm[TM_Z2], z2, SEQ, FH);
  tm_3d(&P.tm[TM_WOUT], d_in[9], FH, DM); tm_3d(&P.tm[TM_WO], d_in[4], HD, DM);
  tm_2d(&P.tm[TS_Q], q, SEQ, HD, ST_ROWS); tm_2d(&P.tm[TS_O], o, SEQ, HD, ST_ROWS); tm_2d(&P.tm[TS_Z2], z2, SEQ, FH, ST_ROWS); tm_2d(&P.tm[TS_U], u, SEQ, FH, ST_ROWS);
  tm_2d(&P.tm[TS_SA], sa, SEQ, DM, ST_ROWS); tm_2d(&P.tm[TS_G], gg, SEQ, DM, ST_ROWS); tm_2d(&P.tm[TS_OUT], d_out, SEQ, DM, 16);
  P.x = (const bf16*)d_in[0]; P.b_sp = (const bf16*)d_in[8];
  fused_kernel<<<2 * NCLUSTER, 384, SMEM_BYTES, cudaStreamPerThread>>>(P);
}
```

```cpp
#include <cuda_runtime.h>
#include <cuda_bf16.h>
#include <cuda.h>
#include <stdint.h>
#include <stdio.h>

typedef __nv_bfloat16 bf16;

constexpr int SEQ = 2048, DM = 1024, NH = 32, HD = 4096, FF = 3584, FH = 1792;

__device__ __align__(1024) bf16 g_xn[SEQ * DM];
__device__ __align__(1024) bf16 g_q[SEQ * HD];
__device__ __align__(1024) bf16 g_o[SEQ * HD];
__device__ __align__(1024) bf16 g_z2[SEQ * FH];
__device__ __align__(1024) bf16 g_u[SEQ * FH];
__device__ __align__(1024) uint2 g_stats[SEQ * 8];
__device__ __align__(1024) bf16 g_g[SEQ * DM];
__device__ __align__(1024) bf16 g_sa[SEQ * DM];
constexpr int F_XN = 0;
constexpr int F_Z2 = 512;
constexpr int F_Q = 768;
constexpr int F_U = 1024;
constexpr int F_O = 1536;
constexpr int F_S = 2048;
constexpr int F_TOTAL = 2112;
__device__ __align__(1024) unsigned g_flags[F_TOTAL];
__device__ unsigned g_done;
__device__ unsigned g_epoch;

__device__ __forceinline__ uint32_t smem_u32(const void* p) { return (uint32_t)__cvta_generic_to_shared(p); }
__device__ __forceinline__ void mbar_init(uint32_t bar, uint32_t cnt) { asm volatile("mbarrier.init.shared::cta.b64 [%0], %1;" :: "r"(bar), "r"(cnt)); }
__device__ __forceinline__ void mbar_expect_tx(uint32_t bar, uint32_t bytes) { asm volatile("mbarrier.arrive.expect_tx.shared::cta.b64 _, [%0], %1;" :: "r"(bar), "r"(bytes) : "memory"); }
__device__ __forceinline__ void mbar_arrive(uint32_t bar) { asm volatile("mbarrier.arrive.shared::cta.b64 _, [%0];" :: "r"(bar) : "memory"); }
__device__ __forceinline__ void mbar_arrive_cta(uint32_t bar, uint32_t cta) {
  asm volatile("{\n.reg .b32 ra;\nmapa.shared::cluster.u32 ra, %0, %1;\nmbarrier.arrive.shared::cluster.b64 _, [ra];\n}" :: "r"(bar), "r"(cta) : "memory");
}
__device__ __forceinline__ bool mbar_test(uint32_t bar, uint32_t parity) {
  uint32_t ok;
  asm volatile("{\n.reg .pred P1;\nmbarrier.test_wait.parity.shared::cta.b64 P1, [%1], %2;\nselp.u32 %0, 1, 0, P1;\n}" : "=r"(ok) : "r"(bar), "r"(parity) : "memory");
  return ok;
}
constexpr uint32_t SPIN_LIMIT = 1u << 22;
__device__ __forceinline__ void trap_if(bool c) { asm volatile("{\n.reg .pred P;\nsetp.ne.u32 P, %0, 0;\n@P trap;\n}" :: "r"((uint32_t)c)); }
__device__ __forceinline__ void mbar_wait(uint32_t bar, uint32_t parity) {
  asm volatile("{\n.reg .pred P1;\n.reg .u32 n;\nmbarrier.try_wait.parity.shared::cta.b64 P1, [%0], %1;\n@P1 bra DONE;\nmov.u32 n, 0;\n"
               "LOOP:\nmbarrier.try_wait.parity.shared::cta.b64 P1, [%0], %1;\n@P1 bra DONE;\nadd.u32 n, n, 1;\nsetp.gt.u32 P1, n, %2;\n@P1 trap;\nbra LOOP;\nDONE:\n}"
               :: "r"(bar), "r"(parity), "n"(SPIN_LIMIT) : "memory");
}
__device__ __forceinline__ void mbar_spin(uint32_t bar, uint32_t parity) {
  asm volatile("{\n.reg .pred P1;\nLOOP:\nmbarrier.try_wait.parity.shared::cta.b64 P1, [%0], %1;\n@!P1 bra LOOP;\n}" :: "r"(bar), "r"(parity) : "memory");
}
__device__ __forceinline__ void mbar_wait_sleep(uint32_t bar, uint32_t parity, uint32_t ns) {
  uint32_t n = 0;
  while (!mbar_test(bar, parity)) { trap_if(++n > SPIN_LIMIT * 4); __nanosleep(ns); }
}
__device__ __forceinline__ void tma_load_2d(uint32_t dst, const CUtensorMap* tm, int c0, int c1, uint32_t bar) {
  asm volatile("cp.async.bulk.tensor.2d.shared::cluster.global.mbarrier::complete_tx::bytes [%0], [%1, {%3, %4}], [%2];"
    :: "r"(dst), "l"(tm), "r"(bar), "r"(c0), "r"(c1) : "memory");
}
__device__ __forceinline__ void tma_load_2d_mc(uint32_t dst, const CUtensorMap* tm, int c0, int c1, uint32_t bar) {
  asm volatile("cp.async.bulk.tensor.2d.shared::cluster.global.mbarrier::complete_tx::bytes.multicast::cluster [%0], [%1, {%3, %4}], [%2], %5;"
    :: "r"(dst), "l"(tm), "r"(bar), "r"(c0), "r"(c1), "h"((uint16_t)3) : "memory");
}
__device__ __forceinline__ void tma_prefetch_2d(const CUtensorMap* tm, int c0, int c1) {
  asm volatile("cp.async.bulk.prefetch.tensor.2d.L2.global [%0, {%1, %2}];" :: "l"(tm), "r"(c0), "r"(c1) : "memory");
}
__device__ __forceinline__ void tma_prefetch_3d(const CUtensorMap* tm, int c1, int c2) {
  asm volatile("cp.async.bulk.prefetch.tensor.3d.L2.global [%0, {%1, %2, %3}];" :: "l"(tm), "r"(0), "r"(c1), "r"(c2) : "memory");
}
__device__ __forceinline__ void tma_load_3d_mc(uint32_t dst, const CUtensorMap* tm, int c1, int c2, uint32_t bar) {
  asm volatile("cp.async.bulk.tensor.3d.shared::cluster.global.mbarrier::complete_tx::bytes.multicast::cluster [%0], [%1, {%3, %4, %5}], [%2], %6;"
    :: "r"(dst), "l"(tm), "r"(bar), "r"(0), "r"(c1), "r"(c2), "h"((uint16_t)3) : "memory");
}
__device__ __forceinline__ void tma_store_2d(const CUtensorMap* tm, uint32_t src, int c0, int c1) {
  asm volatile("cp.async.bulk.tensor.2d.global.shared::cta.bulk_group [%0, {%2, %3}], [%1];" :: "l"(tm), "r"(src), "r"(c0), "r"(c1) : "memory");
}
__device__ __forceinline__ void bulk_commit() { asm volatile("cp.async.bulk.commit_group;" ::: "memory"); }
template <int N> __device__ __forceinline__ void bulk_wait_read() { asm volatile("cp.async.bulk.wait_group.read %0;" :: "n"(N) : "memory"); }
template <int N> __device__ __forceinline__ void bulk_wait() { asm volatile("cp.async.bulk.wait_group %0;" :: "n"(N) : "memory"); }
__device__ __forceinline__ void fence_async_smem() { asm volatile("fence.proxy.async.shared::cta;" ::: "memory"); }
__device__ __forceinline__ void fence_async_global() { asm volatile("fence.proxy.async.global;" ::: "memory"); }
__device__ __forceinline__ void wgmma_fence() { asm volatile("wgmma.fence.sync.aligned;" ::: "memory"); }
__device__ __forceinline__ void wgmma_commit() { asm volatile("wgmma.commit_group.sync.aligned;" ::: "memory"); }
template <int N> __device__ __forceinline__ void wgmma_wait() { asm volatile("wgmma.wait_group.sync.aligned %0;" :: "n"(N) : "memory"); }
__device__ __forceinline__ uint64_t make_desc(uint32_t addr, uint32_t lbo, uint32_t sbo) {
  return (uint64_t)((addr & 0x3FFFF) >> 4) | ((uint64_t)(lbo >> 4) << 16) | ((uint64_t)(sbo >> 4) << 32) | (1ull << 62);
}
template <int N> __device__ __forceinline__ void fence_regs(float (&d)[N]) {
#pragma unroll
  for (int i = 0; i < N; i++) asm volatile("" : "+f"(d[i]) :: "memory");
}
template <int N> __device__ __forceinline__ void fence_regs(uint32_t (&d)[N]) {
#pragma unroll
  for (int i = 0; i < N; i++) asm volatile("" : "+r"(d[i]) :: "memory");
}
__device__ __forceinline__ void named_sync(int id) { asm volatile("bar.sync %0, 256;" :: "r"(id) : "memory"); }
__device__ __forceinline__ void pp_sync(bool w) { asm volatile("{\n.reg .pred p;\nsetp.ne.u32 p, %0, 0;\n@p bar.sync 2, 256;\n@!p bar.sync 1, 256;\n}" :: "r"((uint32_t)w) : "memory"); }
__device__ __forceinline__ void pp_arrive(bool w) { asm volatile("{\n.reg .pred p;\nsetp.ne.u32 p, %0, 0;\n@p bar.arrive 1, 256;\n@!p bar.arrive 2, 256;\n}" :: "r"((uint32_t)w) : "memory"); }
__device__ __forceinline__ bool wg_any(bool w, bool v) {
  uint32_t r;
  asm volatile("{\n.reg .pred p, q;\nsetp.ne.u32 p, %1, 0;\nbar.red.or.pred q, %2, 128, p;\nselp.u32 %0, 1, 0, q;\n}" : "=r"(r) : "r"((uint32_t)v), "r"(w ? 4 : 3) : "memory");
  return __any_sync(0xffffffffu, r);
}
__device__ __forceinline__ int fresh_warp() { uint32_t t; asm volatile("mov.u32 %0, %%tid.x;" : "=r"(t)); return __shfl_sync(0xffffffffu, (int)(t >> 5) - 4, 0); }
__device__ __forceinline__ void cluster_sync_relaxed() { asm volatile("barrier.cluster.arrive.relaxed.aligned;\nbarrier.cluster.wait.aligned;" ::: "memory"); }
__device__ __forceinline__ unsigned ld_acquire(const unsigned* p) { unsigned v; asm volatile("ld.acquire.gpu.global.u32 %0, [%1];" : "=r"(v) : "l"(p) : "memory"); return v; }
__device__ __forceinline__ void red_release(unsigned* p, unsigned v) { asm volatile("red.release.gpu.global.add.u32 [%0], %1;" :: "l"(p), "r"(v) : "memory"); }
__device__ __forceinline__ void flag_wait(const unsigned* p, unsigned target) {
  uint32_t n = 0;
  while (ld_acquire(p) < target) { trap_if(++n > SPIN_LIMIT); __nanosleep(20); }
}
__device__ __forceinline__ void st_tagged(uint2* p, float a, float b, uint32_t tag) {
  asm volatile("{\n.reg .b64 x;\nmov.b64 x, {%1, %2};\nst.relaxed.gpu.global.b64 [%0], x;\n}" :: "l"(p),
               "r"((__float_as_uint(a) & ~63u) | (tag & 63u)), "r"((__float_as_uint(b) & ~63u) | (tag >> 6)) : "memory");
}
__device__ __forceinline__ uint4 ld_tagged2(const uint2* p) {
  uint4 v;
  asm volatile("{\n.reg .b64 x, y;\nld.relaxed.gpu.global.v2.b64 {x, y}, [%4];\nmov.b64 {%0, %1}, x;\nmov.b64 {%2, %3}, y;\n}" : "=r"(v.x), "=r"(v.y), "=r"(v.z), "=r"(v.w) : "l"(p) : "memory");
  return v;
}
__device__ __forceinline__ bool tag_ok(uint32_t a, uint32_t b, uint32_t tag) { return ((a & 63u) | ((b & 63u) << 6)) == tag; }
__device__ __forceinline__ float untag(uint32_t v) { return __uint_as_float(v & ~63u); }
__device__ __forceinline__ uint32_t pack_bf16(float lo, float hi) { uint32_t r; asm("cvt.rn.bf16x2.f32 %0, %1, %2;" : "=r"(r) : "f"(hi), "f"(lo)); return r; }
__device__ __forceinline__ uint32_t bf2_fma(uint32_t a, uint32_t b, uint32_t c) { uint32_t r; asm("fma.rn.bf16x2 %0, %1, %2, %3;" : "=r"(r) : "r"(a), "r"(b), "r"(c)); return r; }
__device__ __forceinline__ uint32_t bf2_mul(uint32_t a, uint32_t b) { uint32_t r; asm("mul.rn.bf16x2 %0, %1, %2;" : "=r"(r) : "r"(a), "r"(b)); return r; }
__device__ __forceinline__ uint32_t bf2_add(uint32_t a, uint32_t b) { uint32_t r; asm("add.rn.bf16x2 %0, %1, %2;" : "=r"(r) : "r"(a), "r"(b)); return r; }
constexpr uint32_t BF2_HALF = 0x3f003f00u;
__device__ __forceinline__ float bf_lo(uint32_t v) { return __uint_as_float(v << 16); }
__device__ __forceinline__ float bf_hi(uint32_t v) { return __uint_as_float(v & 0xffff0000u); }
__device__ __forceinline__ float ex2(float x) { float y; asm("ex2.approx.ftz.f32 %0, %1;" : "=f"(y) : "f"(x)); return y; }
__device__ __forceinline__ float tanh_fast(float x) { float y; asm("tanh.approx.f32 %0, %1;" : "=f"(y) : "f"(x)); return y; }
__device__ __forceinline__ void stmatrix_x4(uint32_t addr, uint32_t a, uint32_t b, uint32_t c, uint32_t d) {
  asm volatile("stmatrix.sync.aligned.m8n8.x4.shared.b16 [%0], {%1, %2, %3, %4};" :: "r"(addr), "r"(a), "r"(b), "r"(c), "r"(d) : "memory");
}
__device__ __forceinline__ void ldmatrix_x4(uint32_t addr, uint32_t& a, uint32_t& b, uint32_t& c, uint32_t& d) {
  asm volatile("ldmatrix.sync.aligned.m8n8.x4.shared.b16 {%0, %1, %2, %3}, [%4];" : "=r"(a), "=r"(b), "=r"(c), "=r"(d) : "r"(addr) : "memory");
}
__device__ __forceinline__ uint32_t lane_id() { uint32_t l; asm volatile("mov.u32 %0, %%laneid;" : "=r"(l)); return l; }
__device__ __forceinline__ bool elect_one() {
  uint32_t r;
  asm volatile("{\n.reg .pred P;\nelect.sync _|P, 0xffffffff;\nselp.u32 %0, 1, 0, P;\n}" : "=r"(r));
  return r;
}

__device__ __forceinline__ void wgmma_m64n128k16_ss_tb0(float (&d)[64], uint64_t da, uint64_t db, int scale_d) {
  asm volatile("{\n.reg .pred p;\nsetp.ne.b32 p, %66, 0;\n"
    "wgmma.mma_async.sync.aligned.m64n128k16.f32.bf16.bf16 "
    "{%0, %1, %2, %3, %4, %5, %6, %7, %8, %9, %10, %11, %12, %13, %14, %15, %16, %17, %18, %19, %20, %21, %22, %23, %24, %25, %26, %27, %28, %29, %30, %31, %32, %33, %34, %35, %36, %37, %38, %39, %40, %41, %42, %43, %44, %45, %46, %47, %48, %49, %50, %51, %52, %53, %54, %55, %56, %57, %58, %59, %60, %61, %62, %63}, "
    "%64, %65, p, 1, 1, 0, 0;\n}\n"
    : "+f"(d[0]), "+f"(d[1]), "+f"(d[2]), "+f"(d[3]), "+f"(d[4]), "+f"(d[5]), "+f"(d[6]), "+f"(d[7]), "+f"(d[8]), "+f"(d[9]), "+f"(d[10]), "+f"(d[11]), "+f"(d[12]), "+f"(d[13]), "+f"(d[14]), "+f"(d[15]), "+f"(d[16]), "+f"(d[17]), "+f"(d[18]), "+f"(d[19]), "+f"(d[20]), "+f"(d[21]), "+f"(d[22]), "+f"(d[23]), "+f"(d[24]), "+f"(d[25]), "+f"(d[26]), "+f"(d[27]), "+f"(d[28]), "+f"(d[29]), "+f"(d[30]), "+f"(d[31]), "+f"(d[32]), "+f"(d[33]), "+f"(d[34]), "+f"(d[35]), "+f"(d[36]), "+f"(d[37]), "+f"(d[38]), "+f"(d[39]), "+f"(d[40]), "+f"(d[41]), "+f"(d[42]), "+f"(d[43]), "+f"(d[44]), "+f"(d[45]), "+f"(d[46]), "+f"(d[47]), "+f"(d[48]), "+f"(d[49]), "+f"(d[50]), "+f"(d[51]), "+f"(d[52]), "+f"(d[53]), "+f"(d[54]), "+f"(d[55]), "+f"(d[56]), "+f"(d[57]), "+f"(d[58]), "+f"(d[59]), "+f"(d[60]), "+f"(d[61]), "+f"(d[62]), "+f"(d[63])
    : "l"(da), "l"(db), "r"(scale_d));
}
__device__ __forceinline__ void wgmma_m64n256k16_ss_tb1(float (&d)[128], uint64_t da, uint64_t db, int scale_d) {
  asm volatile("{\n.reg .pred p;\nsetp.ne.b32 p, %130, 0;\n"
    "wgmma.mma_async.sync.aligned.m64n256k16.f32.bf16.bf16 "
    "{%0, %1, %2, %3, %4, %5, %6, %7, %8, %9, %10, %11, %12, %13, %14, %15, %16, %17, %18, %19, %20, %21, %22, %23, %24, %25, %26, %27, %28, %29, %30, %31, %32, %33, %34, %35, %36, %37, %38, %39, %40, %41, %42, %43, %44, %45, %46, %47, %48, %49, %50, %51, %52, %53, %54, %55, %56, %57, %58, %59, %60, %61, %62, %63, %64, %65, %66, %67, %68, %69, %70, %71, %72, %73, %74, %75, %76, %77, %78, %79, %80, %81, %82, %83, %84, %85, %86, %87, %88, %89, %90, %91, %92, %93, %94, %95, %96, %97, %98, %99, %100, %101, %102, %103, %104, %105, %106, %107, %108, %109, %110, %111, %112, %113, %114, %115, %116, %117, %118, %119, %120, %121, %122, %123, %124, %125, %126, %127}, "
    "%128, %129, p, 1, 1, 0, 1;\n}\n"
    : "+f"(d[0]), "+f"(d[1]), "+f"(d[2]), "+f"(d[3]), "+f"(d[4]), "+f"(d[5]), "+f"(d[6]), "+f"(d[7]), "+f"(d[8]), "+f"(d[9]), "+f"(d[10]), "+f"(d[11]), "+f"(d[12]), "+f"(d[13]), "+f"(d[14]), "+f"(d[15]), "+f"(d[16]), "+f"(d[17]), "+f"(d[18]), "+f"(d[19]), "+f"(d[20]), "+f"(d[21]), "+f"(d[22]), "+f"(d[23]), "+f"(d[24]), "+f"(d[25]), "+f"(d[26]), "+f"(d[27]), "+f"(d[28]), "+f"(d[29]), "+f"(d[30]), "+f"(d[31]), "+f"(d[32]), "+f"(d[33]), "+f"(d[34]), "+f"(d[35]), "+f"(d[36]), "+f"(d[37]), "+f"(d[38]), "+f"(d[39]), "+f"(d[40]), "+f"(d[41]), "+f"(d[42]), "+f"(d[43]), "+f"(d[44]), "+f"(d[45]), "+f"(d[46]), "+f"(d[47]), "+f"(d[48]), "+f"(d[49]), "+f"(d[50]), "+f"(d[51]), "+f"(d[52]), "+f"(d[53]), "+f"(d[54]), "+f"(d[55]), "+f"(d[56]), "+f"(d[57]), "+f"(d[58]), "+f"(d[59]), "+f"(d[60]), "+f"(d[61]), "+f"(d[62]), "+f"(d[63]), "+f"(d[64]), "+f"(d[65]), "+f"(d[66]), "+f"(d[67]), "+f"(d[68]), "+f"(d[69]), "+f"(d[70]), "+f"(d[71]), "+f"(d[72]), "+f"(d[73]), "+f"(d[74]), "+f"(d[75]), "+f"(d[76]), "+f"(d[77]), "+f"(d[78]), "+f"(d[79]), "+f"(d[80]), "+f"(d[81]), "+f"(d[82]), "+f"(d[83]), "+f"(d[84]), "+f"(d[85]), "+f"(d[86]), "+f"(d[87]), "+f"(d[88]), "+f"(d[89]), "+f"(d[90]), "+f"(d[91]), "+f"(d[92]), "+f"(d[93]), "+f"(d[94]), "+f"(d[95]), "+f"(d[96]), "+f"(d[97]), "+f"(d[98]), "+f"(d[99]), "+f"(d[100]), "+f"(d[101]), "+f"(d[102]), "+f"(d[103]), "+f"(d[104]), "+f"(d[105]), "+f"(d[106]), "+f"(d[107]), "+f"(d[108]), "+f"(d[109]), "+f"(d[110]), "+f"(d[111]), "+f"(d[112]), "+f"(d[113]), "+f"(d[114]), "+f"(d[115]), "+f"(d[116]), "+f"(d[117]), "+f"(d[118]), "+f"(d[119]), "+f"(d[120]), "+f"(d[121]), "+f"(d[122]), "+f"(d[123]), "+f"(d[124]), "+f"(d[125]), "+f"(d[126]), "+f"(d[127])
    : "l"(da), "l"(db), "r"(scale_d));
}
__device__ __forceinline__ void wgmma_m64n128k16_rs_tb1(float (&d)[64], uint32_t a0, uint32_t a1, uint32_t a2, uint32_t a3, uint64_t db, int scale_d) {
  asm volatile("{\n.reg .pred p;\nsetp.ne.b32 p, %69, 0;\n"
    "wgmma.mma_async.sync.aligned.m64n128k16.f32.bf16.bf16 "
    "{%0, %1, %2, %3, %4, %5, %6, %7, %8, %9, %10, %11, %12, %13, %14, %15, %16, %17, %18, %19, %20, %21, %22, %23, %24, %25, %26, %27, %28, %29, %30, %31, %32, %33, %34, %35, %36, %37, %38, %39, %40, %41, %42, %43, %44, %45, %46, %47, %48, %49, %50, %51, %52, %53, %54, %55, %56, %57, %58, %59, %60, %61, %62, %63}, "
    "{%64, %65, %66, %67}, %68, p, 1, 1, 1;\n}\n"
    : "+f"(d[0]), "+f"(d[1]), "+f"(d[2]), "+f"(d[3]), "+f"(d[4]), "+f"(d[5]), "+f"(d[6]), "+f"(d[7]), "+f"(d[8]), "+f"(d[9]), "+f"(d[10]), "+f"(d[11]), "+f"(d[12]), "+f"(d[13]), "+f"(d[14]), "+f"(d[15]), "+f"(d[16]), "+f"(d[17]), "+f"(d[18]), "+f"(d[19]), "+f"(d[20]), "+f"(d[21]), "+f"(d[22]), "+f"(d[23]), "+f"(d[24]), "+f"(d[25]), "+f"(d[26]), "+f"(d[27]), "+f"(d[28]), "+f"(d[29]), "+f"(d[30]), "+f"(d[31]), "+f"(d[32]), "+f"(d[33]), "+f"(d[34]), "+f"(d[35]), "+f"(d[36]), "+f"(d[37]), "+f"(d[38]), "+f"(d[39]), "+f"(d[40]), "+f"(d[41]), "+f"(d[42]), "+f"(d[43]), "+f"(d[44]), "+f"(d[45]), "+f"(d[46]), "+f"(d[47]), "+f"(d[48]), "+f"(d[49]), "+f"(d[50]), "+f"(d[51]), "+f"(d[52]), "+f"(d[53]), "+f"(d[54]), "+f"(d[55]), "+f"(d[56]), "+f"(d[57]), "+f"(d[58]), "+f"(d[59]), "+f"(d[60]), "+f"(d[61]), "+f"(d[62]), "+f"(d[63])
    : "r"(a0), "r"(a1), "r"(a2), "r"(a3), "l"(db), "r"(scale_d));
}
__device__ __forceinline__ void wgmma_m64n128k16_ss_tb1(float (&d)[64], uint64_t da, uint64_t db, int scale_d) {
  asm volatile("{\n.reg .pred p;\nsetp.ne.b32 p, %66, 0;\n"
    "wgmma.mma_async.sync.aligned.m64n128k16.f32.bf16.bf16 "
    "{%0, %1, %2, %3, %4, %5, %6, %7, %8, %9, %10, %11, %12, %13, %14, %15, %16, %17, %18, %19, %20, %21, %22, %23, %24, %25, %26, %27, %28, %29, %30, %31, %32, %33, %34, %35, %36, %37, %38, %39, %40, %41, %42, %43, %44, %45, %46, %47, %48, %49, %50, %51, %52, %53, %54, %55, %56, %57, %58, %59, %60, %61, %62, %63}, "
    "%64, %65, p, 1, 1, 0, 1;\n}\n"
    : "+f"(d[0]), "+f"(d[1]), "+f"(d[2]), "+f"(d[3]), "+f"(d[4]), "+f"(d[5]), "+f"(d[6]), "+f"(d[7]), "+f"(d[8]), "+f"(d[9]), "+f"(d[10]), "+f"(d[11]), "+f"(d[12]), "+f"(d[13]), "+f"(d[14]), "+f"(d[15]), "+f"(d[16]), "+f"(d[17]), "+f"(d[18]), "+f"(d[19]), "+f"(d[20]), "+f"(d[21]), "+f"(d[22]), "+f"(d[23]), "+f"(d[24]), "+f"(d[25]), "+f"(d[26]), "+f"(d[27]), "+f"(d[28]), "+f"(d[29]), "+f"(d[30]), "+f"(d[31]), "+f"(d[32]), "+f"(d[33]), "+f"(d[34]), "+f"(d[35]), "+f"(d[36]), "+f"(d[37]), "+f"(d[38]), "+f"(d[39]), "+f"(d[40]), "+f"(d[41]), "+f"(d[42]), "+f"(d[43]), "+f"(d[44]), "+f"(d[45]), "+f"(d[46]), "+f"(d[47]), "+f"(d[48]), "+f"(d[49]), "+f"(d[50]), "+f"(d[51]), "+f"(d[52]), "+f"(d[53]), "+f"(d[54]), "+f"(d[55]), "+f"(d[56]), "+f"(d[57]), "+f"(d[58]), "+f"(d[59]), "+f"(d[60]), "+f"(d[61]), "+f"(d[62]), "+f"(d[63])
    : "l"(da), "l"(db), "r"(scale_d));
}


enum { TM_XN, TM_WSP, TM_U, TM_O, TM_Q, TM_X, TM_SA, TM_G, TM_K, TM_V, TM_WO64,
       TM_WIN, TM_WQ, TM_Z2, TM_WOUT, TM_WO, TS_Q, TS_O, TS_Z2, TS_U, TS_SA, TS_G, TS_OUT, TM_COUNT };
enum { T_Z2 = 0, T_Q = 1, T_U = 2, T_ATT = 3, T_SA = 4, T_FIN = 5, T_END = 7 };
constexpr int NCLUSTER = 66, MAXI = 14;
struct alignas(64) Params {
  const bf16* x;
  const bf16* b_sp;
  CUtensorMap tm[TM_COUNT];
  uint16_t items[NCLUSTER][MAXI];
};

constexpr uint32_t G_STAGE = 49152, G_A = 16384, KV_SLOT = 32768;
constexpr uint32_t OFF_Q1 = 163840, OFF_Q0 = 196608, OFF_BAR = 229376, OFF_LN = OFF_BAR + 256, SMEM_BYTES = OFF_LN + 1024;
constexpr uint32_t B_GF = 0, B_GE = 32, B_KF = 64, B_KE = 104, B_QF = 144, B_QE = 160, B_XF = 176, B_XR = 184, B_STG = 192, B_FREE = 200, B_GO = 208, B_LN = 216, B_TAG = 224, B_RDY = 228, B_PROG = 232, B_PUB = 248;
constexpr int SA_HEADS = 18;
constexpr int SW_NS = 40;
constexpr int ST_ROWS = 16;
constexpr int ST_FLY = 2;
constexpr int KV_PF = 4;
constexpr int FIN_PREP = 8;
constexpr int OWN_OFF = 8;
constexpr int ACT_REP = 33;
constexpr int Q_DELAY = 4;
constexpr int Q_GAP = 4;
constexpr int Z_GAP = 3;
constexpr int LN_SLEEP = 300;
constexpr int U_PACE = 200;
constexpr int Q_AT = 19;
constexpr int Z_DELAY = 4;
constexpr int SW_ATT = 800;
constexpr int OUT_PF = 8;
constexpr int SA_STEPS = 2 * SA_HEADS;
static_assert(SA_STEPS >= 36, "activation, gate store and hold-back have to fit into the second SA segment");
constexpr uint32_t FIN_SLOT0 = (0x0320u >> (4 * ((29 + SA_STEPS) & 3))) & 15;
constexpr float SM_C = 0.08838834764831845f * 1.4426950408889634f;
constexpr float GELU_A = 0.7978845608028654f, GELU_B = 0.7978845608028654f * 0.044715f;
constexpr float SM_LO = 1e-7f, SM_HI = 1e12f;
constexpr float SM_THR = 1024.f;


extern __shared__ __align__(1024) uint8_t smem_raw[];
__device__ __forceinline__ uint32_t smem_base() { return smem_u32(smem_raw); }

struct Ring { uint32_t s, ph; };
template <int N> __device__ __forceinline__ void ring_adv(Ring& r) { if (++r.s == N) { r.s = 0; r.ph ^= 1; } }

__device__ __forceinline__ int get_item(const Params& p, int i) {
  uint32_t b; asm volatile("mov.u32 %0, %%ctaid.x;" : "=r"(b));
  return p.items[b >> 1][i];
}
struct Cons {
  uint32_t sb;
  int warp;
  Ring g;
  uint32_t rot;
  uint32_t fph;
};

__device__ __forceinline__ void stage_acquire(const Cons& c) { mbar_spin(c.sb + OFF_BAR + B_FREE, c.fph); }
__device__ __forceinline__ void stage_commit(Cons& c) {
  __syncwarp();
  if (lane_id() == 0) mbar_arrive(c.sb + OFF_BAR + B_STG);
  c.fph ^= 1;
}

__device__ __forceinline__ void release_slot(const Cons& c, uint32_t bar) {
  if (lane_id() == 0 && (c.warp & 3) < 2) mbar_arrive_cta(bar, c.warp & 1);
}
constexpr uint64_t DESC_HI = (uint64_t)0x40000040u << 32;

template <bool FIRST> __device__ __forceinline__ void gemm_step(float (&acc)[128], Cons& c) {
  mbar_spin(c.sb + OFF_BAR + B_GF + 8 * c.g.s, c.g.ph);
  const uint32_t st = ((c.sb & 0x3FFFF) >> 4) + ((c.g.s + c.rot) & 3) * (G_STAGE >> 4);
  const uint32_t da = st + (c.warp >> 2) * 512 + (1u << 16), db = st + (G_A >> 4) + ((8192u >> 4) << 16);
  wgmma_fence();
#pragma unroll
  for (int kk = 0; kk < 4; kk++) wgmma_m64n256k16_ss_tb1(acc, DESC_HI | (da + kk * 2), DESC_HI | (db + kk * 128), !(FIRST && kk == 0));
  wgmma_commit();
}

template <int N> __device__ __forceinline__ void stage_chunks(uint32_t buf, uint32_t stride, const uint32_t* pk) {
  const uint32_t ln = lane_id();
  const uint32_t a = buf + ((ln & 15) << 7);
  const uint32_t x = ln & 7, hi = ln >> 4;
#pragma unroll
  for (int i = 0; i < 4 * N; i++) stmatrix_x4(a + (i >> 2) * stride + (((2 * (i & 3) + hi) ^ x) << 4), pk[4 * i], pk[4 * i + 1], pk[4 * i + 2], pk[4 * i + 3]);
}

__device__ __forceinline__ float act2_fn(float x, float a, float b) {
  return fmaf(x, tanh_fast(x * fmaf(x * x, b, a)), x);
}
__device__ __forceinline__ float quad_sum(float v) { v += __shfl_xor_sync(0xffffffffu, v, 1); v += __shfl_xor_sync(0xffffffffu, v, 2); return v; }
__device__ __forceinline__ float quad_max(float v) { v = fmaxf(v, __shfl_xor_sync(0xffffffffu, v, 1)); v = fmaxf(v, __shfl_xor_sync(0xffffffffu, v, 2)); return v; }

__device__ __forceinline__ uint32_t load_tag(const Cons& c) { uint32_t t; asm volatile("ld.volatile.shared.u32 %0, [%1];" : "=r"(t) : "r"(c.sb + OFF_BAR + B_TAG)); return t; }

struct Shadow {
  int act;
  int store;
};
__device__ __forceinline__ void rotate16(uint32_t (&h)[64]) {
#pragma unroll
  for (int i = 0; i < 16; i++)
    asm volatile("{\n.reg .b32 t;\nmov.b32 t, %0;\nmov.b32 %0, %1;\nmov.b32 %1, %2;\nmov.b32 %2, %3;\nmov.b32 %3, t;\n}" : "+r"(h[i]), "+r"(h[i + 16]), "+r"(h[i + 32]), "+r"(h[i + 48]));
}

template <int O>
__device__ __forceinline__ void act_block(uint32_t (&held)[64], float ca, float cb, bool first, float& u0, float& u1, float& s0, float& s1, float& q0, float& q1) {
#pragma unroll
  for (int i = O; i < O + 4; i += 2) {
    const float a0 = act2_fn(bf_lo(held[i]), ca, cb), a1 = act2_fn(bf_hi(held[i]), ca, cb);
    const float b0 = act2_fn(bf_lo(held[i + 1]), ca, cb), b1 = act2_fn(bf_hi(held[i + 1]), ca, cb);
    if (i == 0 && first) { u0 = a0; u1 = b0; }
    float d;
    d = a0 - u0; s0 += d; q0 = fmaf(d, d, q0); d = a1 - u0; s0 += d; q0 = fmaf(d, d, q0);
    d = b0 - u1; s1 += d; q1 = fmaf(d, d, q1); d = b1 - u1; s1 += d; q1 = fmaf(d, d, q1);
    held[i] = pack_bf16(a0, a1); held[i + 1] = pack_bf16(b0, b1);
  }
}

template <int O> __device__ __forceinline__ void stage_half(Cons& c, uint32_t (&held)[64], int mode) {
  if (mode == 2) {
    uint32_t a0, a1, r0, r1;
    const uint32_t la = c.sb + OFF_LN + (c.warp * 16 + (lane_id() >> 2)) * 8;
    mbar_spin(c.sb + OFF_BAR + B_LN, 0);
    asm volatile("ld.shared.v2.b32 {%0, %1}, [%2];" : "=r"(r0), "=r"(a0) : "r"(la));
    asm volatile("ld.shared.v2.b32 {%0, %1}, [%2];" : "=r"(r1), "=r"(a1) : "r"(la + 64));
#pragma unroll
    for (int i = O; i < O + 32; i += 2) { held[i] = bf2_mul(bf2_add(held[i], a0), r0); held[i + 1] = bf2_mul(bf2_add(held[i + 1], a1), r1); }
  }
  if (O == 0 && mode == 3) {
#pragma unroll
    for (int i = 0; i < 64; i++) held[i] = bf2_mul(held[i], BF2_HALF);
  }
  stage_acquire(c);
  stage_chunks<2>(c.sb + OFF_Q0 + c.warp * 2048, 16384, held + O);
  stage_commit(c);
}

__device__ __forceinline__ void gemm_seg(float (&acc)[128], uint32_t (&held)[64], Cons& c, const Params& p, Shadow& sh, int nsteps) {
  const bool elected = lane_id() == 0 && (c.warp & 3) < 2;
  uint32_t rel;
  asm("mapa.shared::cluster.u32 %0, %1, %2;" : "=r"(rel) : "r"(c.sb + OFF_BAR + B_GE), "r"((uint32_t)(c.warp & 1)));
  gemm_step<true>(acc, c);
  uint32_t prev = c.g.s;
  ring_adv<4>(c.g);
  int k = 1;
#define G_STEP()                                                                                                       \
  { gemm_step<false>(acc, c);                                                                                          \
    wgmma_wait<1>();                                                                                                   \
    if (elected) asm volatile("mbarrier.arrive.shared::cluster.b64 _, [%0];" :: "r"(rel + 8 * prev) : "memory");       \
    prev = c.g.s; ring_adv<4>(c.g);                                                                                    \
    k++; }
  if (sh.act != 0) {
    float u0 = 0.f, u1 = 0.f, s0 = 0.f, s1 = 0.f, q0 = 0.f, q1 = 0.f;
    const float ca = sh.act == 3 ? 0.5f : GELU_A, cb = sh.act == 3 ? 0.f : GELU_B;
    const int rb = nsteps >= ACT_REP ? 2 : 1, ra = sh.act == 2 ? 0 : rb;
#define G_STEPS(N) { _Pragma("unroll 1") for (int r = 0; r < (N); r++) G_STEP() }
#pragma unroll 1
    for (int q = 0;; q++) {
      act_block<0>(held, ca, cb, q == 0, u0, u1, s0, s1, q0, q1);
      G_STEPS(ra)
      act_block<4>(held, ca, cb, false, u0, u1, s0, s1, q0, q1);
      G_STEPS(rb)
      act_block<8>(held, ca, cb, false, u0, u1, s0, s1, q0, q1);
      G_STEPS(ra)
      act_block<12>(held, ca, cb, false, u0, u1, s0, s1, q0, q1);
      rotate16(held);
      if (q == 3) break;
      G_STEPS(rb)
    }
    if (sh.act == 2) {
      const int zi = get_item(p, 0);
      const int ln = lane_id(), row0 = (((zi >> 5) & 31) * 2 + (blockIdx.x & 1)) * 128 + c.warp * 16 + (ln >> 2), ql = ln & 3;
      const float m0 = fmaf(s0, 1.f / 64, u0), m1 = fmaf(s1, 1.f / 64, u1);
      q0 -= s0 * s0 * (1.f / 64); q1 -= s1 * s1 * (1.f / 64);
      const float mu0 = quad_sum(m0) * 0.25f, mu1 = quad_sum(m1) * 0.25f;
      q0 = quad_sum(fmaf(64.f * (m0 - mu0), m0 - mu0, q0)); q1 = quad_sum(fmaf(64.f * (m1 - mu1), m1 - mu1, q1));
      if (ql < 2) st_tagged(&g_stats[((row0 >> 7) * 8 + (zi & 31)) * 128 + (row0 & 127) + 8 * ql], ql ? mu1 : mu0, ql ? q1 : q0, load_tag(c));
      if (ln == 0) mbar_arrive(c.sb + OFF_BAR + B_PUB);
    }
  }
  const int s0 = sh.store == 0 ? -9 : k + (sh.store == 2 ? Z_DELAY : (sh.store == 1 ? Q_DELAY : 1)), s1 = sh.store == 3 ? -9 : s0 + (sh.store == 1 ? Q_GAP : Z_GAP);
#pragma unroll 1
  while (k < nsteps) {
    G_STEP()
    if (k == s0) stage_half<0>(c, held, sh.store);
    else if (k == s1) stage_half<32>(c, held, sh.store);
    if (k == nsteps - 2 && c.warp >= 4) named_sync(6);
  }
  if (c.warp < 4) asm volatile("bar.arrive 6, 256;" ::: "memory");
  wgmma_wait<0>();
  fence_regs(acc);
  if (elected) asm volatile("mbarrier.arrive.shared::cluster.b64 _, [%0];" :: "r"(rel + 8 * prev) : "memory");
  sh.store = sh.act = 0;
}

template <bool SUB> __device__ __forceinline__ void softmax_exp(const float (&S)[64], uint32_t (&P)[32], float m0, float m1, float& s0, float& s1) {
  float a0 = 0.f, a1 = 0.f, b0 = 0.f, b1 = 0.f;
#pragma unroll
  for (int j = 0; j < 16; j++) {
    const float p0 = ex2(SUB ? S[4 * j] - m0 : S[4 * j]), p1 = ex2(SUB ? S[4 * j + 1] - m0 : S[4 * j + 1]);
    const float p2 = ex2(SUB ? S[4 * j + 2] - m1 : S[4 * j + 2]), p3 = ex2(SUB ? S[4 * j + 3] - m1 : S[4 * j + 3]);
    a0 += p0; b0 += p1; a1 += p2; b1 += p3;
    P[2 * j] = pack_bf16(p0, p1); P[2 * j + 1] = pack_bf16(p2, p3);
  }
  s0 = a0 + b0; s1 = a1 + b1;
}
__device__ __forceinline__ void row_max(const float (&S)[64], float& x0, float& x1) {
  float a0 = fmaxf(S[0], S[1]), a1 = fmaxf(S[2], S[3]);
#pragma unroll
  for (int j = 1; j < 16; j++) { a0 = fmaxf(a0, fmaxf(S[4 * j], S[4 * j + 1])); a1 = fmaxf(a1, fmaxf(S[4 * j + 2], S[4 * j + 3])); }
  x0 = quad_max(a0); x1 = quad_max(a1);
}

__device__ __forceinline__ void issue_qk(float (&S)[64], uint32_t da, uint32_t db) {
#pragma unroll
  for (int kk = 0; kk < 8; kk++) {
    const uint32_t o = (kk >> 2) * 1024 + (kk & 3) * 2;
    wgmma_m64n128k16_ss_tb0(S, DESC_HI | (da + o), DESC_HI | (db + o), kk > 0);
  }
}
__device__ __forceinline__ void issue_pv(float (&O)[64], const uint32_t (&P)[32], uint32_t db, int acc) {
#pragma unroll
  for (int kk = 0; kk < 8; kk++) wgmma_m64n128k16_rs_tb1(O, P[4 * kk], P[4 * kk + 1], P[4 * kk + 2], P[4 * kk + 3], DESC_HI | (db + kk * 128), (acc || kk > 0));
}

__device__ __forceinline__ void att_pack(const float (&O)[64], uint32_t (&pk)[32], float i0, float i1) {
#pragma unroll
  for (int j = 0; j < 16; j++) {
    pk[2 * j] = pack_bf16(O[4 * j] * i0, O[4 * j + 1] * i0);
    pk[2 * j + 1] = pack_bf16(O[4 * j + 2] * i1, O[4 * j + 3] * i1);
  }
}
__device__ __forceinline__ void att_stage(Cons& c, const uint32_t (&pk)[32], uint32_t qbuf) {
  stage_chunks<2>(c.sb + (qbuf ? OFF_Q1 : OFF_Q0) + c.warp * 2048, 16384, pk);
  stage_commit(c);
}

#define ATT_ISSUE(PIN, ACC, PV)                                                                                        \
  wgmma_fence();                                                                                                       \
  issue_qk(S, qd, kd); wgmma_commit();                                                                                 \
  if (g > 1) release_slot(c, vrel);                                                                                    \
  vready = mbar_test(vbar, vph) && g >= 3 && g != 16;                                                                  \
  if (PV) {                                                                                                            \
    mbar_spin(vbar, vph);                                                                                              \
    wgmma_fence();                                                                                                     \
    issue_pv(O, PIN, vd, ACC); wgmma_commit();                                                                         \
  } else {                                                                                                             \
    asm volatile("wgmma.commit_group.sync.aligned; // empty" ::: "memory");                                            \
  }                                                                                                                    \
  krel = kbar + (B_KE - B_KF); vrel = vbar + (B_KE - B_KF);                                                            \
  g++;                                                                                                                 \
  if (g < total) { kd = kd0 + kv.s * (KV_SLOT >> 4); kbar = bars + B_KF + 8 * kv.s; kph = kv.ph; ring_adv<5>(kv); }    \
  vd = vd0 + kv.s * (KV_SLOT >> 4); vbar = bars + B_KF + 8 * kv.s; vph = kv.ph; ring_adv<5>(kv);

#define ATT_WAIT_S()                                                                                                   \
  wgmma_wait<1>();                                                                                                     \
  fence_regs(S);                                                                                                       \
  release_slot(c, krel);                                                                                               \
  if (c.warp == 2) asm volatile("st.volatile.shared.u32 [%0], %1;" :: "r"(bars + B_PROG), "r"(g) : "memory");

#define ATT_SOFTMAX(POUT, FIRST)                                                                                       \
  fresh = false;                                                                                                       \
  _Pragma("unroll 1")                                                                                                  \
  while (true) {                                                                                                       \
    if (__builtin_expect(fresh, 0)) {                                                                                  \
      float x0, x1;                                                                                                    \
      row_max(S, x0, x1);                                                                                              \
      if (FIRST) m0 = m1 = -1e38f;                                                                                     \
      x0 = fmaxf(x0, m0); x1 = fmaxf(x1, m1);                                                                          \
      f0 = ex2(m0 - x0); f1 = ex2(m1 - x1);                                                                            \
      m0 = x0; m1 = x1; l0 *= f0; l1 *= f1;                                                                            \
      zero = false;                                                                                                    \
    }                                                                                                                  \
    if (zero) {                                                                                                        \
      softmax_exp<false>(S, POUT, m0, m1, s0, s1);                                                                     \
      bad = !(s0 <= SM_HI && s1 <= SM_HI) || ((FIRST) && (s0 < SM_LO || s1 < SM_LO));                                  \
    } else {                                                                                                           \
      softmax_exp<true>(S, POUT, m0, m1, s0, s1);                                                                      \
      bad = !(s0 <= SM_THR && s1 <= SM_THR);                                                                           \
    }                                                                                                                  \
    kready = mbar_test(kbar, kph) && vready;                                                                           \
    slow = fresh || __any_sync(0xffffffffu, bad || !kready);                                                           \
    if (__builtin_expect(!slow, 1)) break;                                                                             \
    if (fresh || !__any_sync(0xffffffffu, bad)) break;                                                                 \
    fresh = true;                                                                                                      \
  }                                                                                                                    \
  l0 += s0; l1 += s1;                                                                                                  \
  wgmma_wait<0>(); fence_regs(O);

#define ATT_RESCALE()                                                                                                  \
  { _Pragma("unroll")                                                                                                  \
    for (int i = 0; i < 16; i++) { O[4 * i] *= f0; O[4 * i + 1] *= f0; O[4 * i + 2] *= f1; O[4 * i + 3] *= f1; } }

__device__ __forceinline__ void att_stagger(const Cons& c, int g) {
  if (c.warp >= 4)
    asm volatile("{\n.reg .pred p;\n.reg .s32 v;\nLOOP:\nld.volatile.shared.s32 v, [%0];\nsetp.le.s32 p, v, %1;\n@p bra LOOP;\n}" :: "r"(c.sb + OFF_BAR + B_PROG), "r"(g) : "memory");
}

__device__ __forceinline__ void att_run(Cons& c, const Params& p, int it, int n) {
  const uint32_t bars = c.sb + OFF_BAR;
  float S[64], O[64];
  uint32_t P0[32], P1[32];
#pragma unroll
  for (int i = 0; i < 64; i++) O[i] = 0.f;
#pragma unroll
  for (int i = 0; i < 32; i++) P0[i] = P1[i] = 0u;
  fence_regs(O); fence_regs(P0); fence_regs(P1);
  float m0 = 0.f, m1 = 0.f, l0 = 0.f, l1 = 0.f, f0 = 1.f, f1 = 1.f, s0, s1, pl0 = 0.f, pl1 = 0.f;
  const int total = 16 * n;
  int g = 0;
  Ring kv = {1, 0};
  uint32_t kbar = bars + B_KF, kph = 0, vbar = bars + B_KF, vph = 0, krel, vrel = 0;
  const uint32_t kd0 = (uint32_t)make_desc(c.sb, 16, 1024), vd0 = (uint32_t)make_desc(c.sb, 16384, 1024);
  uint32_t qd = kd0 + ((OFF_Q0 + (c.warp >> 2) * 8192) >> 4), kd = kd0, vd = vd0;
  bool fresh, kready, vready, bad, slow, zero = false;
  mbar_spin(bars + B_QF, 0);
  mbar_spin(bars + B_KF, 0);
  att_stagger(c, 0);
#pragma unroll 1
  while (true) {
    ATT_ISSUE(P1, 1, g > 0)
    const bool first = ((g - 1) & 15) == 0;
    if (first) { pl0 = l0; pl1 = l1; m0 = m1 = l0 = l1 = 0.f; zero = true; }
    ATT_WAIT_S()
    ATT_SOFTMAX(P0, first)
    if (__builtin_expect(slow || first, 0)) {
      if (first) {
        if (g > 1) {
          att_pack(O, P1, __fdividef(1.f, quad_sum(pl0)), __fdividef(1.f, quad_sum(pl1)));
          att_stage(c, P1, ((g >> 4) & 1) ^ 1);
        }
      } else if (fresh) ATT_RESCALE();
      mbar_spin(kbar, kph);
      if (__any_sync(0xffffffffu, !kready)) att_stagger(c, g);
    }
    ATT_ISSUE(P0, !first, true)
    ATT_WAIT_S()
    ATT_SOFTMAX(P1, false)
    if (__builtin_expect(slow || (g & 15) == 0, 0)) {
      if (fresh) ATT_RESCALE();
      if (g == total) break;
      mbar_spin(kbar, kph);
      if (__any_sync(0xffffffffu, !kready)) att_stagger(c, g);
      if ((g & 15) == 0) {
        const int t = g >> 4;
        const uint32_t qb = t & 1;
        mbar_spin(bars + B_QF + 8 * qb, (t >> 1) & 1);
        qd = kd0 + (((qb ? OFF_Q1 : OFF_Q0) + (c.warp >> 2) * 8192) >> 4);
      }
    }
  }
  release_slot(c, vrel);
  mbar_spin(vbar, vph);
  wgmma_fence();
  issue_pv(O, P1, vd, 1); wgmma_commit();
  pl0 = __fdividef(1.f, quad_sum(l0)); pl1 = __fdividef(1.f, quad_sum(l1));
  wgmma_wait<0>();
  fence_regs(O);
  release_slot(c, vbar + (B_KE - B_KF));
  att_pack(O, P0, pl0, pl1);
  if ((get_item(p, it + n) >> 12) == T_END) {
    const uint32_t buf = c.sb + (((n - 1) & 1) ? OFF_Q1 : OFF_Q0) + c.warp * 2048;
    stage_chunks<2>(buf, 16384, P0);
    fence_async_smem();
    __syncwarp();
    if (elect_one()) {
      const int im = get_item(p, it + n - 1), col = ((im >> 5) & 31) * 128, row = ((im & 7) * 2 + (blockIdx.x & 1)) * 128 + c.warp * 16;
      tma_store_2d(&p.tm[TS_O], buf, col, row); tma_store_2d(&p.tm[TS_O], buf + 16384, col + 64, row);
      bulk_commit();
      bulk_wait<0>();
      mbar_arrive(bars + B_STG);
    }
    __syncwarp();
  } else {
    att_stage(c, P0, (n - 1) & 1);
  }
}

__global__ void __cluster_dims__(2, 1, 1) __launch_bounds__(384, 1) fused_kernel(const __grid_constant__ Params p) {
  const uint32_t sb = smem_base();
  const uint32_t bars = sb + OFF_BAR;
  const int tid = threadIdx.x, lane = tid & 31;
  const int warp_id = __shfl_sync(0xffffffffu, tid >> 5, 0), wg = warp_id >> 2;
  const uint32_t rank = blockIdx.x & 1;
  const uint16_t* items = p.items[blockIdx.x >> 1];
  const int gw = blockIdx.x * 8 + warp_id - 4;
  uint4 xv[2][4];
  if (wg != 0 && gw < SEQ / 2) {
#pragma unroll
    for (int rr = 0; rr < 2; rr++)
#pragma unroll
      for (int i = 0; i < 4; i++) xv[rr][i] = __ldg(reinterpret_cast<const uint4*>(p.x + (size_t)(gw * 2 + rr) * DM) + i * 32 + lane);
  }
  if (warp_id == 1 && lane < TM_COUNT) asm volatile("prefetch.tensormap [%0];" :: "l"(&p.tm[lane]) : "memory");
  if (tid == 0) {
    for (int i = 0; i < 4; i++) { mbar_init(bars + B_GF + 8 * i, 1); mbar_init(bars + B_GE + 8 * i, 4); }
    for (int i = 0; i < 5; i++) { mbar_init(bars + B_KF + 8 * i, 1); mbar_init(bars + B_KE + 8 * i, 4); }
    for (int i = 0; i < 2; i++) { mbar_init(bars + B_QF + 8 * i, 1); mbar_init(bars + B_QE + 8 * i, 1); }
    mbar_init(bars + B_XF, 2); mbar_init(bars + B_XR, 2); mbar_init(bars + B_STG, 8); mbar_init(bars + B_FREE, 1); mbar_init(bars + B_GO, 1); mbar_init(bars + B_LN, 2); mbar_init(bars + B_PUB, 8);
    asm volatile("fence.mbarrier_init.release.cluster;" ::: "memory");
  }
  asm volatile("barrier.cluster.arrive.relaxed.aligned;" ::: "memory");

  if (wg == 0) {
    asm volatile("setmaxnreg.dec.sync.aligned.u32 40;");
    asm volatile("barrier.cluster.wait.acquire.aligned;" ::: "memory");
    if (warp_id >= 2 && (items[0] >> 12) == T_Z2) {
      const int r = (warp_id - 2) * 64 + 2 * lane;
      const uint2* ps = &g_stats[(((items[0] >> 5) & 31) * 2 + rank) * 1024 + r];
      uint32_t tag = 0, cnt = 0;
#pragma unroll 1
      for (;;) {
        uint4 t[7];
        bool ok = cnt > 0;
#pragma unroll
        for (int i = 0; i < 7; i++) {
          t[i] = make_uint4(0, 0, 0, 0);
          if (cnt > 0) t[i] = ld_tagged2(ps + i * 128);
        }
        float u0 = 0.f, u1 = 0.f, v0 = 0.f, v1 = 0.f;
#pragma unroll
        for (int i = 0; i < 7; i++) { ok = ok && tag_ok(t[i].x, t[i].y, tag) && tag_ok(t[i].z, t[i].w, tag); u0 += untag(t[i].x); u1 += untag(t[i].z); }
        u0 *= 1.f / 7; u1 *= 1.f / 7;
#pragma unroll
        for (int i = 0; i < 7; i++) {
          const float d0 = untag(t[i].x) - u0, d1 = untag(t[i].z) - u1;
          v0 += fmaf(256.f * d0, d0, untag(t[i].y)); v1 += fmaf(256.f * d1, d1, untag(t[i].w));
        }
        const float r0 = rsqrtf(fmaxf(v0, 0.f) * (1.f / FH) + 4e-5f), r1 = rsqrtf(fmaxf(v1, 0.f) * (1.f / FH) + 4e-5f);
        asm volatile("st.shared.v4.b32 [%0], {%1, %2, %3, %4};" :: "r"(sb + OFF_LN + r * 8), "r"(pack_bf16(r0, r0)), "r"(pack_bf16(-u0, -u0)),
                     "r"(pack_bf16(r1, r1)), "r"(pack_bf16(-u1, -u1)) : "memory");
        if (__all_sync(0xffffffffu, ok)) break;
        if (cnt == 0) {
          if (lane == 0) mbar_wait_sleep(bars + B_PUB, 0, 50);
          __syncwarp();
          asm volatile("ld.volatile.shared.u32 %0, [%1];" : "=r"(tag) : "r"(bars + B_TAG));
          __nanosleep(LN_SLEEP);
        }
        trap_if(++cnt > SPIN_LIMIT);
      }
      __syncwarp();
      if (lane == 0) mbar_arrive(bars + B_LN);
      __syncwarp();
    }
    if (warp_id == 0) {
      trap_if(sb & 1023);
      Ring g = {0, 1};
      int it = 0;
      uint32_t xph = 0;
      if (elect_one()) {
#pragma unroll 1
        for (;; it++) {
          const int item = items[it], type = item >> 12, b = item & 31, row = (((item >> 5) & 31) * 2 + rank) * 128;
          if (type >= T_ATT) break;
#pragma unroll 1
          for (int seg = 0; seg < (type == T_U ? 2 : 1); seg++) {
            const CUtensorMap* tA = &p.tm[seg ? TM_WSP : TM_XN];
            const CUtensorMap* tB = &p.tm[seg ? TM_Z2 : (type == T_Q ? TM_WQ : TM_WIN)];
            const int bchunk = b * 4 + (type == T_Z2 ? 28 : 0) + rank * 2;
            const unsigned* fl = seg ? &g_flags[F_Z2 + b * 32] : &g_flags[F_XN + (row >> 2)];
            const unsigned tgt = seg ? 16 : 128;
            int k = 0;
            if (it == 0 && seg == 0) {
              for (; k < 4; k++) {
                mbar_expect_tx(bars + B_GF + 8 * k, G_STAGE);
                tma_load_3d_mc(sb + k * G_STAGE + G_A + rank * 16384, tB, k * 64, bchunk, bars + B_GF + 8 * k);
              }
              g.ph ^= 1;
            }
            if (seg || type != T_U) { flag_wait(fl, tgt); fence_async_global(); }
            for (int x = 0; x < k; x++) tma_load_2d(sb + x * G_STAGE, tA, x * 64, row, bars + B_GF + 8 * x);
            if (it == 0) asm volatile("st.volatile.shared.v4.u32 [%0], {%1, %2, %2, %2};" :: "r"(bars + B_TAG), "r"(__ldcg(&g_epoch) % 4095u + 1), "r"(0) : "memory");
#pragma unroll 1
            for (; k < (seg ? 32 : 16); k++) {
              mbar_wait(bars + B_GE + 8 * g.s, g.ph);
              const uint32_t st = sb + g.s * G_STAGE, fb = bars + B_GF + 8 * g.s;
              mbar_expect_tx(fb, G_STAGE);
              tma_load_2d(st, tA, k * 64, row, fb);
              tma_load_3d_mc(st + G_A + rank * 16384, tB, k * 64, bchunk, fb);
              ring_adv<4>(g);
            }
          }
        }
      }
      { const int e = __ffs(__ballot_sync(0xffffffffu, elect_one())) - 1; it = __shfl_sync(0xffffffffu, it, e); g.ph = __shfl_sync(0xffffffffu, g.ph, e); }
      const int n = ((items[it] >> 10) & 3) + 3;
      Ring kv = {0, 1};
      if (elect_one()) {
        int prow = 0;
        {
          const int im = items[it];
          tma_prefetch_2d(&p.tm[(im & 1) ? TM_V : TM_K], rank * 64, ((im >> 5) & 31) * SEQ + ((im & 7) >> 1) * 128);
        }
#pragma unroll 1
        for (int x = 0; x <= 32 * n; x++) {
          const int gb = x >> 1, t = gb >> 4;
          const int hrow = ((items[it + t] >> 5) & 31) * SEQ;
          const bool isv = (x & 1) || x == 32 * n;
          if (x != 1) {
            if (x == 0 || x == 2) mbar_wait(bars + B_GE + 4 * x, g.ph);
            if (x == 4) { mbar_wait(bars + B_XF, xph); xph ^= 1; }
            mbar_wait(bars + B_KE + 8 * kv.s, kv.ph);
            mbar_expect_tx(bars + B_KF + 8 * kv.s, KV_SLOT);
            tma_load_2d_mc(sb + kv.s * KV_SLOT + rank * 16384, &p.tm[isv ? TM_V : TM_K], rank * 64, isv ? prow : hrow + (gb & 15) * 128, bars + B_KF + 8 * kv.s);
            ring_adv<5>(kv);
          }
          {
            const int gp = gb + KV_PF, ip = items[it + (gp >> 4)];
            if (gp < 16 * n && ((gp ^ ip) & (7 >> ((ip >> 3) & 3))) == 0) tma_prefetch_2d(&p.tm[(x & 1) ? TM_V : TM_K], rank * 64, ((ip >> 5) & 31) * SEQ + (gp & 15) * 128);
          }
          if (x == 32 * n - 8) mbar_arrive(bars + B_GO);
          if (x & 1) prow = hrow + (gb & 15) * 128;
          if ((x & 31) == Q_AT && t + 1 < n) {
            const int tq = t + 1;
            const int im = items[it + tq], h = (im >> 5) & 31, m = (im & 7) * 2 + rank;
            const uint32_t qb = tq & 1;
            flag_wait(&g_flags[F_Q + m * 16 + (h >> 1)], 1);
            fence_async_global();
            mbar_wait(bars + B_QE + 8 * qb, ((tq - 1) >> 1) & 1);
            const uint32_t dst = sb + (qb ? OFF_Q1 : OFF_Q0), fb = bars + B_QF + 8 * qb;
            mbar_expect_tx(fb, 32768);
            tma_load_2d(dst, &p.tm[TM_Q], h * 128, m * 128, fb);
            tma_load_2d(dst + 16384, &p.tm[TM_Q], h * 128 + 64, m * 128, fb);
          }
        }
      }
      __syncwarp();
      it += n;
      uint32_t ready = 0;
      auto wait_head = [&](int h) {
        if ((ready >> h) & 1) return;
        uint32_t cnt = 0;
        while (true) {
          asm volatile("ld.acquire.cta.shared.u32 %0, [%1];" : "=r"(ready) : "r"(bars + B_RDY) : "memory");
          if ((ready >> h) & 1) break;
          trap_if(++cnt > SPIN_LIMIT * 8);
          __nanosleep(20);
        }
        fence_async_global();
      };
      int item = items[it];
      if ((item >> 12) == T_SA) {
        const int m = ((item >> 5) & 31) * 2 + rank, b = item & 31;
        Ring dr = kv;
        wait_head(0);
#pragma unroll 1
        for (int i = 0; i < 28 + SA_STEPS; i++) {
          {
            const bool so = i >= 28;
            const int k = so ? i - 28 : i;
            if (so) wait_head(k >> 1);
            if (elect_one()) {
              if (i < 4) { for (int x = 0; x < ((0x1022 >> (4 * i)) & 3); x++) { mbar_wait(bars + B_KE + 8 * dr.s, dr.ph); ring_adv<5>(dr); } }
              if (i == 2) { mbar_wait(bars + B_XF, xph); xph ^= 1; }
              mbar_wait(bars + B_GE + 8 * g.s, g.ph);
              const uint32_t st = sb + ((g.s + 1) & 3) * G_STAGE, fb = bars + B_GF + 8 * g.s;
              mbar_expect_tx(fb, G_STAGE);
              tma_load_2d(st, &p.tm[so ? TM_O : TM_U], k * 64, m * 128, fb);
              tma_load_3d_mc(st + G_A + rank * 16384, &p.tm[so ? TM_WO : TM_WOUT], k * 64, b * 4 + rank * 2, fb);
            }
            ring_adv<4>(g);
          }
          const int ip = i + OUT_PF;
          if (ip < 28 + SA_STEPS && elect_one()) {
            const bool so = ip >= 28;
            const int k = so ? ip - 28 : ip;
            if ((ip & 3) == b && (!so || ((ready >> (k >> 1)) & 1))) tma_prefetch_2d(&p.tm[so ? TM_O : TM_U], k * 64, m * 128);
            if ((ip & 7) == (m >> 1)) tma_prefetch_3d(&p.tm[so ? TM_WO : TM_WOUT], k * 64, b * 4 + rank * 2);
          }
          __syncwarp();
        }
        item = items[++it];
      }
      if ((item >> 12) == T_FIN) {
        const bool own = item & 4;
        const int m = ((item >> 5) & 31) * 2 + rank, col = (item & 3) * 256 + (own ? 128 : 0);
        uint32_t ps = own ? FIN_SLOT0 : kv.s;
#pragma unroll 1
        for (int i = SA_STEPS; i <= 2 * NH; i++) {
          const bool extra = i == 2 * NH - FIN_PREP;
          if (extra && own) continue;
          const int k = i > 2 * NH - FIN_PREP ? i - 1 : i;
          if (!extra) wait_head(k >> 1);
          if (elect_one()) {
            if (i == SA_STEPS) {
              for (int y = k; y < k + 4; y++) if ((ready >> (y >> 1)) & 1) tma_prefetch_2d(&p.tm[TM_O], y * 64, m * 128);
            }
            if (own && i < SA_STEPS + 5) {
              const uint32_t s0 = ((0x22100u >> (4 * ps)) - 1) & 3, s1 = ((0x32110u >> (4 * ps)) - 1) & 3;
              mbar_wait(bars + B_GE + 8 * s0, g.ph ^ (s0 < g.s)); mbar_wait(bars + B_GE + 8 * s1, g.ph ^ (s1 < g.s));
            }
            if (extra) { flag_wait(&g_flags[F_S + m * 4 + (item & 3)], 2); fence_async_global(); }
            mbar_wait(bars + B_KE + 8 * kv.s, kv.ph);
            const uint32_t dst = sb + ps * KV_SLOT, fb = bars + B_KF + 8 * kv.s;
            if (++ps == 5) ps = 0;
            mbar_expect_tx(fb, KV_SLOT);
            if (!extra) {
              tma_load_2d(dst, &p.tm[TM_O], k * 64, m * 128, fb);
              tma_load_2d_mc(dst + 16384 + rank * 8192, &p.tm[TM_WO64], col + rank * 64, k * 64, fb);
            } else {
              tma_load_2d(dst, &p.tm[TM_SA], col, m * 128, fb);
              tma_load_2d(dst + 16384, &p.tm[TM_SA], col + 64, m * 128, fb);
            }
            ring_adv<5>(kv);
          }
          __syncwarp();
        }
      }
      unsigned last = 0;
      if (lane == 0 && (item >> 12) == T_FIN) mbar_wait_sleep(bars + B_XR, 0, 100);
      if (lane == 0) { __threadfence(); last = atomicInc(&g_done, gridDim.x - 1) == gridDim.x - 1; }
      last = __shfl_sync(0xffffffffu, last, 0);
      if (last) {
        for (int i = lane; i < F_TOTAL / 4; i += 32) reinterpret_cast<uint4*>(g_flags)[i] = make_uint4(0, 0, 0, 0);
        if (lane == 0) g_epoch = g_epoch + 1;
      }
    } else if (warp_id == 1) {
      if (elect_one()) {
        uint32_t ph = 0;
        int t = 0;
#pragma unroll 1
        for (int it = 0;; it++) {
          const int item = items[it], type = item >> 12, a = (item >> 5) & 31, b = item & 31;
          if (type == T_END) break;
          const int nt = items[it + 1] >> 12;
          int row = (a * 2 + rank) * 128, col = b * 256;
          unsigned* f = &g_flags[F_S + (a * 2 + rank) * 4 + b];
          int tm = TS_G, npair = 2;
          bool quad = false;
          uint32_t src = sb + OFF_Q0;
          if (type == T_Z2) { tm = TS_Z2; f = &g_flags[F_Z2 + b * 32]; }
          else if (type == T_Q) { tm = TS_Q; f = &g_flags[F_Q + (a * 2 + rank) * 16 + b]; if (nt >= T_ATT) { npair = 0; quad = true; } }
          else if (type == T_U) { tm = TS_U; f = &g_flags[F_U + (a * 2 + rank) * 32]; npair = 0; quad = true; }
          else if (type == T_ATT) { tm = TS_O; f = &g_flags[F_O + ((b & 7) * 2 + rank) * 32 + a]; npair = 1; row = ((b & 7) * 2 + rank) * 128; col = a * 128; if (t & 1) src = sb + OFF_Q1; }
          else if (type == T_FIN) npair = 1;
          auto load_fin = [&](int fi, int tmi, uint32_t qb) {
            const int fc = (fi & 3) * 256 + ((fi & 4) ? 128 : 0), fr = (((fi >> 5) & 31) * 2 + rank) * 128;
            mbar_expect_tx(bars + B_QF + 8 * qb, 32768);
            tma_load_2d(sb + (qb ? OFF_Q1 : OFF_Q0), &p.tm[tmi], fc, fr, bars + B_QF + 8 * qb);
            tma_load_2d(sb + (qb ? OFF_Q1 : OFF_Q0) + 16384, &p.tm[tmi], fc + 64, fr, bars + B_QF + 8 * qb);
          };
          if (type == T_ATT && nt == T_FIN) load_fin(items[it + 1], TM_X, (t & 1) ^ 1);
          if (type == T_FIN) {
            if (!(item & 4)) { flag_wait(&g_flags[F_S + (a * 2 + rank) * 4 + (b & 3)], 1); fence_async_global(); load_fin(item, TM_G, (t & 1) ^ 1); }
            mbar_arrive(bars + B_XR);
          }
#pragma unroll 1
          for (int op = 0; op < npair + quad; op++) {
            const bool q = op == npair;
            const int c0 = (q || type == T_SA) ? col : col + op * 128;
            mbar_wait_sleep(bars + B_STG, ph, (type == T_ATT && nt == T_ATT) ? SW_ATT : SW_NS);
            if (type == T_FIN) break;
            ph ^= 1;
            fence_async_smem();
            if (type == T_SA && op == 1) { tm = TS_SA; load_fin(items[it + 1], TM_X, 1); }
            int c1 = c0;
            if (q) {
              const CUtensorMap* tb = &p.tm[type == T_U ? TM_U : TM_Q];
              tma_store_2d(tb, sb + 2 * G_STAGE, c0, row);
              tma_store_2d(tb, sb + 3 * G_STAGE, c0 + 64, row);
              bulk_commit();
              bulk_wait_read<0>();
              mbar_arrive_cta(bars + B_XF, 0); mbar_arrive_cta(bars + B_XF, 1);
              src = sb + OFF_Q1; c1 += 128;
            }
            if (nt != T_END) {
#pragma unroll 1
              for (int r = 0; r < 256; r += ST_ROWS) {
                tma_store_2d(&p.tm[tm], src + r * 128, c1 + (r >> 7) * 64, row + (r & 127));
                bulk_commit();
                bulk_wait_read<ST_FLY>();
                if (q) __nanosleep(U_PACE);
              }
            }
            bulk_wait_read<0>();
            mbar_arrive(bars + B_FREE);
            if (type == T_ATT && (t & 1) && (nt == T_SA || (items[it + 2] >> 12) == T_SA)) { mbar_arrive_cta(bars + B_XF, 0); mbar_arrive_cta(bars + B_XF, 1); }
            if (type == T_ATT) mbar_arrive(bars + B_QE + 8 * (t & 1));
            else if (nt == T_ATT) mbar_arrive(bars + B_QE + 8);
            if (op + 1 >= npair || type == T_SA) {
              bulk_wait<0>();
              red_release(f, 1);
            }
          }
          if (type == T_ATT) t++;
          else if (t == 0 && (items[it + 1] >> 12) < T_ATT && (items[it + 2] >> 12) == T_ATT) {
            const int im = items[it + 2], h = (im >> 5) & 31, m = (im & 7) * 2 + rank;
            flag_wait(&g_flags[F_Q + m * 16 + (h >> 1)], 1);
            fence_async_global();
            mbar_expect_tx(bars + B_QF, 32768);
            tma_load_2d(sb + OFF_Q0, &p.tm[TM_Q], h * 128, m * 128, bars + B_QF);
            tma_load_2d(sb + OFF_Q0 + 16384, &p.tm[TM_Q], h * 128 + 64, m * 128, bars + B_QF);
          }
        }
      }
      __syncwarp();
    } else if (warp_id == 2) {
      int it = 0;
      while ((items[it] >> 12) <= T_ATT) it++;
      if ((items[it] >> 12) != T_END) {
        const bool sa = (items[it] >> 12) == T_SA;
        const int m = ((items[it] >> 5) & 31) * 2 + rank;
        if (lane == 0) {
          mbar_wait_sleep(bars + B_GO, 0, 500);
          if (sa) {
            const int b = items[it] & 3;
            flag_wait(&g_flags[F_U + m * 32], 7);
            fence_async_global();
            for (int y = b; y < OUT_PF; y += 4) tma_prefetch_2d(&p.tm[TM_U], y * 64, m * 128);
            tma_prefetch_3d(&p.tm[TM_WOUT], (m >> 1) * 64, b * 4 + rank * 2);
          }
          if (!sa) for (int y = m * 4 + (items[it] & 3); y < 16 * (NH - SA_HEADS); y += 64) tma_prefetch_3d(&p.tm[TM_WO], (2 * SA_HEADS + (y >> 3)) * 64, (y & 7) * 2);
        }
        __syncwarp();
        uint32_t cnt = 0;
        while (true) {
          const uint32_t r = __ballot_sync(0xffffffffu, ld_acquire(&g_flags[F_O + m * 32 + lane]) != 0);
          if (lane == 0) asm volatile("st.release.cta.shared.u32 [%0], %1;" :: "r"(bars + B_RDY), "r"(r) : "memory");
          if (r == ~0u) break;
          trap_if(++cnt > SPIN_LIMIT);
          __nanosleep(r >> 28 ? 20 : 300);
        }
        if (lane == 0) mbar_arrive(bars + B_XR);
      }
      __syncwarp();
    }
    cluster_sync_relaxed();
  } else {
    Cons c;
    c.sb = sb; c.warp = warp_id - 4; c.g = {0, 0}; c.fph = 1; c.rot = 0;
    if (gw < SEQ / 2) {
      float f[2][32], rs[2];
#pragma unroll
      for (int rr = 0; rr < 2; rr++) {
#pragma unroll
        for (int i = 0; i < 4; i++) {
          const uint4 v = xv[rr][i];
          f[rr][8 * i + 0] = bf_lo(v.x); f[rr][8 * i + 1] = bf_hi(v.x); f[rr][8 * i + 2] = bf_lo(v.y); f[rr][8 * i + 3] = bf_hi(v.y);
          f[rr][8 * i + 4] = bf_lo(v.z); f[rr][8 * i + 5] = bf_hi(v.z); f[rr][8 * i + 6] = bf_lo(v.w); f[rr][8 * i + 7] = bf_hi(v.w);
        }
        float s = 0.f;
#pragma unroll
        for (int i = 0; i < 32; i++) s += f[rr][i];
#pragma unroll
        for (int o = 16; o; o >>= 1) s += __shfl_xor_sync(0xffffffffu, s, o);
        const float mean = s * (1.f / DM);
        float q = 0.f;
#pragma unroll
        for (int i = 0; i < 32; i++) { f[rr][i] -= mean; q = fmaf(f[rr][i], f[rr][i], q); }
#pragma unroll
        for (int o = 16; o; o >>= 1) q += __shfl_xor_sync(0xffffffffu, q, o);
        rs[rr] = rsqrtf(q * (1.f / DM) + 1e-5f);
      }
      uint4* dst = reinterpret_cast<uint4*>(g_xn + (size_t)gw * 2 * DM) + lane;
#pragma unroll
      for (int rr = 0; rr < 2; rr++) {
        const float r = rs[rr];
#pragma unroll
        for (int i = 0; i < 4; i++) {
          const float* y = &f[rr][8 * i];
          dst[rr * 128 + i * 32] = make_uint4(pack_bf16(y[0] * r, y[1] * r), pack_bf16(y[2] * r, y[3] * r), pack_bf16(y[4] * r, y[5] * r), pack_bf16(y[6] * r, y[7] * r));
        }
      }
      named_sync(7);
      if (tid == 128) red_release(&g_flags[F_XN + (gw >> 6) * 32], 16);
    }
    asm volatile("setmaxnreg.inc.sync.aligned.u32 232;");
    asm volatile("barrier.cluster.wait.acquire.aligned;" ::: "memory");
    int natt = 0;
    int it = 0;
    uint32_t held[64];
#pragma unroll
    for (int i = 0; i < 64; i++) held[i] = 0u;
    Shadow sh = {0, 0};
    float facc[64];
#pragma unroll 1
    while (true) {
      const int item = get_item(p, it), type = item >> 12, a = (item >> 5) & 31;
      c.warp = fresh_warp();
      if (type == T_ATT) {
        const int n = ((item >> 10) & 3) + 3;
        att_run(c, p, it, n);
#pragma unroll
        for (int i = 0; i < 64; i++) held[i] = 0u;
        natt = n;
        it += n;
        c.rot = 1;
        if ((get_item(p, it) >> 12) == T_SA) continue;
#pragma unroll
        for (int i = 0; i < 64; i++) facc[i] = 0.f;
        break;
      }
      float acc[128];
      const bool sa = type == T_SA;
      bool more = type >= T_U;
      int nsteps = sa ? 28 : 16;
      const bool direct = (get_item(p, it + 1) >> 12) >= T_ATT;
      uint32_t bias0 = 0, bias1 = 0;
#pragma unroll 1
      while (true) {
        gemm_seg(acc, held, c, p, sh, nsteps);
        if (!more && direct && !sa) pp_arrive(c.warp >= 4);
        if (type == T_Q) {
#pragma unroll
          for (int i = 0; i < 128; i++) acc[i] *= SM_C;
        }
        if (!more && direct) break;
#pragma unroll
        for (int i = 0; i < 64; i++) held[i] = pack_bf16(acc[2 * i], acc[2 * i + 1]);
        if (!more) break;
        more = false;
        nsteps = sa ? SA_STEPS : 32;
        sh.act = sa ? 3 : 1;
        if (sa) {
          sh.store = 3;
        } else {
          const int row0 = (a * 2 + rank) * 128 + c.warp * 16 + (lane_id() >> 2);
          asm volatile("ld.global.nc.u16 %0, [%1];" : "=r"(bias0) : "l"(p.b_sp + row0));
          asm volatile("ld.global.nc.u16 %0, [%1];" : "=r"(bias1) : "l"(p.b_sp + row0 + 8));
        }
      }
      c.warp = fresh_warp();
      if (direct) {
        const uint32_t hb0 = bf2_mul(bias0 * 0x10001u, BF2_HALF), hb1 = bf2_mul(bias1 * 0x10001u, BF2_HALF);
        stage_acquire(c);
#pragma unroll
        for (int h = 0; h < 2; h++) {
          uint32_t pk[32];
#pragma unroll
          for (int i = 0; i < 32; i++) pk[i] = pack_bf16(acc[64 * h + 2 * i], acc[64 * h + 2 * i + 1]);
          if (type == T_U) {
#pragma unroll
            for (int i = 0; i < 32; i++) pk[i] = bf2_mul(bf2_fma(pk[i], BF2_HALF, (i & 1) ? hb1 : hb0), held[32 * h + i]);
          }
          if (h) pp_sync(c.warp >= 4);
          stage_chunks<2>(sb + (h ? OFF_Q1 : (sa ? OFF_Q0 : 2 * G_STAGE)) + c.warp * 2048, (h || sa) ? 16384 : G_STAGE, pk);
          if (sa) break;
        }
        stage_commit(c);
        if (sa) {
#pragma unroll
          for (int i = 0; i < 64; i++) facc[i] = acc[64 + i];
          it++;
          break;
        }
      } else if (type == T_Q) {
        sh.store = 1;
      } else {
        sh.act = sh.store = 2;
      }
      it++;
    }
    const int fin = get_item(p, it);
    if ((fin >> 12) == T_FIN) {
      c.warp = fresh_warp();
      const bool own = fin & 4;
      Ring kv = {(uint32_t)(32 * natt) % 5, ((uint32_t)(32 * natt) / 5) & 1};
      uint32_t prev = 0, ps = own ? FIN_SLOT0 : kv.s;
      fence_regs(facc);
      auto fin_steps = [&](int k0, int k1) {
#pragma unroll 1
        for (int k = k0; k < k1; k++) {
          mbar_spin(bars + B_KF + 8 * kv.s, kv.ph);
          const uint32_t st = ((c.sb & 0x3FFFF) >> 4) + ps * (KV_SLOT >> 4);
          if (++ps == 5) ps = 0;
          const uint32_t da = st + (c.warp >> 2) * 512 + (1u << 16), db = st + 1024 + ((8192u >> 4) << 16);
          wgmma_fence();
#pragma unroll
          for (int kk = 0; kk < 4; kk++) wgmma_m64n128k16_ss_tb1(facc, DESC_HI | (da + kk * 2), DESC_HI | (db + kk * 128), 1);
          wgmma_commit();
          wgmma_wait<1>();
          if (k > SA_STEPS) release_slot(c, prev);
          prev = bars + B_KE + 8 * kv.s;
          ring_adv<5>(kv);
        }
      };
      const int kp = (own && ((fin >> 5) & 31) == 7) ? SA_STEPS + 5 : 2 * NH - FIN_PREP - (own ? OWN_OFF : 0);
      fin_steps(SA_STEPS, kp);
      const uint32_t ln = lane_id(), xb = own ? 1 : natt & 1;
      const uint32_t lo = c.warp * 2048 + ((ln & 15) << 7);
      uint32_t xs[32];
      auto load_tile = [&](uint32_t base, uint32_t* d) {
#pragma unroll
        for (int i = 0; i < 8; i++) ldmatrix_x4(base + lo + (i >> 2) * 16384 + (((2 * (i & 3) + (ln >> 4)) ^ (ln & 7)) << 4), d[4 * i], d[4 * i + 1], d[4 * i + 2], d[4 * i + 3]);
      };
      const uint32_t xa = sb + (xb ? OFF_Q1 : OFF_Q0);
      mbar_spin(bars + B_QF + 8 * xb, ((natt + 1 - xb) >> 1) & 1);
      load_tile(xa, xs);
      if (!own) {
        mbar_spin(bars + B_QF + 8 * (xb ^ 1), ((natt + xb) >> 1) & 1);
        load_tile(sb + (xb ? OFF_Q0 : OFF_Q1), held + 32);
      }
      float gf[64], rf[64];
#pragma unroll
      for (int i = 0; i < 32; i++) { gf[2 * i] = bf_lo(held[32 + i]); gf[2 * i + 1] = bf_hi(held[32 + i]); rf[2 * i] = bf_lo(xs[i]); rf[2 * i + 1] = bf_hi(xs[i]); }
      if (!own) {
        mbar_spin(bars + B_KF + 8 * kv.s, kv.ph);
#pragma unroll
        for (int i = 0; i < 8; i++) {
          uint32_t t[4];
          ldmatrix_x4(sb + ps * KV_SLOT + lo + (i >> 2) * 16384 + (((2 * (i & 3) + (ln >> 4)) ^ (ln & 7)) << 4), t[0], t[1], t[2], t[3]);
#pragma unroll
          for (int y = 0; y < 4; y++) {
            rf[8 * i + 2 * y] = fmaf(bf_lo(t[y]), gf[8 * i + 2 * y], rf[8 * i + 2 * y]);
            rf[8 * i + 2 * y + 1] = fmaf(bf_hi(t[y]), gf[8 * i + 2 * y + 1], rf[8 * i + 2 * y + 1]);
          }
        }
        wg_any(c.warp >= 4, false);
        release_slot(c, bars + B_KE + 8 * kv.s);
        if (++ps == 5) ps = 0;
        ring_adv<5>(kv);
      }
      fence_regs(gf); fence_regs(rf);
      fin_steps(kp, 2 * NH);
      wgmma_wait<0>();
      fence_regs(facc);
#pragma unroll
      for (int i = 0; i < 32; i++) xs[i] = pack_bf16(fmaf(facc[2 * i], gf[2 * i], rf[2 * i]), fmaf(facc[2 * i + 1], gf[2 * i + 1], rf[2 * i + 1]));
      __syncwarp();
      stage_chunks<2>(xa + c.warp * 2048, 16384, xs);
      fence_async_smem();
      __syncwarp();
      if (elect_one()) {
        const int col = (fin & 3) * 256 + (own ? 128 : 0), row = (((fin >> 5) & 31) * 2 + rank) * 128 + c.warp * 16;
        tma_store_2d(&p.tm[TS_OUT], xa + c.warp * 2048, col, row);
        tma_store_2d(&p.tm[TS_OUT], xa + c.warp * 2048 + 16384, col + 64, row);
        bulk_commit();
        mbar_arrive(bars + B_STG);
        bulk_wait_read<0>();
      }
    }
    __syncwarp();
    cluster_sync_relaxed();
  }
}

typedef CUresult (*PFN_encodeTiled)(CUtensorMap*, CUtensorMapDataType, cuuint32_t, void*, const cuuint64_t*, const cuuint64_t*, const cuuint32_t*, const cuuint32_t*,
                                    CUtensorMapInterleave, CUtensorMapSwizzle, CUtensorMapL2promotion, CUtensorMapFloatOOBfill);
static PFN_encodeTiled s_encode = nullptr;
static void tm_2d(CUtensorMap* tm, const void* ptr, uint64_t rows, uint64_t cols, uint32_t box_rows) {
  cuuint64_t dims[2] = {cols, rows}; cuuint64_t strides[1] = {cols * 2}; cuuint32_t box[2] = {64, box_rows}; cuuint32_t es[2] = {1, 1};
  CUresult r = s_encode(tm, CU_TENSOR_MAP_DATA_TYPE_BFLOAT16, 2, (void*)ptr, dims, strides, box, es, CU_TENSOR_MAP_INTERLEAVE_NONE,
                        CU_TENSOR_MAP_SWIZZLE_128B, CU_TENSOR_MAP_L2_PROMOTION_L2_128B, CU_TENSOR_MAP_FLOAT_OOB_FILL_NONE);
  if (r != CUDA_SUCCESS) fprintf(stderr, "tensor map encode failed (%d)\n", (int)r);
}
static void tm_3d(CUtensorMap* tm, const void* ptr, uint64_t rows, uint64_t cols) {
  cuuint64_t dims[3] = {64, rows, cols / 64}; cuuint64_t strides[2] = {cols * 2, 128}; cuuint32_t box[3] = {64, 64, 2}; cuuint32_t es[3] = {1, 1, 1};
  CUresult r = s_encode(tm, CU_TENSOR_MAP_DATA_TYPE_BFLOAT16, 3, (void*)ptr, dims, strides, box, es, CU_TENSOR_MAP_INTERLEAVE_NONE,
                        CU_TENSOR_MAP_SWIZZLE_128B, CU_TENSOR_MAP_L2_PROMOTION_L2_128B, CU_TENSOR_MAP_FLOAT_OOB_FILL_NONE);
  if (r != CUDA_SUCCESS) fprintf(stderr, "tensor map encode failed (%d)\n", (int)r);
}
static inline uint16_t mk(int type, int a, int b) { return (uint16_t)(type << 12 | a << 5 | b); }

static void build_schedule(Params& P) {
  int cnt[NCLUSTER];
  for (int c = 0; c < NCLUSTER; c++) { cnt[c] = 0; for (int i = 0; i < MAXI; i++) P.items[c][i] = mk(T_END, 0, 0); }
  auto phys = [](int c) { return c == 64 ? 9 : c == 65 ? 17 : c == 9 ? 64 : c == 17 ? 65 : c; };
  auto push = [&](int c, uint16_t v) { P.items[phys(c)][cnt[c]++] = v; };
  int natt[NCLUSTER], nq[NCLUSTER];
  for (int c = 0; c < NCLUSTER; c++) { natt[c] = c < 32 ? 3 : (c < 56 ? 5 : (c < 62 ? 4 : (c < 64 ? 3 : 5))); nq[c] = c < 56 ? 1 : (c < 62 ? 7 : (c < 64 ? 9 : 6)); }
  for (int c = 0; c < 56; c++) push(c, mk(T_Z2, c % 8, c / 8));
  int qi = 0;
  for (int slot = 0; slot < 9; slot++)
    for (int c = NCLUSTER - 1; c >= 0; c--) {
      const int first = c < 56 ? 1 : 0;
      if (slot >= first && slot < first + nq[c]) { push(c, mk(T_Q, qi % 8, qi / 8)); qi++; }
    }
  for (int c = 0; c < 56; c++) push(c, mk(T_U, c % 8, c / 8));
  int ai = 0, grp[256], own[256];
  for (int slot = 0; slot < 5; slot++)
    for (int c = 0; c < NCLUSTER; c++) {
      const int first = c < 32 ? 0 : 5 - natt[c];
      if (slot >= first && slot < first + natt[c]) { grp[ai] = slot * 2 + (c >= 64); own[ai++] = c; }
    }
  for (int i = 0; i < 256; i++) {
    int s = 0;
    for (int j = i & ~7; j < (i & ~7) + 8; j++) s += grp[j] == grp[i];
    const int share = s >= 8 ? 0 : s >= 4 ? 1 : s >= 2 ? 2 : 3;
    push(own[i], mk(T_ATT, i / 8, share << 3 | i % 8) | (natt[own[i]] - 3) << 10);
  }
  for (int c = 0; c < 32; c++) push(c, mk(T_SA, c % 8, c / 8));
  for (int c = 0; c < 64; c++) push(c, mk(T_FIN, c % 8, (c / 8) % 4 | (c < 32 ? 4 : 0)));
  if (qi != 128 || ai != 256) fprintf(stderr, "bad schedule %d %d\n", qi, ai);
}

static Params s_params;
extern "C" void kernel_launch(void* const* d_in, const int* in_sizes, int n_in, void* d_out, int out_size) {
  (void)in_sizes; (void)n_in; (void)out_size;
  if (!s_encode) {
    void* fn = nullptr; cudaDriverEntryPointQueryResult qr;
    cudaGetDriverEntryPoint("cuTensorMapEncodeTiled", &fn, cudaEnableDefault, &qr);
    s_encode = (PFN_encodeTiled)fn;
    cudaFuncSetAttribute(fused_kernel, cudaFuncAttributeMaxDynamicSharedMemorySize, SMEM_BYTES);
    build_schedule(s_params);
  }
  Params& P = s_params;
  void *xn, *q, *o, *z2, *u, *gg, *sa;
  cudaGetSymbolAddress(&gg, g_g); cudaGetSymbolAddress(&sa, g_sa);
  cudaGetSymbolAddress(&xn, g_xn); cudaGetSymbolAddress(&q, g_q); cudaGetSymbolAddress(&o, g_o);
  cudaGetSymbolAddress(&z2, g_z2); cudaGetSymbolAddress(&u, g_u);
  tm_2d(&P.tm[TM_XN], xn, SEQ, DM, 128); tm_2d(&P.tm[TM_WSP], d_in[7], SEQ, SEQ, 128); tm_2d(&P.tm[TM_U], u, SEQ, FH, 128);
  tm_2d(&P.tm[TM_O], o, SEQ, HD, 128); tm_2d(&P.tm[TM_Q], q, SEQ, HD, 128); tm_2d(&P.tm[TM_X], d_in[0], SEQ, DM, 128);
  tm_2d(&P.tm[TM_K], d_in[1], NH * SEQ, 128, 128); tm_2d(&P.tm[TM_V], d_in[2], NH * SEQ, 128, 128);
  tm_2d(&P.tm[TM_SA], sa, SEQ, DM, 128); tm_2d(&P.tm[TM_G], gg, SEQ, DM, 128); tm_2d(&P.tm[TM_WO64], d_in[4], HD, DM, 64);
  tm_3d(&P.tm[TM_WIN], d_in[6], DM, FF); tm_3d(&P.tm[TM_WQ], d_in[3], DM, HD); tm_3d(&P.tm[TM_Z2], z2, SEQ, FH);
  tm_3d(&P.tm[TM_WOUT], d_in[9], FH, DM); tm_3d(&P.tm[TM_WO], d_in[4], HD, DM);
  tm_2d(&P.tm[TS_Q], q, SEQ, HD, ST_ROWS); tm_2d(&P.tm[TS_O], o, SEQ, HD, ST_ROWS); tm_2d(&P.tm[TS_Z2], z2, SEQ, FH, ST_ROWS); tm_2d(&P.tm[TS_U], u, SEQ, FH, ST_ROWS);
  tm_2d(&P.tm[TS_SA], sa, SEQ, DM, ST_ROWS); tm_2d(&P.tm[TS_G], gg, SEQ, DM, ST_ROWS); tm_2d(&P.tm[TS_OUT], d_out, SEQ, DM, 16);
  P.x = (const bf16*)d_in[0]; P.b_sp = (const bf16*)d_in[8];
  fused_kernel<<<2 * NCLUSTER, 384, SMEM_BYTES, cudaStreamPerThread>>>(P);
}
```

```cpp
#include <cuda_runtime.h>
#include <cuda_bf16.h>
#include <cuda.h>
#include <stdint.h>
#include <stdio.h>

typedef __nv_bfloat16 bf16;

constexpr int SEQ = 2048, DM = 1024, NH = 32, HD = 4096, FF = 3584, FH = 1792;

__device__ __align__(1024) bf16 g_xn[SEQ * DM];
__device__ __align__(1024) bf16 g_q[SEQ * HD];
__device__ __align__(1024) bf16 g_o[SEQ * HD];
__device__ __align__(1024) bf16 g_z2[SEQ * FH];
__device__ __align__(1024) bf16 g_u[SEQ * FH];
__device__ __align__(1024) uint2 g_stats[SEQ * 8];
__device__ __align__(1024) bf16 g_g[SEQ * DM];
__device__ __align__(1024) bf16 g_sa[SEQ * DM];
constexpr int F_XN = 0;
constexpr int F_Z2 = 512;
constexpr int F_Q = 768;
constexpr int F_U = 1024;
constexpr int F_O = 1536;
constexpr int F_S = 2048;
constexpr int F_TOTAL = 2112;
__device__ __align__(1024) unsigned g_flags[F_TOTAL];
__device__ unsigned g_done;
__device__ unsigned g_epoch;

__device__ __forceinline__ uint32_t smem_u32(const void* p) { return (uint32_t)__cvta_generic_to_shared(p); }
__device__ __forceinline__ void mbar_init(uint32_t bar, uint32_t cnt) { asm volatile("mbarrier.init.shared::cta.b64 [%0], %1;" :: "r"(bar), "r"(cnt)); }
__device__ __forceinline__ void mbar_expect_tx(uint32_t bar, uint32_t bytes) { asm volatile("mbarrier.arrive.expect_tx.shared::cta.b64 _, [%0], %1;" :: "r"(bar), "r"(bytes) : "memory"); }
__device__ __forceinline__ void mbar_arrive(uint32_t bar) { asm volatile("mbarrier.arrive.shared::cta.b64 _, [%0];" :: "r"(bar) : "memory"); }
__device__ __forceinline__ void mbar_arrive_cta(uint32_t bar, uint32_t cta) {
  asm volatile("{\n.reg .b32 ra;\nmapa.shared::cluster.u32 ra, %0, %1;\nmbarrier.arrive.shared::cluster.b64 _, [ra];\n}" :: "r"(bar), "r"(cta) : "memory");
}
__device__ __forceinline__ bool mbar_test(uint32_t bar, uint32_t parity) {
  uint32_t ok;
  asm volatile("{\n.reg .pred P1;\nmbarrier.test_wait.parity.shared::cta.b64 P1, [%1], %2;\nselp.u32 %0, 1, 0, P1;\n}" : "=r"(ok) : "r"(bar), "r"(parity) : "memory");
  return ok;
}
__device__ __forceinline__ bool mbar_test_a(uint32_t bar, uint32_t parity) {
  uint32_t ok;
  asm volatile("{\n.reg .pred P2;\nmbarrier.test_wait.parity.shared::cta.b64 P2, [%1], %2;\nselp.u32 %0, 1, 0, P2;\n}" : "=r"(ok) : "r"(bar), "r"(parity) : "memory");
  return ok;
}
constexpr uint32_t SPIN_LIMIT = 1u << 22;
__device__ __forceinline__ void trap_if(bool c) { asm volatile("{\n.reg .pred P;\nsetp.ne.u32 P, %0, 0;\n@P trap;\n}" :: "r"((uint32_t)c)); }
__device__ __forceinline__ void mbar_wait(uint32_t bar, uint32_t parity) {
  asm volatile("{\n.reg .pred P1;\n.reg .u32 n;\nmbarrier.try_wait.parity.shared::cta.b64 P1, [%0], %1;\n@P1 bra DONE;\nmov.u32 n, 0;\n"
               "LOOP:\nmbarrier.try_wait.parity.shared::cta.b64 P1, [%0], %1;\n@P1 bra DONE;\nadd.u32 n, n, 1;\nsetp.gt.u32 P1, n, %2;\n@P1 trap;\nbra LOOP;\nDONE:\n}"
               :: "r"(bar), "r"(parity), "n"(SPIN_LIMIT) : "memory");
}
__device__ __forceinline__ void mbar_spin(uint32_t bar, uint32_t parity) {
  asm volatile("{\n.reg .pred P1;\nLOOP:\nmbarrier.try_wait.parity.shared::cta.b64 P1, [%0], %1;\n@!P1 bra LOOP;\n}" :: "r"(bar), "r"(parity) : "memory");
}
__device__ __forceinline__ void mbar_wait_sleep(uint32_t bar, uint32_t parity, uint32_t ns) {
  uint32_t n = 0;
  while (!mbar_test(bar, parity)) { trap_if(++n > SPIN_LIMIT * 4); __nanosleep(ns); }
}
__device__ __forceinline__ void tma_load_2d(uint32_t dst, const CUtensorMap* tm, int c0, int c1, uint32_t bar) {
  asm volatile("cp.async.bulk.tensor.2d.shared::cluster.global.mbarrier::complete_tx::bytes [%0], [%1, {%3, %4}], [%2];"
    :: "r"(dst), "l"(tm), "r"(bar), "r"(c0), "r"(c1) : "memory");
}
__device__ __forceinline__ void tma_load_2d_mc(uint32_t dst, const CUtensorMap* tm, int c0, int c1, uint32_t bar) {
  asm volatile("cp.async.bulk.tensor.2d.shared::cluster.global.mbarrier::complete_tx::bytes.multicast::cluster [%0], [%1, {%3, %4}], [%2], %5;"
    :: "r"(dst), "l"(tm), "r"(bar), "r"(c0), "r"(c1), "h"((uint16_t)3) : "memory");
}
__device__ __forceinline__ void tma_prefetch_2d(const CUtensorMap* tm, int c0, int c1) {
  asm volatile("cp.async.bulk.prefetch.tensor.2d.L2.global [%0, {%1, %2}];" :: "l"(tm), "r"(c0), "r"(c1) : "memory");
}
__device__ __forceinline__ void tma_prefetch_3d(const CUtensorMap* tm, int c1, int c2) {
  asm volatile("cp.async.bulk.prefetch.tensor.3d.L2.global [%0, {%1, %2, %3}];" :: "l"(tm), "r"(0), "r"(c1), "r"(c2) : "memory");
}
__device__ __forceinline__ void tma_load_3d_mc(uint32_t dst, const CUtensorMap* tm, int c1, int c2, uint32_t bar) {
  asm volatile("cp.async.bulk.tensor.3d.shared::cluster.global.mbarrier::complete_tx::bytes.multicast::cluster [%0], [%1, {%3, %4, %5}], [%2], %6;"
    :: "r"(dst), "l"(tm), "r"(bar), "r"(0), "r"(c1), "r"(c2), "h"((uint16_t)3) : "memory");
}
__device__ __forceinline__ void tma_store_2d(const CUtensorMap* tm, uint32_t src, int c0, int c1) {
  asm volatile("cp.async.bulk.tensor.2d.global.shared::cta.bulk_group [%0, {%2, %3}], [%1];" :: "l"(tm), "r"(src), "r"(c0), "r"(c1) : "memory");
}
__device__ __forceinline__ void bulk_commit() { asm volatile("cp.async.bulk.commit_group;" ::: "memory"); }
template <int N> __device__ __forceinline__ void bulk_wait_read() { asm volatile("cp.async.bulk.wait_group.read %0;" :: "n"(N) : "memory"); }
template <int N> __device__ __forceinline__ void bulk_wait() { asm volatile("cp.async.bulk.wait_group %0;" :: "n"(N) : "memory"); }
__device__ __forceinline__ void fence_async_smem() { asm volatile("fence.proxy.async.shared::cta;" ::: "memory"); }
__device__ __forceinline__ void fence_async_global() { asm volatile("fence.proxy.async.global;" ::: "memory"); }
__device__ __forceinline__ void wgmma_fence() { asm volatile("wgmma.fence.sync.aligned;" ::: "memory"); }
__device__ __forceinline__ void wgmma_commit() { asm volatile("wgmma.commit_group.sync.aligned;" ::: "memory"); }
template <int N> __device__ __forceinline__ void wgmma_wait() { asm volatile("wgmma.wait_group.sync.aligned %0;" :: "n"(N) : "memory"); }
__device__ __forceinline__ uint64_t make_desc(uint32_t addr, uint32_t lbo, uint32_t sbo) {
  return (uint64_t)((addr & 0x3FFFF) >> 4) | ((uint64_t)(lbo >> 4) << 16) | ((uint64_t)(sbo >> 4) << 32) | (1ull << 62);
}
template <int N> __device__ __forceinline__ void fence_regs(float (&d)[N]) {
#pragma unroll
  for (int i = 0; i < N; i++) asm volatile("" : "+f"(d[i]) :: "memory");
}
template <int N> __device__ __forceinline__ void fence_regs(uint32_t (&d)[N]) {
#pragma unroll
  for (int i = 0; i < N; i++) asm volatile("" : "+r"(d[i]) :: "memory");
}
__device__ __forceinline__ void named_sync(int id) { asm volatile("bar.sync %0, 256;" :: "r"(id) : "memory"); }
__device__ __forceinline__ void pp_sync(bool w) { asm volatile("{\n.reg .pred p;\nsetp.ne.u32 p, %0, 0;\n@p bar.sync 2, 256;\n@!p bar.sync 1, 256;\n}" :: "r"((uint32_t)w) : "memory"); }
__device__ __forceinline__ void pp_arrive(bool w) { asm volatile("{\n.reg .pred p;\nsetp.ne.u32 p, %0, 0;\n@p bar.arrive 1, 256;\n@!p bar.arrive 2, 256;\n}" :: "r"((uint32_t)w) : "memory"); }
__device__ __forceinline__ bool wg_any(bool w, bool v) {
  uint32_t r;
  asm volatile("{\n.reg .pred p, q;\nsetp.ne.u32 p, %1, 0;\nbar.red.or.pred q, %2, 128, p;\nselp.u32 %0, 1, 0, q;\n}" : "=r"(r) : "r"((uint32_t)v), "r"(w ? 4 : 3) : "memory");
  return __any_sync(0xffffffffu, r);
}
__device__ __forceinline__ int fresh_warp() { uint32_t t; asm volatile("mov.u32 %0, %%tid.x;" : "=r"(t)); return __shfl_sync(0xffffffffu, (int)(t >> 5) - 4, 0); }
__device__ __forceinline__ void cluster_sync_relaxed() { asm volatile("barrier.cluster.arrive.relaxed.aligned;\nbarrier.cluster.wait.aligned;" ::: "memory"); }
__device__ __forceinline__ unsigned ld_acquire(const unsigned* p) { unsigned v; asm volatile("ld.acquire.gpu.global.u32 %0, [%1];" : "=r"(v) : "l"(p) : "memory"); return v; }
__device__ __forceinline__ void red_release(unsigned* p, unsigned v) { asm volatile("red.release.gpu.global.add.u32 [%0], %1;" :: "l"(p), "r"(v) : "memory"); }
__device__ __forceinline__ void flag_wait(const unsigned* p, unsigned target) {
  uint32_t n = 0;
  while (ld_acquire(p) < target) { trap_if(++n > SPIN_LIMIT); __nanosleep(20); }
}
__device__ __forceinline__ void st_tagged(uint2* p, float a, float b, uint32_t tag) {
  asm volatile("{\n.reg .b64 x;\nmov.b64 x, {%1, %2};\nst.relaxed.gpu.global.b64 [%0], x;\n}" :: "l"(p),
               "r"((__float_as_uint(a) & ~63u) | (tag & 63u)), "r"((__float_as_uint(b) & ~63u) | (tag >> 6)) : "memory");
}
__device__ __forceinline__ uint4 ld_tagged2(const uint2* p) {
  uint4 v;
  asm volatile("{\n.reg .b64 x, y;\nld.relaxed.gpu.global.v2.b64 {x, y}, [%4];\nmov.b64 {%0, %1}, x;\nmov.b64 {%2, %3}, y;\n}" : "=r"(v.x), "=r"(v.y), "=r"(v.z), "=r"(v.w) : "l"(p) : "memory");
  return v;
}
__device__ __forceinline__ bool tag_ok(uint32_t a, uint32_t b, uint32_t tag) { return ((a & 63u) | ((b & 63u) << 6)) == tag; }
__device__ __forceinline__ float untag(uint32_t v) { return __uint_as_float(v & ~63u); }
__device__ __forceinline__ uint32_t pack_bf16(float lo, float hi) { uint32_t r; asm("cvt.rn.bf16x2.f32 %0, %1, %2;" : "=r"(r) : "f"(hi), "f"(lo)); return r; }
__device__ __forceinline__ uint32_t bf2_fma(uint32_t a, uint32_t b, uint32_t c) { uint32_t r; asm("fma.rn.bf16x2 %0, %1, %2, %3;" : "=r"(r) : "r"(a), "r"(b), "r"(c)); return r; }
__device__ __forceinline__ uint32_t bf2_mul(uint32_t a, uint32_t b) { uint32_t r; asm("mul.rn.bf16x2 %0, %1, %2;" : "=r"(r) : "r"(a), "r"(b)); return r; }
__device__ __forceinline__ uint32_t bf2_add(uint32_t a, uint32_t b) { uint32_t r; asm("add.rn.bf16x2 %0, %1, %2;" : "=r"(r) : "r"(a), "r"(b)); return r; }
constexpr uint32_t BF2_HALF = 0x3f003f00u;
__device__ __forceinline__ float bf_lo(uint32_t v) { return __uint_as_float(v << 16); }
__device__ __forceinline__ float bf_hi(uint32_t v) { return __uint_as_float(v & 0xffff0000u); }
__device__ __forceinline__ float ex2(float x) { float y; asm("ex2.approx.ftz.f32 %0, %1;" : "=f"(y) : "f"(x)); return y; }
__device__ __forceinline__ float tanh_fast(float x) { float y; asm("tanh.approx.f32 %0, %1;" : "=f"(y) : "f"(x)); return y; }
__device__ __forceinline__ void stmatrix_x4(uint32_t addr, uint32_t a, uint32_t b, uint32_t c, uint32_t d) {
  asm volatile("stmatrix.sync.aligned.m8n8.x4.shared.b16 [%0], {%1, %2, %3, %4};" :: "r"(addr), "r"(a), "r"(b), "r"(c), "r"(d) : "memory");
}
__device__ __forceinline__ void ldmatrix_x4(uint32_t addr, uint32_t& a, uint32_t& b, uint32_t& c, uint32_t& d) {
  asm volatile("ldmatrix.sync.aligned.m8n8.x4.shared.b16 {%0, %1, %2, %3}, [%4];" : "=r"(a), "=r"(b), "=r"(c), "=r"(d) : "r"(addr) : "memory");
}
__device__ __forceinline__ uint32_t lane_id() { uint32_t l; asm volatile("mov.u32 %0, %%laneid;" : "=r"(l)); return l; }
__device__ __forceinline__ bool elect_one() {
  uint32_t r;
  asm volatile("{\n.reg .pred P;\nelect.sync _|P, 0xffffffff;\nselp.u32 %0, 1, 0, P;\n}" : "=r"(r));
  return r;
}

__device__ __forceinline__ void wgmma_m64n128k16_ss_tb0(float (&d)[64], uint64_t da, uint64_t db, int scale_d) {
  asm volatile("{\n.reg .pred p;\nsetp.ne.b32 p, %66, 0;\n"
    "wgmma.mma_async.sync.aligned.m64n128k16.f32.bf16.bf16 "
    "{%0, %1, %2, %3, %4, %5, %6, %7, %8, %9, %10, %11, %12, %13, %14, %15, %16, %17, %18, %19, %20, %21, %22, %23, %24, %25, %26, %27, %28, %29, %30, %31, %32, %33, %34, %35, %36, %37, %38, %39, %40, %41, %42, %43, %44, %45, %46, %47, %48, %49, %50, %51, %52, %53, %54, %55, %56, %57, %58, %59, %60, %61, %62, %63}, "
    "%64, %65, p, 1, 1, 0, 0;\n}\n"
    : "+f"(d[0]), "+f"(d[1]), "+f"(d[2]), "+f"(d[3]), "+f"(d[4]), "+f"(d[5]), "+f"(d[6]), "+f"(d[7]), "+f"(d[8]), "+f"(d[9]), "+f"(d[10]), "+f"(d[11]), "+f"(d[12]), "+f"(d[13]), "+f"(d[14]), "+f"(d[15]), "+f"(d[16]), "+f"(d[17]), "+f"(d[18]), "+f"(d[19]), "+f"(d[20]), "+f"(d[21]), "+f"(d[22]), "+f"(d[23]), "+f"(d[24]), "+f"(d[25]), "+f"(d[26]), "+f"(d[27]), "+f"(d[28]), "+f"(d[29]), "+f"(d[30]), "+f"(d[31]), "+f"(d[32]), "+f"(d[33]), "+f"(d[34]), "+f"(d[35]), "+f"(d[36]), "+f"(d[37]), "+f"(d[38]), "+f"(d[39]), "+f"(d[40]), "+f"(d[41]), "+f"(d[42]), "+f"(d[43]), "+f"(d[44]), "+f"(d[45]), "+f"(d[46]), "+f"(d[47]), "+f"(d[48]), "+f"(d[49]), "+f"(d[50]), "+f"(d[51]), "+f"(d[52]), "+f"(d[53]), "+f"(d[54]), "+f"(d[55]), "+f"(d[56]), "+f"(d[57]), "+f"(d[58]), "+f"(d[59]), "+f"(d[60]), "+f"(d[61]), "+f"(d[62]), "+f"(d[63])
    : "l"(da), "l"(db), "r"(scale_d));
}
__device__ __forceinline__ void wgmma_m64n256k16_ss_tb1(float (&d)[128], uint64_t da, uint64_t db, int scale_d) {
  asm volatile("{\n.reg .pred p;\nsetp.ne.b32 p, %130, 0;\n"
    "wgmma.mma_async.sync.aligned.m64n256k16.f32.bf16.bf16 "
    "{%0, %1, %2, %3, %4, %5, %6, %7, %8, %9, %10, %11, %12, %13, %14, %15, %16, %17, %18, %19, %20, %21, %22, %23, %24, %25, %26, %27, %28, %29, %30, %31, %32, %33, %34, %35, %36, %37, %38, %39, %40, %41, %42, %43, %44, %45, %46, %47, %48, %49, %50, %51, %52, %53, %54, %55, %56, %57, %58, %59, %60, %61, %62, %63, %64, %65, %66, %67, %68, %69, %70, %71, %72, %73, %74, %75, %76, %77, %78, %79, %80, %81, %82, %83, %84, %85, %86, %87, %88, %89, %90, %91, %92, %93, %94, %95, %96, %97, %98, %99, %100, %101, %102, %103, %104, %105, %106, %107, %108, %109, %110, %111, %112, %113, %114, %115, %116, %117, %118, %119, %120, %121, %122, %123, %124, %125, %126, %127}, "
    "%128, %129, p, 1, 1, 0, 1;\n}\n"
    : "+f"(d[0]), "+f"(d[1]), "+f"(d[2]), "+f"(d[3]), "+f"(d[4]), "+f"(d[5]), "+f"(d[6]), "+f"(d[7]), "+f"(d[8]), "+f"(d[9]), "+f"(d[10]), "+f"(d[11]), "+f"(d[12]), "+f"(d[13]), "+f"(d[14]), "+f"(d[15]), "+f"(d[16]), "+f"(d[17]), "+f"(d[18]), "+f"(d[19]), "+f"(d[20]), "+f"(d[21]), "+f"(d[22]), "+f"(d[23]), "+f"(d[24]), "+f"(d[25]), "+f"(d[26]), "+f"(d[27]), "+f"(d[28]), "+f"(d[29]), "+f"(d[30]), "+f"(d[31]), "+f"(d[32]), "+f"(d[33]), "+f"(d[34]), "+f"(d[35]), "+f"(d[36]), "+f"(d[37]), "+f"(d[38]), "+f"(d[39]), "+f"(d[40]), "+f"(d[41]), "+f"(d[42]), "+f"(d[43]), "+f"(d[44]), "+f"(d[45]), "+f"(d[46]), "+f"(d[47]), "+f"(d[48]), "+f"(d[49]), "+f"(d[50]), "+f"(d[51]), "+f"(d[52]), "+f"(d[53]), "+f"(d[54]), "+f"(d[55]), "+f"(d[56]), "+f"(d[57]), "+f"(d[58]), "+f"(d[59]), "+f"(d[60]), "+f"(d[61]), "+f"(d[62]), "+f"(d[63]), "+f"(d[64]), "+f"(d[65]), "+f"(d[66]), "+f"(d[67]), "+f"(d[68]), "+f"(d[69]), "+f"(d[70]), "+f"(d[71]), "+f"(d[72]), "+f"(d[73]), "+f"(d[74]), "+f"(d[75]), "+f"(d[76]), "+f"(d[77]), "+f"(d[78]), "+f"(d[79]), "+f"(d[80]), "+f"(d[81]), "+f"(d[82]), "+f"(d[83]), "+f"(d[84]), "+f"(d[85]), "+f"(d[86]), "+f"(d[87]), "+f"(d[88]), "+f"(d[89]), "+f"(d[90]), "+f"(d[91]), "+f"(d[92]), "+f"(d[93]), "+f"(d[94]), "+f"(d[95]), "+f"(d[96]), "+f"(d[97]), "+f"(d[98]), "+f"(d[99]), "+f"(d[100]), "+f"(d[101]), "+f"(d[102]), "+f"(d[103]), "+f"(d[104]), "+f"(d[105]), "+f"(d[106]), "+f"(d[107]), "+f"(d[108]), "+f"(d[109]), "+f"(d[110]), "+f"(d[111]), "+f"(d[112]), "+f"(d[113]), "+f"(d[114]), "+f"(d[115]), "+f"(d[116]), "+f"(d[117]), "+f"(d[118]), "+f"(d[119]), "+f"(d[120]), "+f"(d[121]), "+f"(d[122]), "+f"(d[123]), "+f"(d[124]), "+f"(d[125]), "+f"(d[126]), "+f"(d[127])
    : "l"(da), "l"(db), "r"(scale_d));
}
__device__ __forceinline__ void wgmma_m64n128k16_rs_tb1(float (&d)[64], uint32_t a0, uint32_t a1, uint32_t a2, uint32_t a3, uint64_t db, int scale_d) {
  asm volatile("{\n.reg .pred p;\nsetp.ne.b32 p, %69, 0;\n"
    "wgmma.mma_async.sync.aligned.m64n128k16.f32.bf16.bf16 "
    "{%0, %1, %2, %3, %4, %5, %6, %7, %8, %9, %10, %11, %12, %13, %14, %15, %16, %17, %18, %19, %20, %21, %22, %23, %24, %25, %26, %27, %28, %29, %30, %31, %32, %33, %34, %35, %36, %37, %38, %39, %40, %41, %42, %43, %44, %45, %46, %47, %48, %49, %50, %51, %52, %53, %54, %55, %56, %57, %58, %59, %60, %61, %62, %63}, "
    "{%64, %65, %66, %67}, %68, p, 1, 1, 1;\n}\n"
    : "+f"(d[0]), "+f"(d[1]), "+f"(d[2]), "+f"(d[3]), "+f"(d[4]), "+f"(d[5]), "+f"(d[6]), "+f"(d[7]), "+f"(d[8]), "+f"(d[9]), "+f"(d[10]), "+f"(d[11]), "+f"(d[12]), "+f"(d[13]), "+f"(d[14]), "+f"(d[15]), "+f"(d[16]), "+f"(d[17]), "+f"(d[18]), "+f"(d[19]), "+f"(d[20]), "+f"(d[21]), "+f"(d[22]), "+f"(d[23]), "+f"(d[24]), "+f"(d[25]), "+f"(d[26]), "+f"(d[27]), "+f"(d[28]), "+f"(d[29]), "+f"(d[30]), "+f"(d[31]), "+f"(d[32]), "+f"(d[33]), "+f"(d[34]), "+f"(d[35]), "+f"(d[36]), "+f"(d[37]), "+f"(d[38]), "+f"(d[39]), "+f"(d[40]), "+f"(d[41]), "+f"(d[42]), "+f"(d[43]), "+f"(d[44]), "+f"(d[45]), "+f"(d[46]), "+f"(d[47]), "+f"(d[48]), "+f"(d[49]), "+f"(d[50]), "+f"(d[51]), "+f"(d[52]), "+f"(d[53]), "+f"(d[54]), "+f"(d[55]), "+f"(d[56]), "+f"(d[57]), "+f"(d[58]), "+f"(d[59]), "+f"(d[60]), "+f"(d[61]), "+f"(d[62]), "+f"(d[63])
    : "r"(a0), "r"(a1), "r"(a2), "r"(a3), "l"(db), "r"(scale_d));
}
__device__ __forceinline__ void wgmma_m64n128k16_ss_tb1(float (&d)[64], uint64_t da, uint64_t db, int scale_d) {
  asm volatile("{\n.reg .pred p;\nsetp.ne.b32 p, %66, 0;\n"
    "wgmma.mma_async.sync.aligned.m64n128k16.f32.bf16.bf16 "
    "{%0, %1, %2, %3, %4, %5, %6, %7, %8, %9, %10, %11, %12, %13, %14, %15, %16, %17, %18, %19, %20, %21, %22, %23, %24, %25, %26, %27, %28, %29, %30, %31, %32, %33, %34, %35, %36, %37, %38, %39, %40, %41, %42, %43, %44, %45, %46, %47, %48, %49, %50, %51, %52, %53, %54, %55, %56, %57, %58, %59, %60, %61, %62, %63}, "
    "%64, %65, p, 1, 1, 0, 1;\n}\n"
    : "+f"(d[0]), "+f"(d[1]), "+f"(d[2]), "+f"(d[3]), "+f"(d[4]), "+f"(d[5]), "+f"(d[6]), "+f"(d[7]), "+f"(d[8]), "+f"(d[9]), "+f"(d[10]), "+f"(d[11]), "+f"(d[12]), "+f"(d[13]), "+f"(d[14]), "+f"(d[15]), "+f"(d[16]), "+f"(d[17]), "+f"(d[18]), "+f"(d[19]), "+f"(d[20]), "+f"(d[21]), "+f"(d[22]), "+f"(d[23]), "+f"(d[24]), "+f"(d[25]), "+f"(d[26]), "+f"(d[27]), "+f"(d[28]), "+f"(d[29]), "+f"(d[30]), "+f"(d[31]), "+f"(d[32]), "+f"(d[33]), "+f"(d[34]), "+f"(d[35]), "+f"(d[36]), "+f"(d[37]), "+f"(d[38]), "+f"(d[39]), "+f"(d[40]), "+f"(d[41]), "+f"(d[42]), "+f"(d[43]), "+f"(d[44]), "+f"(d[45]), "+f"(d[46]), "+f"(d[47]), "+f"(d[48]), "+f"(d[49]), "+f"(d[50]), "+f"(d[51]), "+f"(d[52]), "+f"(d[53]), "+f"(d[54]), "+f"(d[55]), "+f"(d[56]), "+f"(d[57]), "+f"(d[58]), "+f"(d[59]), "+f"(d[60]), "+f"(d[61]), "+f"(d[62]), "+f"(d[63])
    : "l"(da), "l"(db), "r"(scale_d));
}


enum { TM_XN, TM_WSP, TM_U, TM_O, TM_Q, TM_X, TM_SA, TM_G, TM_K, TM_V, TM_WO64,
       TM_WIN, TM_WQ, TM_Z2, TM_WOUT, TM_WO, TS_Q, TS_O, TS_Z2, TS_U, TS_SA, TS_G, TS_OUT, TM_COUNT };
enum { T_Z2 = 0, T_Q = 1, T_U = 2, T_ATT = 3, T_SA = 4, T_FIN = 5, T_END = 7 };
constexpr int NCLUSTER = 66, MAXI = 14;
struct alignas(64) Params {
  const bf16* x;
  const bf16* b_sp;
  CUtensorMap tm[TM_COUNT];
  uint16_t items[NCLUSTER][MAXI];
};

constexpr uint32_t G_STAGE = 49152, G_A = 16384, KV_SLOT = 32768;
constexpr uint32_t OFF_Q1 = 163840, OFF_Q0 = 196608, OFF_BAR = 229376, OFF_LN = OFF_BAR + 256, SMEM_BYTES = OFF_LN + 1024;
constexpr uint32_t B_GF = 0, B_GE = 32, B_KF = 64, B_KE = 104, B_QF = 144, B_QE = 160, B_XF = 176, B_XR = 184, B_STG = 192, B_FREE = 200;
constexpr uint32_t B_GO = 208, B_LN = 216, B_PUB = 248, B_TAG = 224, B_RDY = 228, B_PROG = 232;
constexpr int SA_HEADS = 18;
constexpr int SW_NS = 40;
constexpr int SW_ATT = 800;
constexpr int ST_ROWS = 16;
constexpr int ST_FLY = 2;
constexpr int KV_PF = 4;
constexpr int FIN_PREP = 8;
constexpr int OWN_OFF = 8;
constexpr int ACT_REP = 33;
constexpr int Q_DELAY = 4;
constexpr int Q_GAP = 4;
constexpr int QW = 2;
constexpr int Z_DELAY = 4;
constexpr int Z_GAP = 3;
constexpr int LN_SLEEP = 300;
constexpr int U_PACE = 200;
constexpr int Q_AT = 19;
constexpr int OUT_PF = 8;
constexpr int SA_STEPS = 2 * SA_HEADS;
static_assert(ST_ROWS == 16, "the per-warp stores of the last o tile use the same tensor map");
static_assert(SA_STEPS >= 36, "activation, gate store and hold-back have to fit into the second SA segment");
constexpr uint32_t FIN_SLOT0 = (0x0320u >> (4 * ((29 + SA_STEPS) & 3))) & 15;
constexpr float SM_C = 0.08838834764831845f * 1.4426950408889634f;
constexpr float GELU_A = 0.7978845608028654f, GELU_B = 0.7978845608028654f * 0.044715f;
constexpr float SM_LO = 1e-7f, SM_HI = 1e12f;
constexpr float SM_THR = 1024.f;


extern __shared__ __align__(1024) uint8_t smem_raw[];
__device__ __forceinline__ uint32_t smem_base() { return smem_u32(smem_raw); }

struct Ring { uint32_t s, ph; };
template <int N> __device__ __forceinline__ void ring_adv(Ring& r) { if (++r.s == N) { r.s = 0; r.ph ^= 1; } }

__device__ __forceinline__ int get_item(const Params& p, int i) {
  uint32_t b; asm volatile("mov.u32 %0, %%ctaid.x;" : "=r"(b));
  return p.items[b >> 1][i];
}
struct Cons {
  uint32_t sb;
  int warp;
  Ring g;
  uint32_t rot;
  uint32_t fph;
};

__device__ __forceinline__ void stage_acquire(const Cons& c) { mbar_spin(c.sb + OFF_BAR + B_FREE, c.fph); }
__device__ __forceinline__ void stage_commit(Cons& c) {
  __syncwarp();
  if (lane_id() == 0) mbar_arrive(c.sb + OFF_BAR + B_STG);
  c.fph ^= 1;
}

__device__ __forceinline__ void release_slot(const Cons& c, uint32_t bar) {
  if (lane_id() == 0 && (c.warp & 3) < 2) mbar_arrive_cta(bar, c.warp & 1);
}
constexpr uint64_t DESC_HI = (uint64_t)0x40000040u << 32;

template <bool FIRST> __device__ __forceinline__ void gemm_step(float (&acc)[128], Cons& c) {
  mbar_spin(c.sb + OFF_BAR + B_GF + 8 * c.g.s, c.g.ph);
  const uint32_t st = ((c.sb & 0x3FFFF) >> 4) + ((c.g.s + c.rot) & 3) * (G_STAGE >> 4);
  const uint32_t da = st + (c.warp >> 2) * 512 + (1u << 16), db = st + (G_A >> 4) + ((8192u >> 4) << 16);
  wgmma_fence();
#pragma unroll
  for (int kk = 0; kk < 4; kk++) wgmma_m64n256k16_ss_tb1(acc, DESC_HI | (da + kk * 2), DESC_HI | (db + kk * 128), !(FIRST && kk == 0));
  wgmma_commit();
}

template <int N> __device__ __forceinline__ void stage_chunks(uint32_t buf, uint32_t stride, const uint32_t* pk) {
  const uint32_t ln = lane_id();
  const uint32_t a = buf + ((ln & 15) << 7);
  const uint32_t x = ln & 7, hi = ln >> 4;
#pragma unroll
  for (int i = 0; i < 4 * N; i++) stmatrix_x4(a + (i >> 2) * stride + (((2 * (i & 3) + hi) ^ x) << 4), pk[4 * i], pk[4 * i + 1], pk[4 * i + 2], pk[4 * i + 3]);
}

__device__ __forceinline__ float act2_fn(float x, float a, float b) {
  return fmaf(x, tanh_fast(x * fmaf(x * x, b, a)), x);
}
__device__ __forceinline__ float quad_sum(float v) { v += __shfl_xor_sync(0xffffffffu, v, 1); v += __shfl_xor_sync(0xffffffffu, v, 2); return v; }
__device__ __forceinline__ float quad_max(float v) { v = fmaxf(v, __shfl_xor_sync(0xffffffffu, v, 1)); v = fmaxf(v, __shfl_xor_sync(0xffffffffu, v, 2)); return v; }

__device__ __forceinline__ uint32_t load_tag(const Cons& c) { uint32_t t; asm volatile("ld.volatile.shared.u32 %0, [%1];" : "=r"(t) : "r"(c.sb + OFF_BAR + B_TAG)); return t; }

struct Shadow {
  int act;
  int store;
};
__device__ __forceinline__ void rotate16(uint32_t (&h)[64]) {
#pragma unroll
  for (int i = 0; i < 16; i++)
    asm volatile("{\n.reg .b32 t;\nmov.b32 t, %0;\nmov.b32 %0, %1;\nmov.b32 %1, %2;\nmov.b32 %2, %3;\nmov.b32 %3, t;\n}" : "+r"(h[i]), "+r"(h[i + 16]), "+r"(h[i + 32]), "+r"(h[i + 48]));
}

template <int O>
__device__ __forceinline__ void act_block(uint32_t (&held)[64], float ca, float cb, bool first, float& u0, float& u1, float& s0, float& s1, float& q0, float& q1) {
#pragma unroll
  for (int i = O; i < O + 4; i += 2) {
    const float a0 = act2_fn(bf_lo(held[i]), ca, cb), a1 = act2_fn(bf_hi(held[i]), ca, cb);
    const float b0 = act2_fn(bf_lo(held[i + 1]), ca, cb), b1 = act2_fn(bf_hi(held[i + 1]), ca, cb);
    if (i == 0 && first) { u0 = a0; u1 = b0; }
    float d;
    d = a0 - u0; s0 += d; q0 = fmaf(d, d, q0); d = a1 - u0; s0 += d; q0 = fmaf(d, d, q0);
    d = b0 - u1; s1 += d; q1 = fmaf(d, d, q1); d = b1 - u1; s1 += d; q1 = fmaf(d, d, q1);
    held[i] = pack_bf16(a0, a1); held[i + 1] = pack_bf16(b0, b1);
  }
}

template <int O> __device__ __forceinline__ void stage_half(Cons& c, uint32_t (&held)[64], int mode) {
  if (mode == 2) {
    uint32_t a0, a1, r0, r1;
    const uint32_t la = c.sb + OFF_LN + (c.warp * 16 + (lane_id() >> 2)) * 8;
    mbar_spin(c.sb + OFF_BAR + B_LN, 0);
    asm volatile("ld.shared.v2.b32 {%0, %1}, [%2];" : "=r"(r0), "=r"(a0) : "r"(la));
    asm volatile("ld.shared.v2.b32 {%0, %1}, [%2];" : "=r"(r1), "=r"(a1) : "r"(la + 64));
#pragma unroll
    for (int i = O; i < O + 32; i += 2) { held[i] = bf2_mul(bf2_add(held[i], a0), r0); held[i + 1] = bf2_mul(bf2_add(held[i + 1], a1), r1); }
  }
  if (O == 0 && mode == 3) {
#pragma unroll
    for (int i = 0; i < 64; i++) held[i] = bf2_mul(held[i], BF2_HALF);
  }
  stage_acquire(c);
  stage_chunks<2>(c.sb + OFF_Q0 + c.warp * 2048, 16384, held + O);
  stage_commit(c);
}

__device__ __forceinline__ void gemm_seg(float (&acc)[128], uint32_t (&held)[64], Cons& c, const Params& p, Shadow& sh, int nsteps) {
  const bool elected = lane_id() == 0 && (c.warp & 3) < 2;
  uint32_t rel;
  asm("mapa.shared::cluster.u32 %0, %1, %2;" : "=r"(rel) : "r"(c.sb + OFF_BAR + B_GE), "r"((uint32_t)(c.warp & 1)));
  gemm_step<true>(acc, c);
  uint32_t prev = c.g.s;
  ring_adv<4>(c.g);
  int k = 1;
#define G_STEP()                                                                                                       \
  { gemm_step<false>(acc, c);                                                                                          \
    wgmma_wait<1>();                                                                                                   \
    if (elected) asm volatile("mbarrier.arrive.shared::cluster.b64 _, [%0];" :: "r"(rel + 8 * prev) : "memory");       \
    prev = c.g.s; ring_adv<4>(c.g);                                                                                    \
    k++; }
  if (sh.act != 0) {
    float u0 = 0.f, u1 = 0.f, s0 = 0.f, s1 = 0.f, q0 = 0.f, q1 = 0.f;
    const float ca = sh.act == 3 ? 0.5f : GELU_A, cb = sh.act == 3 ? 0.f : GELU_B;
    const int rb = nsteps >= ACT_REP ? 2 : 1, ra = sh.act == 2 ? 0 : rb;
#define G_STEPS(N) { _Pragma("unroll 1") for (int r = 0; r < (N); r++) G_STEP() }
#pragma unroll 1
    for (int q = 0;; q++) {
      act_block<0>(held, ca, cb, q == 0, u0, u1, s0, s1, q0, q1);
      G_STEPS(ra)
      act_block<4>(held, ca, cb, false, u0, u1, s0, s1, q0, q1);
      G_STEPS(rb)
      act_block<8>(held, ca, cb, false, u0, u1, s0, s1, q0, q1);
      G_STEPS(ra)
      act_block<12>(held, ca, cb, false, u0, u1, s0, s1, q0, q1);
      rotate16(held);
      if (q == 3) break;
      G_STEPS(rb)
    }
    if (sh.act == 2) {
      const int zi = get_item(p, 0);
      const int ln = lane_id(), row0 = (((zi >> 5) & 31) * 2 + (blockIdx.x & 1)) * 128 + c.warp * 16 + (ln >> 2), ql = ln & 3;
      const float m0 = fmaf(s0, 1.f / 64, u0), m1 = fmaf(s1, 1.f / 64, u1);
      q0 -= s0 * s0 * (1.f / 64); q1 -= s1 * s1 * (1.f / 64);
      const float mu0 = quad_sum(m0) * 0.25f, mu1 = quad_sum(m1) * 0.25f;
      q0 = quad_sum(fmaf(64.f * (m0 - mu0), m0 - mu0, q0)); q1 = quad_sum(fmaf(64.f * (m1 - mu1), m1 - mu1, q1));
      if (ql < 2) st_tagged(&g_stats[((row0 >> 7) * 8 + (zi & 31)) * 128 + (row0 & 127) + 8 * ql], ql ? mu1 : mu0, ql ? q1 : q0, load_tag(c));
      if (ln == 0) mbar_arrive(c.sb + OFF_BAR + B_PUB);
    }
  }
  const int s0 = sh.store == 0 ? -9 : k + (sh.store == 2 ? Z_DELAY : (sh.store == 1 ? Q_DELAY : 1)), s1 = sh.store == 3 ? -9 : s0 + (sh.store == 1 ? Q_GAP : Z_GAP);
#pragma unroll 1
  while (k < nsteps) {
    G_STEP()
    if (k == s0) stage_half<0>(c, held, sh.store);
    else if (k == s1) stage_half<32>(c, held, sh.store);
    if (k == nsteps - 2 && c.warp >= 4) named_sync(6);
  }
  if (c.warp < 4) asm volatile("bar.arrive 6, 256;" ::: "memory");
  wgmma_wait<0>();
  fence_regs(acc);
  if (elected) asm volatile("mbarrier.arrive.shared::cluster.b64 _, [%0];" :: "r"(rel + 8 * prev) : "memory");
  sh.store = sh.act = 0;
}

template <bool SUB> __device__ __forceinline__ void softmax_exp(const float (&S)[64], uint32_t (&P)[32], float m0, float m1, float& s0, float& s1) {
  float a0 = 0.f, a1 = 0.f, b0 = 0.f, b1 = 0.f;
#pragma unroll
  for (int j = 0; j < 16; j++) {
    const float p0 = ex2(SUB ? S[4 * j] - m0 : S[4 * j]), p1 = ex2(SUB ? S[4 * j + 1] - m0 : S[4 * j + 1]);
    const float p2 = ex2(SUB ? S[4 * j + 2] - m1 : S[4 * j + 2]), p3 = ex2(SUB ? S[4 * j + 3] - m1 : S[4 * j + 3]);
    a0 += p0; b0 += p1; a1 += p2; b1 += p3;
    P[2 * j] = pack_bf16(p0, p1); P[2 * j + 1] = pack_bf16(p2, p3);
  }
  s0 = a0 + b0; s1 = a1 + b1;
}
__device__ __forceinline__ void row_max(const float (&S)[64], float& x0, float& x1) {
  float a0 = fmaxf(S[0], S[1]), a1 = fmaxf(S[2], S[3]);
#pragma unroll
  for (int j = 1; j < 16; j++) { a0 = fmaxf(a0, fmaxf(S[4 * j], S[4 * j + 1])); a1 = fmaxf(a1, fmaxf(S[4 * j + 2], S[4 * j + 3])); }
  x0 = quad_max(a0); x1 = quad_max(a1);
}

__device__ __forceinline__ void issue_qk(float (&S)[64], uint32_t da, uint32_t db) {
#pragma unroll
  for (int kk = 0; kk < 8; kk++) {
    const uint32_t o = (kk >> 2) * 1024 + (kk & 3) * 2;
    wgmma_m64n128k16_ss_tb0(S, DESC_HI | (da + o), DESC_HI | (db + o), kk > 0);
  }
}
__device__ __forceinline__ void issue_pv(float (&O)[64], const uint32_t (&P)[32], uint32_t db, int acc) {
#pragma unroll
  for (int kk = 0; kk < 8; kk++) wgmma_m64n128k16_rs_tb1(O, P[4 * kk], P[4 * kk + 1], P[4 * kk + 2], P[4 * kk + 3], DESC_HI | (db + kk * 128), (acc || kk > 0));
}

__device__ __forceinline__ void att_pack(const float (&O)[64], uint32_t (&pk)[32], float i0, float i1) {
#pragma unroll
  for (int j = 0; j < 16; j++) {
    pk[2 * j] = pack_bf16(O[4 * j] * i0, O[4 * j + 1] * i0);
    pk[2 * j + 1] = pack_bf16(O[4 * j + 2] * i1, O[4 * j + 3] * i1);
  }
}
__device__ __forceinline__ void att_stage(Cons& c, const uint32_t (&pk)[32], uint32_t qbuf) {
  stage_chunks<2>(c.sb + (qbuf ? OFF_Q1 : OFF_Q0) + c.warp * 2048, 16384, pk);
  stage_commit(c);
}

#define ATT_ISSUE(PIN, ACC, PV)                                                                                        \
  wgmma_fence();                                                                                                       \
  issue_qk(S, qd, kd); wgmma_commit();                                                                                 \
  if (g > 1) release_slot(c, vrel);                                                                                    \
  vready = mbar_test(vbar, vph) && g >= 3 && g != 16;                                                                  \
  if (PV) {                                                                                                            \
    mbar_spin(vbar, vph);                                                                                              \
    wgmma_fence();                                                                                                     \
    issue_pv(O, PIN, vd, ACC); wgmma_commit();                                                                         \
  } else {                                                                                                             \
    asm volatile("wgmma.commit_group.sync.aligned; // empty" ::: "memory");                                            \
  }                                                                                                                    \
  krel = kbar + (B_KE - B_KF); vrel = vbar + (B_KE - B_KF);                                                            \
  g++;                                                                                                                 \
  if (g < total) { kd = kd0 + kv.s * (KV_SLOT >> 4); kbar = bars + B_KF + 8 * kv.s; kph = kv.ph; ring_adv<5>(kv); }    \
  vd = vd0 + kv.s * (KV_SLOT >> 4); vbar = bars + B_KF + 8 * kv.s; vph = kv.ph; ring_adv<5>(kv);

#define ATT_WAIT_S()                                                                                                   \
  wgmma_wait<1>();                                                                                                     \
  fence_regs(S);                                                                                                       \
  release_slot(c, krel);                                                                                               \
  if (c.warp == 2) asm volatile("st.volatile.shared.u32 [%0], %1;" :: "r"(bars + B_PROG), "r"(g) : "memory");

#define ATT_SOFTMAX(POUT, FIRST)                                                                                       \
  fresh = false;                                                                                                       \
  _Pragma("unroll 1")                                                                                                  \
  while (true) {                                                                                                       \
    if (__builtin_expect(fresh, 0)) {                                                                                  \
      float x0, x1;                                                                                                    \
      row_max(S, x0, x1);                                                                                              \
      if (FIRST) m0 = m1 = -1e38f;                                                                                     \
      x0 = fmaxf(x0, m0); x1 = fmaxf(x1, m1);                                                                          \
      f0 = ex2(m0 - x0); f1 = ex2(m1 - x1);                                                                            \
      m0 = x0; m1 = x1; l0 *= f0; l1 *= f1;                                                                            \
      zero = false;                                                                                                    \
    }                                                                                                                  \
    if (zero) {                                                                                                        \
      softmax_exp<false>(S, POUT, m0, m1, s0, s1);                                                                     \
      kready = mbar_test_a(kbar, kph);                                                                                 \
      bad = !(s0 <= SM_HI && s1 <= SM_HI) || ((FIRST) && (s0 < SM_LO || s1 < SM_LO));                                  \
    } else {                                                                                                           \
      softmax_exp<true>(S, POUT, m0, m1, s0, s1);                                                                      \
      kready = mbar_test(kbar, kph);                                                                                   \
      bad = !(s0 <= SM_THR && s1 <= SM_THR);                                                                           \
    }                                                                                                                  \
    kready = kready && vready;                                                                                         \
    slow = fresh || __any_sync(0xffffffffu, bad || !kready);                                                           \
    if (__builtin_expect(!slow, 1)) break;                                                                             \
    if (fresh || !__any_sync(0xffffffffu, bad)) break;                                                                 \
    fresh = true;                                                                                                      \
  }                                                                                                                    \
  l0 += s0; l1 += s1;                                                                                                  \
  wgmma_wait<0>(); fence_regs(O);

#define ATT_RESCALE()                                                                                                  \
  { _Pragma("unroll")                                                                                                  \
    for (int i = 0; i < 16; i++) { O[4 * i] *= f0; O[4 * i + 1] *= f0; O[4 * i + 2] *= f1; O[4 * i + 3] *= f1; } }

__device__ __forceinline__ void att_stagger(const Cons& c, int g) {
  if (c.warp >= 4)
    asm volatile("{\n.reg .pred p;\n.reg .s32 v;\nLOOP:\nld.volatile.shared.s32 v, [%0];\nsetp.le.s32 p, v, %1;\n@p bra LOOP;\n}" :: "r"(c.sb + OFF_BAR + B_PROG), "r"(g) : "memory");
}

__device__ __forceinline__ void att_run(Cons& c, const Params& p, int it, int n) {
  const uint32_t bars = c.sb + OFF_BAR;
  float S[64], O[64];
  uint32_t P0[32], P1[32];
#pragma unroll
  for (int i = 0; i < 64; i++) O[i] = 0.f;
#pragma unroll
  for (int i = 0; i < 32; i++) P0[i] = P1[i] = 0u;
  fence_regs(O); fence_regs(P0); fence_regs(P1);
  float m0 = 0.f, m1 = 0.f, l0 = 0.f, l1 = 0.f, f0 = 1.f, f1 = 1.f, s0, s1, pl0 = 0.f, pl1 = 0.f;
  const int total = 16 * n;
  int g = 0;
  Ring kv = {1, 0};
  uint32_t kbar = bars + B_KF, kph = 0, vbar = bars + B_KF, vph = 0, krel, vrel = 0;
  const uint32_t kd0 = (uint32_t)make_desc(c.sb, 16, 1024), vd0 = (uint32_t)make_desc(c.sb, 16384, 1024);
  uint32_t qd = kd0 + ((OFF_Q0 + (c.warp >> 2) * 8192) >> 4), kd = kd0, vd = vd0;
  bool fresh, kready, vready, bad, slow, zero = true;
  mbar_spin(bars + B_QF, 0);
  mbar_spin(bars + B_KF, 0);
  att_stagger(c, 0);
#pragma unroll 1
  while (true) {
    ATT_ISSUE(P1, 1, g > 0)
    const bool first = ((g - 1) & 15) == 0;
    ATT_WAIT_S()
    ATT_SOFTMAX(P0, first)
    if (__builtin_expect(slow || first, 0)) {
      if (first) {
        if (g > 1) {
          att_pack(O, P1, pl0, pl1);
          att_stage(c, P1, ((g >> 4) & 1) ^ 1);
        }
      } else if (fresh) ATT_RESCALE();
      if (slow) {
        mbar_spin(kbar, kph);
        if (__any_sync(0xffffffffu, !kready)) att_stagger(c, g);
      }
    }
    ATT_ISSUE(P0, !first, true)
    ATT_WAIT_S()
    ATT_SOFTMAX(P1, false)
    if (__builtin_expect(slow || ((g + QW) & 15) <= QW, 0)) {
      if (fresh) ATT_RESCALE();
      if (g == total) break;
      if (slow) {
        mbar_spin(kbar, kph);
        if (__any_sync(0xffffffffu, !kready)) att_stagger(c, g);
      }
      if (((g + QW) & 15) == 0 && g + QW < total) { const int t = (g + QW) >> 4; mbar_spin(bars + B_QF + 8 * (t & 1), (t >> 1) & 1); }
      if ((g & 15) == 0) {
        qd = kd0 + ((((g & 16) ? OFF_Q1 : OFF_Q0) + (c.warp >> 2) * 8192) >> 4);
        pl0 = __fdividef(1.f, quad_sum(l0)); pl1 = __fdividef(1.f, quad_sum(l1));
        m0 = m1 = l0 = l1 = 0.f; zero = true;
      }
    }
  }
  release_slot(c, vrel);
  mbar_spin(vbar, vph);
  wgmma_fence();
  issue_pv(O, P1, vd, 1); wgmma_commit();
  pl0 = __fdividef(1.f, quad_sum(l0)); pl1 = __fdividef(1.f, quad_sum(l1));
  wgmma_wait<0>();
  fence_regs(O);
  release_slot(c, vbar + (B_KE - B_KF));
  att_pack(O, P0, pl0, pl1);
  if ((get_item(p, it + n) >> 12) == T_END) {
    const uint32_t buf = c.sb + (((n - 1) & 1) ? OFF_Q1 : OFF_Q0) + c.warp * 2048;
    stage_chunks<2>(buf, 16384, P0);
    fence_async_smem();
    __syncwarp();
    if (elect_one()) {
      const int im = get_item(p, it + n - 1), col = ((im >> 5) & 31) * 128, row = ((im & 7) * 2 + (blockIdx.x & 1)) * 128 + c.warp * 16;
      tma_store_2d(&p.tm[TS_O], buf, col, row); tma_store_2d(&p.tm[TS_O], buf + 16384, col + 64, row);
      bulk_commit();
      bulk_wait<0>();
      mbar_arrive(bars + B_STG);
    }
    __syncwarp();
  } else {
    att_stage(c, P0, (n - 1) & 1);
  }
}

__global__ void __cluster_dims__(2, 1, 1) __launch_bounds__(384, 1) fused_kernel(const __grid_constant__ Params p) {
  const uint32_t sb = smem_base();
  const uint32_t bars = sb + OFF_BAR;
  const int tid = threadIdx.x, lane = tid & 31;
  const int warp_id = __shfl_sync(0xffffffffu, tid >> 5, 0), wg = warp_id >> 2;
  const uint32_t rank = blockIdx.x & 1;
  const uint16_t* items = p.items[blockIdx.x >> 1];
  const int gw = blockIdx.x * 8 + warp_id - 4;
  uint4 xv[2][4];
  if (wg != 0 && gw < SEQ / 2) {
#pragma unroll
    for (int rr = 0; rr < 2; rr++)
#pragma unroll
      for (int i = 0; i < 4; i++) xv[rr][i] = __ldg(reinterpret_cast<const uint4*>(p.x + (size_t)(gw * 2 + rr) * DM) + i * 32 + lane);
  }
  if (warp_id == 1 && lane < TM_COUNT) asm volatile("prefetch.tensormap [%0];" :: "l"(&p.tm[lane]) : "memory");
  if (tid == 0) {
    for (int i = 0; i < 4; i++) { mbar_init(bars + B_GF + 8 * i, 1); mbar_init(bars + B_GE + 8 * i, 4); }
    for (int i = 0; i < 5; i++) { mbar_init(bars + B_KF + 8 * i, 1); mbar_init(bars + B_KE + 8 * i, 4); }
    for (int i = 0; i < 2; i++) { mbar_init(bars + B_QF + 8 * i, 1); mbar_init(bars + B_QE + 8 * i, 1); }
    mbar_init(bars + B_XF, 2); mbar_init(bars + B_XR, 2); mbar_init(bars + B_STG, 8); mbar_init(bars + B_FREE, 1); mbar_init(bars + B_GO, 1); mbar_init(bars + B_LN, 2); mbar_init(bars + B_PUB, 8);
    asm volatile("fence.mbarrier_init.release.cluster;" ::: "memory");
  }
  asm volatile("barrier.cluster.arrive.relaxed.aligned;" ::: "memory");

  if (wg == 0) {
    asm volatile("setmaxnreg.dec.sync.aligned.u32 40;");
    asm volatile("barrier.cluster.wait.acquire.aligned;" ::: "memory");
    if (warp_id >= 2 && (items[0] >> 12) == T_Z2) {
      const int r = (warp_id - 2) * 64 + 2 * lane;
      const uint2* ps = &g_stats[(((items[0] >> 5) & 31) * 2 + rank) * 1024 + r];
      uint32_t tag = 0, cnt = 0;
#pragma unroll 1
      for (;;) {
        uint4 t[7];
        bool ok = cnt > 0;
#pragma unroll
        for (int i = 0; i < 7; i++) {
          t[i] = make_uint4(0, 0, 0, 0);
          if (cnt > 0) t[i] = ld_tagged2(ps + i * 128);
        }
        float u0 = 0.f, u1 = 0.f, v0 = 0.f, v1 = 0.f;
#pragma unroll
        for (int i = 0; i < 7; i++) { ok = ok && tag_ok(t[i].x, t[i].y, tag) && tag_ok(t[i].z, t[i].w, tag); u0 += untag(t[i].x); u1 += untag(t[i].z); }
        u0 *= 1.f / 7; u1 *= 1.f / 7;
#pragma unroll
        for (int i = 0; i < 7; i++) {
          const float d0 = untag(t[i].x) - u0, d1 = untag(t[i].z) - u1;
          v0 += fmaf(256.f * d0, d0, untag(t[i].y)); v1 += fmaf(256.f * d1, d1, untag(t[i].w));
        }
        const float r0 = rsqrtf(fmaxf(v0, 0.f) * (1.f / FH) + 4e-5f), r1 = rsqrtf(fmaxf(v1, 0.f) * (1.f / FH) + 4e-5f);
        asm volatile("st.shared.v4.b32 [%0], {%1, %2, %3, %4};" :: "r"(sb + OFF_LN + r * 8), "r"(pack_bf16(r0, r0)), "r"(pack_bf16(-u0, -u0)),
                     "r"(pack_bf16(r1, r1)), "r"(pack_bf16(-u1, -u1)) : "memory");
        if (__all_sync(0xffffffffu, ok)) break;
        if (cnt == 0) {
          if (lane == 0) mbar_wait_sleep(bars + B_PUB, 0, 50);
          __syncwarp();
          asm volatile("ld.volatile.shared.u32 %0, [%1];" : "=r"(tag) : "r"(bars + B_TAG));
          __nanosleep(LN_SLEEP);
        }
        trap_if(++cnt > SPIN_LIMIT);
      }
      __syncwarp();
      if (lane == 0) mbar_arrive(bars + B_LN);
      __syncwarp();
    }
    if (warp_id == 0) {
      trap_if(sb & 1023);
      Ring g = {0, 1};
      int it = 0;
      uint32_t xph = 0;
      if (elect_one()) {
#pragma unroll 1
        for (;; it++) {
          const int item = items[it], type = item >> 12, b = item & 31, row = (((item >> 5) & 31) * 2 + rank) * 128;
          if (type >= T_ATT) break;
#pragma unroll 1
          for (int seg = 0; seg < (type == T_U ? 2 : 1); seg++) {
            const CUtensorMap* tA = &p.tm[seg ? TM_WSP : TM_XN];
            const CUtensorMap* tB = &p.tm[seg ? TM_Z2 : (type == T_Q ? TM_WQ : TM_WIN)];
            const int bchunk = b * 4 + (type == T_Z2 ? 28 : 0) + rank * 2;
            const unsigned* fl = seg ? &g_flags[F_Z2 + b * 32] : &g_flags[F_XN + (row >> 2)];
            const unsigned tgt = seg ? 16 : 128;
            int k = 0;
            if (it == 0 && seg == 0) {
              for (; k < 4; k++) {
                mbar_expect_tx(bars + B_GF + 8 * k, G_STAGE);
                tma_load_3d_mc(sb + k * G_STAGE + G_A + rank * 16384, tB, k * 64, bchunk, bars + B_GF + 8 * k);
              }
              g.ph ^= 1;
            }
            if (seg || type != T_U) { flag_wait(fl, tgt); fence_async_global(); }
            for (int x = 0; x < k; x++) tma_load_2d(sb + x * G_STAGE, tA, x * 64, row, bars + B_GF + 8 * x);
            if (it == 0) asm volatile("st.volatile.shared.v4.u32 [%0], {%1, %2, %2, %2};" :: "r"(bars + B_TAG), "r"(__ldcg(&g_epoch) % 4095u + 1), "r"(0) : "memory");
#pragma unroll 1
            for (; k < (seg ? 32 : 16); k++) {
              mbar_wait(bars + B_GE + 8 * g.s, g.ph);
              const uint32_t st = sb + g.s * G_STAGE, fb = bars + B_GF + 8 * g.s;
              mbar_expect_tx(fb, G_STAGE);
              tma_load_2d(st, tA, k * 64, row, fb);
              tma_load_3d_mc(st + G_A + rank * 16384, tB, k * 64, bchunk, fb);
              ring_adv<4>(g);
            }
          }
        }
      }
      { const int e = __ffs(__ballot_sync(0xffffffffu, elect_one())) - 1; it = __shfl_sync(0xffffffffu, it, e); g.ph = __shfl_sync(0xffffffffu, g.ph, e); }
      const int n = ((items[it] >> 10) & 3) + 3;
      Ring kv = {0, 1};
      if (elect_one()) {
        int prow = 0;
        {
          const int im = items[it];
          tma_prefetch_2d(&p.tm[(im & 1) ? TM_V : TM_K], rank * 64, ((im >> 5) & 31) * SEQ + ((im & 7) >> 1) * 128);
        }
#pragma unroll 1
        for (int x = 0; x <= 32 * n; x++) {
          const int gb = x >> 1, t = gb >> 4;
          const int hrow = ((items[it + t] >> 5) & 31) * SEQ;
          const bool isv = (x & 1) || x == 32 * n;
          if (x != 1) {
            if (x == 0 || x == 2) mbar_wait(bars + B_GE + 4 * x, g.ph);
            if (x == 4) { mbar_wait(bars + B_XF, xph); xph ^= 1; }
            mbar_wait(bars + B_KE + 8 * kv.s, kv.ph);
            mbar_expect_tx(bars + B_KF + 8 * kv.s, KV_SLOT);
            tma_load_2d_mc(sb + kv.s * KV_SLOT + rank * 16384, &p.tm[isv ? TM_V : TM_K], rank * 64, isv ? prow : hrow + (gb & 15) * 128, bars + B_KF + 8 * kv.s);
            ring_adv<5>(kv);
          }
          {
            const int gp = gb + KV_PF, ip = items[it + (gp >> 4)];
            if (gp < 16 * n && ((gp ^ ip) & (7 >> ((ip >> 3) & 3))) == 0) tma_prefetch_2d(&p.tm[(x & 1) ? TM_V : TM_K], rank * 64, ((ip >> 5) & 31) * SEQ + (gp & 15) * 128);
          }
          if (x == 32 * n - 8) mbar_arrive(bars + B_GO);
          if (x & 1) prow = hrow + (gb & 15) * 128;
          if ((x & 31) == Q_AT && t + 1 < n) {
            const int tq = t + 1;
            const int im = items[it + tq], h = (im >> 5) & 31, m = (im & 7) * 2 + rank;
            const uint32_t qb = tq & 1;
            flag_wait(&g_flags[F_Q + m * 16 + (h >> 1)], 1);
            fence_async_global();
            mbar_wait(bars + B_QE + 8 * qb, ((tq - 1) >> 1) & 1);
            const uint32_t dst = sb + (qb ? OFF_Q1 : OFF_Q0), fb = bars + B_QF + 8 * qb;
            mbar_expect_tx(fb, 32768);
            tma_load_2d(dst, &p.tm[TM_Q], h * 128, m * 128, fb);
            tma_load_2d(dst + 16384, &p.tm[TM_Q], h * 128 + 64, m * 128, fb);
          }
        }
      }
      __syncwarp();
      it += n;
      uint32_t ready = 0;
      auto wait_head = [&](int h) {
        if ((ready >> h) & 1) return;
        uint32_t cnt = 0;
        while (true) {
          asm volatile("ld.acquire.cta.shared.u32 %0, [%1];" : "=r"(ready) : "r"(bars + B_RDY) : "memory");
          if ((ready >> h) & 1) break;
          trap_if(++cnt > SPIN_LIMIT * 8);
          __nanosleep(20);
        }
        fence_async_global();
      };
      int item = items[it];
      if ((item >> 12) == T_SA) {
        const int m = ((item >> 5) & 31) * 2 + rank, b = item & 31;
        Ring dr = kv;
        wait_head(0);
#pragma unroll 1
        for (int i = 0; i < 28 + SA_STEPS; i++) {
          {
            const bool so = i >= 28;
            const int k = so ? i - 28 : i;
            if (so) wait_head(k >> 1);
            if (elect_one()) {
              if (i < 4) { for (int x = 0; x < ((0x1022 >> (4 * i)) & 3); x++) { mbar_wait(bars + B_KE + 8 * dr.s, dr.ph); ring_adv<5>(dr); } }
              if (i == 2) { mbar_wait(bars + B_XF, xph); xph ^= 1; }
              mbar_wait(bars + B_GE + 8 * g.s, g.ph);
              const uint32_t st = sb + ((g.s + 1) & 3) * G_STAGE, fb = bars + B_GF + 8 * g.s;
              mbar_expect_tx(fb, G_STAGE);
              tma_load_2d(st, &p.tm[so ? TM_O : TM_U], k * 64, m * 128, fb);
              tma_load_3d_mc(st + G_A + rank * 16384, &p.tm[so ? TM_WO : TM_WOUT], k * 64, b * 4 + rank * 2, fb);
            }
            ring_adv<4>(g);
          }
          const int ip = i + OUT_PF;
          if (ip < 28 + SA_STEPS && elect_one()) {
            const bool so = ip >= 28;
            const int k = so ? ip - 28 : ip;
            if ((ip & 3) == b && (!so || ((ready >> (k >> 1)) & 1))) tma_prefetch_2d(&p.tm[so ? TM_O : TM_U], k * 64, m * 128);
            if ((ip & 7) == (m >> 1)) tma_prefetch_3d(&p.tm[so ? TM_WO : TM_WOUT], k * 64, b * 4 + rank * 2);
          }
          __syncwarp();
        }
        item = items[++it];
      }
      if ((item >> 12) == T_FIN) {
        const bool own = item & 4;
        const int m = ((item >> 5) & 31) * 2 + rank, col = (item & 3) * 256 + (own ? 128 : 0);
        uint32_t ps = own ? FIN_SLOT0 : kv.s;
#pragma unroll 1
        for (int i = SA_STEPS; i <= 2 * NH; i++) {
          const bool extra = i == 2 * NH - FIN_PREP;
          if (extra && own) continue;
          const int k = i > 2 * NH - FIN_PREP ? i - 1 : i;
          if (!extra) wait_head(k >> 1);
          if (elect_one()) {
            if (i == SA_STEPS) {
              for (int y = k; y < k + 4; y++) if ((ready >> (y >> 1)) & 1) tma_prefetch_2d(&p.tm[TM_O], y * 64, m * 128);
            }
            if (own && i < SA_STEPS + 5) {
              const uint32_t s0 = ((0x22100u >> (4 * ps)) - 1) & 3, s1 = ((0x32110u >> (4 * ps)) - 1) & 3;
              mbar_wait(bars + B_GE + 8 * s0, g.ph ^ (s0 < g.s)); mbar_wait(bars + B_GE + 8 * s1, g.ph ^ (s1 < g.s));
            }
            if (extra) { flag_wait(&g_flags[F_S + m * 4 + (item & 3)], 2); fence_async_global(); }
            mbar_wait(bars + B_KE + 8 * kv.s, kv.ph);
            const uint32_t dst = sb + ps * KV_SLOT, fb = bars + B_KF + 8 * kv.s;
            if (++ps == 5) ps = 0;
            mbar_expect_tx(fb, KV_SLOT);
            if (!extra) {
              tma_load_2d(dst, &p.tm[TM_O], k * 64, m * 128, fb);
              tma_load_2d_mc(dst + 16384 + rank * 8192, &p.tm[TM_WO64], col + rank * 64, k * 64, fb);
            } else {
              tma_load_2d(dst, &p.tm[TM_SA], col, m * 128, fb);
              tma_load_2d(dst + 16384, &p.tm[TM_SA], col + 64, m * 128, fb);
            }
            ring_adv<5>(kv);
          }
          __syncwarp();
        }
      }
      unsigned last = 0;
      if (lane == 0 && (item >> 12) == T_FIN) mbar_wait_sleep(bars + B_XR, 0, 100);
      if (lane == 0) { __threadfence(); last = atomicInc(&g_done, gridDim.x - 1) == gridDim.x - 1; }
      last = __shfl_sync(0xffffffffu, last, 0);
      if (last) {
        for (int i = lane; i < F_TOTAL / 4; i += 32) reinterpret_cast<uint4*>(g_flags)[i] = make_uint4(0, 0, 0, 0);
        if (lane == 0) g_epoch = g_epoch + 1;
      }
    } else if (warp_id == 1) {
      if (elect_one()) {
        uint32_t ph = 0;
        int t = 0;
#pragma unroll 1
        for (int it = 0;; it++) {
          const int item = items[it], type = item >> 12, a = (item >> 5) & 31, b = item & 31;
          if (type == T_END) break;
          const int nt = items[it + 1] >> 12;
          int row = (a * 2 + rank) * 128, col = b * 256;
          unsigned* f = &g_flags[F_S + (a * 2 + rank) * 4 + b];
          int tm = TS_G, npair = 2;
          bool quad = false;
          uint32_t src = sb + OFF_Q0;
          if (type == T_Z2) { tm = TS_Z2; f = &g_flags[F_Z2 + b * 32]; }
          else if (type == T_Q) { tm = TS_Q; f = &g_flags[F_Q + (a * 2 + rank) * 16 + b]; if (nt >= T_ATT) { npair = 0; quad = true; } }
          else if (type == T_U) { tm = TS_U; f = &g_flags[F_U + (a * 2 + rank) * 32]; npair = 0; quad = true; }
          else if (type == T_ATT) { tm = TS_O; f = &g_flags[F_O + ((b & 7) * 2 + rank) * 32 + a]; npair = 1; row = ((b & 7) * 2 + rank) * 128; col = a * 128; if (t & 1) src = sb + OFF_Q1; }
          else if (type == T_FIN) npair = 1;
          auto load_fin = [&](int fi, int tmi, uint32_t qb) {
            const int fc = (fi & 3) * 256 + ((fi & 4) ? 128 : 0), fr = (((fi >> 5) & 31) * 2 + rank) * 128;
            mbar_expect_tx(bars + B_QF + 8 * qb, 32768);
            tma_load_2d(sb + (qb ? OFF_Q1 : OFF_Q0), &p.tm[tmi], fc, fr, bars + B_QF + 8 * qb);
            tma_load_2d(sb + (qb ? OFF_Q1 : OFF_Q0) + 16384, &p.tm[tmi], fc + 64, fr, bars + B_QF + 8 * qb);
          };
          if (type == T_ATT && nt == T_FIN) load_fin(items[it + 1], TM_X, (t & 1) ^ 1);
          if (type == T_FIN) {
            if (!(item & 4)) { flag_wait(&g_flags[F_S + (a * 2 + rank) * 4 + (b & 3)], 1); fence_async_global(); load_fin(item, TM_G, (t & 1) ^ 1); }
            mbar_arrive(bars + B_XR);
          }
#pragma unroll 1
          for (int op = 0; op < npair + quad; op++) {
            const bool q = op == npair;
            const int c0 = (q || type == T_SA) ? col : col + op * 128;
            mbar_wait_sleep(bars + B_STG, ph, (type == T_ATT && nt == T_ATT) ? SW_ATT : SW_NS);
            if (type == T_FIN) break;
            ph ^= 1;
            fence_async_smem();
            if (type == T_SA && op == 1) { tm = TS_SA; load_fin(items[it + 1], TM_X, 1); }
            int c1 = c0;
            if (q) {
              const CUtensorMap* tb = &p.tm[type == T_U ? TM_U : TM_Q];
              tma_store_2d(tb, sb + 2 * G_STAGE, c0, row);
              tma_store_2d(tb, sb + 3 * G_STAGE, c0 + 64, row);
              bulk_commit();
              bulk_wait_read<0>();
              mbar_arrive_cta(bars + B_XF, 0); mbar_arrive_cta(bars + B_XF, 1);
              src = sb + OFF_Q1; c1 += 128;
            }
            if (nt != T_END) {
#pragma unroll 1
              for (int r = 0; r < 256; r += ST_ROWS) {
                tma_store_2d(&p.tm[tm], src + r * 128, c1 + (r >> 7) * 64, row + (r & 127));
                bulk_commit();
                bulk_wait_read<ST_FLY>();
                if (q) __nanosleep(U_PACE);
              }
            }
            bulk_wait_read<0>();
            mbar_arrive(bars + B_FREE);
            if (type == T_ATT && (t & 1) && (nt == T_SA || (items[it + 2] >> 12) == T_SA)) { mbar_arrive_cta(bars + B_XF, 0); mbar_arrive_cta(bars + B_XF, 1); }
            if (type == T_ATT) mbar_arrive(bars + B_QE + 8 * (t & 1));
            else if (nt == T_ATT) mbar_arrive(bars + B_QE + 8);
            if (op + 1 >= npair || type == T_SA) {
              bulk_wait<0>();
              red_release(f, 1);
            }
          }
          if (type == T_ATT) t++;
          else if (t == 0 && (items[it + 1] >> 12) < T_ATT && (items[it + 2] >> 12) == T_ATT) {
            const int im = items[it + 2], h = (im >> 5) & 31, m = (im & 7) * 2 + rank;
            flag_wait(&g_flags[F_Q + m * 16 + (h >> 1)], 1);
            fence_async_global();
            mbar_expect_tx(bars + B_QF, 32768);
            tma_load_2d(sb + OFF_Q0, &p.tm[TM_Q], h * 128, m * 128, bars + B_QF);
            tma_load_2d(sb + OFF_Q0 + 16384, &p.tm[TM_Q], h * 128 + 64, m * 128, bars + B_QF);
          }
        }
      }
      __syncwarp();
    } else if (warp_id == 2) {
      int it = 0;
      while ((items[it] >> 12) <= T_ATT) it++;
      if ((items[it] >> 12) != T_END) {
        const bool sa = (items[it] >> 12) == T_SA;
        const int m = ((items[it] >> 5) & 31) * 2 + rank;
        if (lane == 0) {
          mbar_wait_sleep(bars + B_GO, 0, 500);
          if (sa) {
            const int b = items[it] & 3;
            flag_wait(&g_flags[F_U + m * 32], 7);
            fence_async_global();
            for (int y = b; y < OUT_PF; y += 4) tma_prefetch_2d(&p.tm[TM_U], y * 64, m * 128);
            tma_prefetch_3d(&p.tm[TM_WOUT], (m >> 1) * 64, b * 4 + rank * 2);
          }
          if (!sa) for (int y = m * 4 + (items[it] & 3); y < 16 * (NH - SA_HEADS); y += 64) tma_prefetch_3d(&p.tm[TM_WO], (2 * SA_HEADS + (y >> 3)) * 64, (y & 7) * 2);
        }
        __syncwarp();
        uint32_t cnt = 0;
        while (true) {
          const uint32_t r = __ballot_sync(0xffffffffu, ld_acquire(&g_flags[F_O + m * 32 + lane]) != 0);
          if (lane == 0) asm volatile("st.release.cta.shared.u32 [%0], %1;" :: "r"(bars + B_RDY), "r"(r) : "memory");
          if (r == ~0u) break;
          trap_if(++cnt > SPIN_LIMIT);
          __nanosleep(r >> 28 ? 20 : 300);
        }
        if (lane == 0) mbar_arrive(bars + B_XR);
      }
      __syncwarp();
    }
    cluster_sync_relaxed();
  } else {
    Cons c;
    c.sb = sb; c.warp = warp_id - 4; c.g = {0, 0}; c.fph = 1; c.rot = 0;
    if (gw < SEQ / 2) {
      float f[2][32], rs[2];
#pragma unroll
      for (int rr = 0; rr < 2; rr++) {
#pragma unroll
        for (int i = 0; i < 4; i++) {
          const uint4 v = xv[rr][i];
          f[rr][8 * i + 0] = bf_lo(v.x); f[rr][8 * i + 1] = bf_hi(v.x); f[rr][8 * i + 2] = bf_lo(v.y); f[rr][8 * i + 3] = bf_hi(v.y);
          f[rr][8 * i + 4] = bf_lo(v.z); f[rr][8 * i + 5] = bf_hi(v.z); f[rr][8 * i + 6] = bf_lo(v.w); f[rr][8 * i + 7] = bf_hi(v.w);
        }
        float s = 0.f;
#pragma unroll
        for (int i = 0; i < 32; i++) s += f[rr][i];
#pragma unroll
        for (int o = 16; o; o >>= 1) s += __shfl_xor_sync(0xffffffffu, s, o);
        const float mean = s * (1.f / DM);
        float q = 0.f;
#pragma unroll
        for (int i = 0; i < 32; i++) { f[rr][i] -= mean; q = fmaf(f[rr][i], f[rr][i], q); }
#pragma unroll
        for (int o = 16; o; o >>= 1) q += __shfl_xor_sync(0xffffffffu, q, o);
        rs[rr] = rsqrtf(q * (1.f / DM) + 1e-5f);
      }
      uint4* dst = reinterpret_cast<uint4*>(g_xn + (size_t)gw * 2 * DM) + lane;
#pragma unroll
      for (int rr = 0; rr < 2; rr++) {
        const float r = rs[rr];
#pragma unroll
        for (int i = 0; i < 4; i++) {
          const float* y = &f[rr][8 * i];
          dst[rr * 128 + i * 32] = make_uint4(pack_bf16(y[0] * r, y[1] * r), pack_bf16(y[2] * r, y[3] * r), pack_bf16(y[4] * r, y[5] * r), pack_bf16(y[6] * r, y[7] * r));
        }
      }
      named_sync(7);
      if (tid == 128) red_release(&g_flags[F_XN + (gw >> 6) * 32], 16);
    }
    asm volatile("setmaxnreg.inc.sync.aligned.u32 232;");
    asm volatile("barrier.cluster.wait.acquire.aligned;" ::: "memory");
    int natt = 0;
    int it = 0;
    uint32_t held[64];
#pragma unroll
    for (int i = 0; i < 64; i++) held[i] = 0u;
    Shadow sh = {0, 0};
    float facc[64];
#pragma unroll 1
    while (true) {
      const int item = get_item(p, it), type = item >> 12, a = (item >> 5) & 31;
      c.warp = fresh_warp();
      if (type == T_ATT) {
        const int n = ((item >> 10) & 3) + 3;
        att_run(c, p, it, n);
#pragma unroll
        for (int i = 0; i < 64; i++) held[i] = 0u;
        natt = n;
        it += n;
        c.rot = 1;
        if ((get_item(p, it) >> 12) == T_SA) continue;
#pragma unroll
        for (int i = 0; i < 64; i++) facc[i] = 0.f;
        break;
      }
      float acc[128];
      const bool sa = type == T_SA;
      bool more = type >= T_U;
      int nsteps = sa ? 28 : 16;
      const bool direct = (get_item(p, it + 1) >> 12) >= T_ATT;
      uint32_t bias0 = 0, bias1 = 0;
#pragma unroll 1
      while (true) {
        gemm_seg(acc, held, c, p, sh, nsteps);
        if (!more && direct && !sa) pp_arrive(c.warp >= 4);
        if (type == T_Q) {
#pragma unroll
          for (int i = 0; i < 128; i++) acc[i] *= SM_C;
        }
        if (!more && direct) break;
#pragma unroll
        for (int i = 0; i < 64; i++) held[i] = pack_bf16(acc[2 * i], acc[2 * i + 1]);
        if (!more) break;
        more = false;
        nsteps = sa ? SA_STEPS : 32;
        sh.act = sa ? 3 : 1;
        if (sa) {
          sh.store = 3;
        } else {
          const int row0 = (a * 2 + rank) * 128 + c.warp * 16 + (lane_id() >> 2);
          asm volatile("ld.global.nc.u16 %0, [%1];" : "=r"(bias0) : "l"(p.b_sp + row0));
          asm volatile("ld.global.nc.u16 %0, [%1];" : "=r"(bias1) : "l"(p.b_sp + row0 + 8));
        }
      }
      c.warp = fresh_warp();
      if (direct) {
        const uint32_t hb0 = bf2_mul(bias0 * 0x10001u, BF2_HALF), hb1 = bf2_mul(bias1 * 0x10001u, BF2_HALF);
        stage_acquire(c);
#pragma unroll
        for (int h = 0; h < 2; h++) {
          uint32_t pk[32];
#pragma unroll
          for (int i = 0; i < 32; i++) pk[i] = pack_bf16(acc[64 * h + 2 * i], acc[64 * h + 2 * i + 1]);
          if (type == T_U) {
#pragma unroll
            for (int i = 0; i < 32; i++) pk[i] = bf2_mul(bf2_fma(pk[i], BF2_HALF, (i & 1) ? hb1 : hb0), held[32 * h + i]);
          }
          if (h) pp_sync(c.warp >= 4);
          stage_chunks<2>(sb + (h ? OFF_Q1 : (sa ? OFF_Q0 : 2 * G_STAGE)) + c.warp * 2048, (h || sa) ? 16384 : G_STAGE, pk);
          if (sa) break;
        }
        stage_commit(c);
        if (sa) {
#pragma unroll
          for (int i = 0; i < 64; i++) facc[i] = acc[64 + i];
          it++;
          break;
        }
      } else if (type == T_Q) {
        sh.store = 1;
      } else {
        sh.act = sh.store = 2;
      }
      it++;
    }
    const int fin = get_item(p, it);
    if ((fin >> 12) == T_FIN) {
      c.warp = fresh_warp();
      const bool own = fin & 4;
      Ring kv = {(uint32_t)(32 * natt) % 5, ((uint32_t)(32 * natt) / 5) & 1};
      uint32_t prev = 0, ps = own ? FIN_SLOT0 : kv.s;
      fence_regs(facc);
      auto fin_steps = [&](int k0, int k1) {
#pragma unroll 1
        for (int k = k0; k < k1; k++) {
          mbar_spin(bars + B_KF + 8 * kv.s, kv.ph);
          const uint32_t st = ((c.sb & 0x3FFFF) >> 4) + ps * (KV_SLOT >> 4);
          if (++ps == 5) ps = 0;
          const uint32_t da = st + (c.warp >> 2) * 512 + (1u << 16), db = st + 1024 + ((8192u >> 4) << 16);
          wgmma_fence();
#pragma unroll
          for (int kk = 0; kk < 4; kk++) wgmma_m64n128k16_ss_tb1(facc, DESC_HI | (da + kk * 2), DESC_HI | (db + kk * 128), 1);
          wgmma_commit();
          wgmma_wait<1>();
          if (k > SA_STEPS) release_slot(c, prev);
          prev = bars + B_KE + 8 * kv.s;
          ring_adv<5>(kv);
        }
      };
      const int kp = (own && ((fin >> 5) & 31) == 7) ? SA_STEPS + 5 : 2 * NH - FIN_PREP - (own ? OWN_OFF : 0);
      fin_steps(SA_STEPS, kp);
      const uint32_t ln = lane_id(), xb = own ? 1 : natt & 1;
      const uint32_t lo = c.warp * 2048 + ((ln & 15) << 7);
      uint32_t xs[32];
      auto load_tile = [&](uint32_t base, uint32_t* d) {
#pragma unroll
        for (int i = 0; i < 8; i++) ldmatrix_x4(base + lo + (i >> 2) * 16384 + (((2 * (i & 3) + (ln >> 4)) ^ (ln & 7)) << 4), d[4 * i], d[4 * i + 1], d[4 * i + 2], d[4 * i + 3]);
      };
      const uint32_t xa = sb + (xb ? OFF_Q1 : OFF_Q0);
      mbar_spin(bars + B_QF + 8 * xb, ((natt + 1 - xb) >> 1) & 1);
      load_tile(xa, xs);
      if (!own) {
        mbar_spin(bars + B_QF + 8 * (xb ^ 1), ((natt + xb) >> 1) & 1);
        load_tile(sb + (xb ? OFF_Q0 : OFF_Q1), held + 32);
      }
      float gf[64], rf[64];
#pragma unroll
      for (int i = 0; i < 32; i++) { gf[2 * i] = bf_lo(held[32 + i]); gf[2 * i + 1] = bf_hi(held[32 + i]); rf[2 * i] = bf_lo(xs[i]); rf[2 * i + 1] = bf_hi(xs[i]); }
      if (!own) {
        mbar_spin(bars + B_KF + 8 * kv.s, kv.ph);
#pragma unroll
        for (int i = 0; i < 8; i++) {
          uint32_t t[4];
          ldmatrix_x4(sb + ps * KV_SLOT + lo + (i >> 2) * 16384 + (((2 * (i & 3) + (ln >> 4)) ^ (ln & 7)) << 4), t[0], t[1], t[2], t[3]);
#pragma unroll
          for (int y = 0; y < 4; y++) {
            rf[8 * i + 2 * y] = fmaf(bf_lo(t[y]), gf[8 * i + 2 * y], rf[8 * i + 2 * y]);
            rf[8 * i + 2 * y + 1] = fmaf(bf_hi(t[y]), gf[8 * i + 2 * y + 1], rf[8 * i + 2 * y + 1]);
          }
        }
        wg_any(c.warp >= 4, false);
        release_slot(c, bars + B_KE + 8 * kv.s);
        if (++ps == 5) ps = 0;
        ring_adv<5>(kv);
      }
      fence_regs(gf); fence_regs(rf);
      fin_steps(kp, 2 * NH);
      wgmma_wait<0>();
      fence_regs(facc);
#pragma unroll
      for (int i = 0; i < 32; i++) xs[i] = pack_bf16(fmaf(facc[2 * i], gf[2 * i], rf[2 * i]), fmaf(facc[2 * i + 1], gf[2 * i + 1], rf[2 * i + 1]));
      __syncwarp();
      stage_chunks<2>(xa + c.warp * 2048, 16384, xs);
      fence_async_smem();
      __syncwarp();
      if (elect_one()) {
        const int col = (fin & 3) * 256 + (own ? 128 : 0), row = (((fin >> 5) & 31) * 2 + rank) * 128 + c.warp * 16;
        tma_store_2d(&p.tm[TS_OUT], xa + c.warp * 2048, col, row);
        tma_store_2d(&p.tm[TS_OUT], xa + c.warp * 2048 + 16384, col + 64, row);
        bulk_commit();
        mbar_arrive(bars + B_STG);
        bulk_wait_read<0>();
      }
    }
    __syncwarp();
    cluster_sync_relaxed();
  }
}

typedef CUresult (*PFN_encodeTiled)(CUtensorMap*, CUtensorMapDataType, cuuint32_t, void*, const cuuint64_t*, const cuuint64_t*, const cuuint32_t*, const cuuint32_t*,
                                    CUtensorMapInterleave, CUtensorMapSwizzle, CUtensorMapL2promotion, CUtensorMapFloatOOBfill);
static PFN_encodeTiled s_encode = nullptr;
static void tm_2d(CUtensorMap* tm, const void* ptr, uint64_t rows, uint64_t cols, uint32_t box_rows) {
  cuuint64_t dims[2] = {cols, rows}; cuuint64_t strides[1] = {cols * 2}; cuuint32_t box[2] = {64, box_rows}; cuuint32_t es[2] = {1, 1};
  CUresult r = s_encode(tm, CU_TENSOR_MAP_DATA_TYPE_BFLOAT16, 2, (void*)ptr, dims, strides, box, es, CU_TENSOR_MAP_INTERLEAVE_NONE,
                        CU_TENSOR_MAP_SWIZZLE_128B, CU_TENSOR_MAP_L2_PROMOTION_L2_128B, CU_TENSOR_MAP_FLOAT_OOB_FILL_NONE);
  if (r != CUDA_SUCCESS) fprintf(stderr, "tensor map encode failed (%d)\n", (int)r);
}
static void tm_3d(CUtensorMap* tm, const void* ptr, uint64_t rows, uint64_t cols) {
  cuuint64_t dims[3] = {64, rows, cols / 64}; cuuint64_t strides[2] = {cols * 2, 128}; cuuint32_t box[3] = {64, 64, 2}; cuuint32_t es[3] = {1, 1, 1};
  CUresult r = s_encode(tm, CU_TENSOR_MAP_DATA_TYPE_BFLOAT16, 3, (void*)ptr, dims, strides, box, es, CU_TENSOR_MAP_INTERLEAVE_NONE,
                        CU_TENSOR_MAP_SWIZZLE_128B, CU_TENSOR_MAP_L2_PROMOTION_L2_128B, CU_TENSOR_MAP_FLOAT_OOB_FILL_NONE);
  if (r != CUDA_SUCCESS) fprintf(stderr, "tensor map encode failed (%d)\n", (int)r);
}
static inline uint16_t mk(int type, int a, int b) { return (uint16_t)(type << 12 | a << 5 | b); }

static void build_schedule(Params& P) {
  int cnt[NCLUSTER];
  for (int c = 0; c < NCLUSTER; c++) { cnt[c] = 0; for (int i = 0; i < MAXI; i++) P.items[c][i] = mk(T_END, 0, 0); }
  auto phys = [](int c) { return c == 64 ? 9 : c == 65 ? 17 : c == 9 ? 64 : c == 17 ? 65 : c; };
  auto push = [&](int c, uint16_t v) { P.items[phys(c)][cnt[c]++] = v; };
  int natt[NCLUSTER], nq[NCLUSTER];
  for (int c = 0; c < NCLUSTER; c++) { natt[c] = c < 32 ? 3 : (c < 56 ? 5 : (c < 62 ? 4 : (c < 64 ? 3 : 5))); nq[c] = c < 56 ? 1 : (c < 62 ? 7 : (c < 64 ? 9 : 6)); }
  for (int c = 0; c < 56; c++) push(c, mk(T_Z2, c % 8, c / 8));
  int qi = 0;
  for (int slot = 0; slot < 9; slot++)
    for (int c = NCLUSTER - 1; c >= 0; c--) {
      const int first = c < 56 ? 1 : 0;
      if (slot >= first && slot < first + nq[c]) { push(c, mk(T_Q, qi % 8, qi / 8)); qi++; }
    }
  for (int c = 0; c < 56; c++) push(c, mk(T_U, c % 8, c / 8));
  int ai = 0, grp[256], own[256];
  for (int slot = 0; slot < 5; slot++)
    for (int c = 0; c < NCLUSTER; c++) {
      const int first = c < 32 ? 0 : 5 - natt[c];
      if (slot >= first && slot < first + natt[c]) { grp[ai] = slot * 2 + (c >= 64); own[ai++] = c; }
    }
  for (int i = 0; i < 256; i++) {
    int s = 0;
    for (int j = i & ~7; j < (i & ~7) + 8; j++) s += grp[j] == grp[i];
    const int share = s >= 8 ? 0 : s >= 4 ? 1 : s >= 2 ? 2 : 3;
    push(own[i], mk(T_ATT, i / 8, share << 3 | i % 8) | (natt[own[i]] - 3) << 10);
  }
  for (int c = 0; c < 32; c++) push(c, mk(T_SA, c % 8, c / 8));
  for (int c = 0; c < 64; c++) push(c, mk(T_FIN, c % 8, (c / 8) % 4 | (c < 32 ? 4 : 0)));
  if (qi != 128 || ai != 256) fprintf(stderr, "bad schedule %d %d\n", qi, ai);
}

static Params s_params;
extern "C" void kernel_launch(void* const* d_in, const int* in_sizes, int n_in, void* d_out, int out_size) {
  (void)in_sizes; (void)n_in; (void)out_size;
  if (!s_encode) {
    void* fn = nullptr; cudaDriverEntryPointQueryResult qr;
    cudaGetDriverEntryPoint("cuTensorMapEncodeTiled", &fn, cudaEnableDefault, &qr);
    s_encode = (PFN_encodeTiled)fn;
    cudaFuncSetAttribute(fused_kernel, cudaFuncAttributeMaxDynamicSharedMemorySize, SMEM_BYTES);
    build_schedule(s_params);
  }
  Params& P = s_params;
  void *xn, *q, *o, *z2, *u, *gg, *sa;
  cudaGetSymbolAddress(&gg, g_g); cudaGetSymbolAddress(&sa, g_sa);
  cudaGetSymbolAddress(&xn, g_xn); cudaGetSymbolAddress(&q, g_q); cudaGetSymbolAddress(&o, g_o);
  cudaGetSymbolAddress(&z2, g_z2); cudaGetSymbolAddress(&u, g_u);
  tm_2d(&P.tm[TM_XN], xn, SEQ, DM, 128); tm_2d(&P.tm[TM_WSP], d_in[7], SEQ, SEQ, 128); tm_2d(&P.tm[TM_U], u, SEQ, FH, 128);
  tm_2d(&P.tm[TM_O], o, SEQ, HD, 128); tm_2d(&P.tm[TM_Q], q, SEQ, HD, 128); tm_2d(&P.tm[TM_X], d_in[0], SEQ, DM, 128);
  tm_2d(&P.tm[TM_K], d_in[1], NH * SEQ, 128, 128); tm_2d(&P.tm[TM_V], d_in[2], NH * SEQ, 128, 128);
  tm_2d(&P.tm[TM_SA], sa, SEQ, DM, 128); tm_2d(&P.tm[TM_G], gg, SEQ, DM, 128); tm_2d(&P.tm[TM_WO64], d_in[4], HD, DM, 64);
  tm_3d(&P.tm[TM_WIN], d_in[6], DM, FF); tm_3d(&P.tm[TM_WQ], d_in[3], DM, HD); tm_3d(&P.tm[TM_Z2], z2, SEQ, FH);
  tm_3d(&P.tm[TM_WOUT], d_in[9], FH, DM); tm_3d(&P.tm[TM_WO], d_in[4], HD, DM);
  tm_2d(&P.tm[TS_Q], q, SEQ, HD, ST_ROWS); tm_2d(&P.tm[TS_O], o, SEQ, HD, ST_ROWS); tm_2d(&P.tm[TS_Z2], z2, SEQ, FH, ST_ROWS); tm_2d(&P.tm[TS_U], u, SEQ, FH, ST_ROWS);
  tm_2d(&P.tm[TS_SA], sa, SEQ, DM, ST_ROWS); tm_2d(&P.tm[TS_G], gg, SEQ, DM, ST_ROWS); tm_2d(&P.tm[TS_OUT], d_out, SEQ, DM, 16);
  P.x = (const bf16*)d_in[0]; P.b_sp = (const bf16*)d_in[8];
  fused_kernel<<<2 * NCLUSTER, 384, SMEM_BYTES, cudaStreamPerThread>>>(P);
}
```

```cpp
#include <cuda_runtime.h>
#include <cuda_bf16.h>
#include <cuda.h>
#include <stdint.h>
#include <stdio.h>

typedef __nv_bfloat16 bf16;

constexpr int SEQ = 2048, DM = 1024, NH = 32, HD = 4096, FF = 3584, FH = 1792;

__device__ __align__(1024) bf16 g_xn[SEQ * DM];
__device__ __align__(1024) bf16 g_q[SEQ * HD];
__device__ __align__(1024) bf16 g_o[SEQ * HD];
__device__ __align__(1024) bf16 g_z2[SEQ * FH];
__device__ __align__(1024) bf16 g_u[SEQ * FH];
__device__ __align__(1024) uint2 g_stats[SEQ * 8];
__device__ __align__(1024) bf16 g_g[SEQ * DM];
__device__ __align__(1024) bf16 g_sa[SEQ * DM];
constexpr int F_XN = 0;
constexpr int F_Z2 = 512;
constexpr int F_Q = 768;
constexpr int F_U = 1024;
constexpr int F_O = 1536;
constexpr int F_S = 2048;
constexpr int F_TOTAL = 2112;
__device__ __align__(1024) unsigned g_flags[F_TOTAL];
__device__ unsigned g_done;
__device__ unsigned g_epoch;

__device__ __forceinline__ uint32_t smem_u32(const void* p) { return (uint32_t)__cvta_generic_to_shared(p); }
__device__ __forceinline__ void mbar_init(uint32_t bar, uint32_t cnt) { asm volatile("mbarrier.init.shared::cta.b64 [%0], %1;" :: "r"(bar), "r"(cnt)); }
__device__ __forceinline__ void mbar_expect_tx(uint32_t bar, uint32_t bytes) { asm volatile("mbarrier.arrive.expect_tx.shared::cta.b64 _, [%0], %1;" :: "r"(bar), "r"(bytes) : "memory"); }
__device__ __forceinline__ void mbar_arrive(uint32_t bar) { asm volatile("mbarrier.arrive.shared::cta.b64 _, [%0];" :: "r"(bar) : "memory"); }
__device__ __forceinline__ void mbar_arrive_cta(uint32_t bar, uint32_t cta) {
  asm volatile("{\n.reg .b32 ra;\nmapa.shared::cluster.u32 ra, %0, %1;\nmbarrier.arrive.shared::cluster.b64 _, [ra];\n}" :: "r"(bar), "r"(cta) : "memory");
}
__device__ __forceinline__ bool mbar_test(uint32_t bar, uint32_t parity) {
  uint32_t ok;
  asm volatile("{\n.reg .pred P1;\nmbarrier.test_wait.parity.shared::cta.b64 P1, [%1], %2;\nselp.u32 %0, 1, 0, P1;\n}" : "=r"(ok) : "r"(bar), "r"(parity) : "memory");
  return ok;
}
__device__ __forceinline__ bool mbar_test_a(uint32_t bar, uint32_t parity) {
  uint32_t ok;
  asm volatile("{\n.reg .pred P2;\nmbarrier.test_wait.parity.shared::cta.b64 P2, [%1], %2;\nselp.u32 %0, 1, 0, P2;\n}" : "=r"(ok) : "r"(bar), "r"(parity) : "memory");
  return ok;
}
constexpr uint32_t SPIN_LIMIT = 1u << 22;
__device__ __forceinline__ void trap_if(bool c) { asm volatile("{\n.reg .pred P;\nsetp.ne.u32 P, %0, 0;\n@P trap;\n}" :: "r"((uint32_t)c)); }
__device__ __forceinline__ void mbar_wait(uint32_t bar, uint32_t parity) {
  asm volatile("{\n.reg .pred P1;\n.reg .u32 n;\nmbarrier.try_wait.parity.shared::cta.b64 P1, [%0], %1;\n@P1 bra DONE;\nmov.u32 n, 0;\n"
               "LOOP:\nmbarrier.try_wait.parity.shared::cta.b64 P1, [%0], %1;\n@P1 bra DONE;\nadd.u32 n, n, 1;\nsetp.gt.u32 P1, n, %2;\n@P1 trap;\nbra LOOP;\nDONE:\n}"
               :: "r"(bar), "r"(parity), "n"(SPIN_LIMIT) : "memory");
}
__device__ __forceinline__ void mbar_spin(uint32_t bar, uint32_t parity) {
  asm volatile("{\n.reg .pred P1;\nLOOP:\nmbarrier.try_wait.parity.shared::cta.b64 P1, [%0], %1;\n@!P1 bra LOOP;\n}" :: "r"(bar), "r"(parity) : "memory");
}
__device__ __forceinline__ void mbar_wait_sleep(uint32_t bar, uint32_t parity, uint32_t ns) {
  uint32_t n = 0;
  while (!mbar_test(bar, parity)) { trap_if(++n > SPIN_LIMIT * 4); __nanosleep(ns); }
}
__device__ __forceinline__ void tma_load_2d(uint32_t dst, const CUtensorMap* tm, int c0, int c1, uint32_t bar) {
  asm volatile("cp.async.bulk.tensor.2d.shared::cluster.global.mbarrier::complete_tx::bytes [%0], [%1, {%3, %4}], [%2];"
    :: "r"(dst), "l"(tm), "r"(bar), "r"(c0), "r"(c1) : "memory");
}
__device__ __forceinline__ void tma_load_2d_mc(uint32_t dst, const CUtensorMap* tm, int c0, int c1, uint32_t bar) {
  asm volatile("cp.async.bulk.tensor.2d.shared::cluster.global.mbarrier::complete_tx::bytes.multicast::cluster [%0], [%1, {%3, %4}], [%2], %5;"
    :: "r"(dst), "l"(tm), "r"(bar), "r"(c0), "r"(c1), "h"((uint16_t)3) : "memory");
}
__device__ __forceinline__ void tma_prefetch_2d(const CUtensorMap* tm, int c0, int c1) {
  asm volatile("cp.async.bulk.prefetch.tensor.2d.L2.global [%0, {%1, %2}];" :: "l"(tm), "r"(c0), "r"(c1) : "memory");
}
__device__ __forceinline__ void tma_prefetch_3d(const CUtensorMap* tm, int c1, int c2) {
  asm volatile("cp.async.bulk.prefetch.tensor.3d.L2.global [%0, {%1, %2, %3}];" :: "l"(tm), "r"(0), "r"(c1), "r"(c2) : "memory");
}
__device__ __forceinline__ void tma_load_3d_mc(uint32_t dst, const CUtensorMap* tm, int c1, int c2, uint32_t bar) {
  asm volatile("cp.async.bulk.tensor.3d.shared::cluster.global.mbarrier::complete_tx::bytes.multicast::cluster [%0], [%1, {%3, %4, %5}], [%2], %6;"
    :: "r"(dst), "l"(tm), "r"(bar), "r"(0), "r"(c1), "r"(c2), "h"((uint16_t)3) : "memory");
}
__device__ __forceinline__ void tma_store_2d(const CUtensorMap* tm, uint32_t src, int c0, int c1) {
  asm volatile("cp.async.bulk.tensor.2d.global.shared::cta.bulk_group [%0, {%2, %3}], [%1];" :: "l"(tm), "r"(src), "r"(c0), "r"(c1) : "memory");
}
__device__ __forceinline__ void bulk_commit() { asm volatile("cp.async.bulk.commit_group;" ::: "memory"); }
template <int N> __device__ __forceinline__ void bulk_wait_read() { asm volatile("cp.async.bulk.wait_group.read %0;" :: "n"(N) : "memory"); }
template <int N> __device__ __forceinline__ void bulk_wait() { asm volatile("cp.async.bulk.wait_group %0;" :: "n"(N) : "memory"); }
__device__ __forceinline__ void fence_async_smem() { asm volatile("fence.proxy.async.shared::cta;" ::: "memory"); }
__device__ __forceinline__ void fence_async_global() { asm volatile("fence.proxy.async.global;" ::: "memory"); }
__device__ __forceinline__ void wgmma_fence() { asm volatile("wgmma.fence.sync.aligned;" ::: "memory"); }
__device__ __forceinline__ void wgmma_commit() { asm volatile("wgmma.commit_group.sync.aligned;" ::: "memory"); }
template <int N> __device__ __forceinline__ void wgmma_wait() { asm volatile("wgmma.wait_group.sync.aligned %0;" :: "n"(N) : "memory"); }
__device__ __forceinline__ uint64_t make_desc(uint32_t addr, uint32_t lbo, uint32_t sbo) {
  return (uint64_t)((addr & 0x3FFFF) >> 4) | ((uint64_t)(lbo >> 4) << 16) | ((uint64_t)(sbo >> 4) << 32) | (1ull << 62);
}
template <int N> __device__ __forceinline__ void fence_regs(float (&d)[N]) {
#pragma unroll
  for (int i = 0; i < N; i++) asm volatile("" : "+f"(d[i]) :: "memory");
}
template <int N> __device__ __forceinline__ void fence_regs(uint32_t (&d)[N]) {
#pragma unroll
  for (int i = 0; i < N; i++) asm volatile("" : "+r"(d[i]) :: "memory");
}
__device__ __forceinline__ void named_sync(int id) { asm volatile("bar.sync %0, 256;" :: "r"(id) : "memory"); }
__device__ __forceinline__ void pp_sync(bool w) { asm volatile("{\n.reg .pred p;\nsetp.ne.u32 p, %0, 0;\n@p bar.sync 2, 256;\n@!p bar.sync 1, 256;\n}" :: "r"((uint32_t)w) : "memory"); }
__device__ __forceinline__ void pp_arrive(bool w) { asm volatile("{\n.reg .pred p;\nsetp.ne.u32 p, %0, 0;\n@p bar.arrive 1, 256;\n@!p bar.arrive 2, 256;\n}" :: "r"((uint32_t)w) : "memory"); }
__device__ __forceinline__ bool wg_any(bool w, bool v) {
  uint32_t r;
  asm volatile("{\n.reg .pred p, q;\nsetp.ne.u32 p, %1, 0;\nbar.red.or.pred q, %2, 128, p;\nselp.u32 %0, 1, 0, q;\n}" : "=r"(r) : "r"((uint32_t)v), "r"(w ? 4 : 3) : "memory");
  return __any_sync(0xffffffffu, r);
}
__device__ __forceinline__ int fresh_warp() { uint32_t t; asm volatile("mov.u32 %0, %%tid.x;" : "=r"(t)); return __shfl_sync(0xffffffffu, (int)(t >> 5) - 4, 0); }
__device__ __forceinline__ void cluster_sync_relaxed() { asm volatile("barrier.cluster.arrive.relaxed.aligned;\nbarrier.cluster.wait.aligned;" ::: "memory"); }
__device__ __forceinline__ unsigned ld_acquire(const unsigned* p) { unsigned v; asm volatile("ld.acquire.gpu.global.u32 %0, [%1];" : "=r"(v) : "l"(p) : "memory"); return v; }
__device__ __forceinline__ void red_release(unsigned* p, unsigned v) { asm volatile("red.release.gpu.global.add.u32 [%0], %1;" :: "l"(p), "r"(v) : "memory"); }
__device__ __forceinline__ void flag_wait(const unsigned* p, unsigned target) {
  uint32_t n = 0;
  while (ld_acquire(p) < target) { trap_if(++n > SPIN_LIMIT); __nanosleep(20); }
}
__device__ __forceinline__ void st_tagged(uint2* p, float a, float b, uint32_t tag) {
  asm volatile("{\n.reg .b64 x;\nmov.b64 x, {%1, %2};\nst.relaxed.gpu.global.b64 [%0], x;\n}" :: "l"(p),
               "r"((__float_as_uint(a) & ~63u) | (tag & 63u)), "r"((__float_as_uint(b) & ~63u) | (tag >> 6)) : "memory");
}
__device__ __forceinline__ uint4 ld_tagged2(const uint2* p) {
  uint4 v;
  asm volatile("{\n.reg .b64 x, y;\nld.relaxed.gpu.global.v2.b64 {x, y}, [%4];\nmov.b64 {%0, %1}, x;\nmov.b64 {%2, %3}, y;\n}" : "=r"(v.x), "=r"(v.y), "=r"(v.z), "=r"(v.w) : "l"(p) : "memory");
  return v;
}
__device__ __forceinline__ bool tag_ok(uint32_t a, uint32_t b, uint32_t tag) { return ((a & 63u) | ((b & 63u) << 6)) == tag; }
__device__ __forceinline__ float untag(uint32_t v) { return __uint_as_float(v & ~63u); }
__device__ __forceinline__ uint32_t pack_bf16(float lo, float hi) { uint32_t r; asm("cvt.rn.bf16x2.f32 %0, %1, %2;" : "=r"(r) : "f"(hi), "f"(lo)); return r; }
__device__ __forceinline__ uint32_t bf2_fma(uint32_t a, uint32_t b, uint32_t c) { uint32_t r; asm("fma.rn.bf16x2 %0, %1, %2, %3;" : "=r"(r) : "r"(a), "r"(b), "r"(c)); return r; }
__device__ __forceinline__ uint32_t bf2_mul(uint32_t a, uint32_t b) { uint32_t r; asm("mul.rn.bf16x2 %0, %1, %2;" : "=r"(r) : "r"(a), "r"(b)); return r; }
__device__ __forceinline__ uint32_t bf2_add(uint32_t a, uint32_t b) { uint32_t r; asm("add.rn.bf16x2 %0, %1, %2;" : "=r"(r) : "r"(a), "r"(b)); return r; }
constexpr uint32_t BF2_HALF = 0x3f003f00u;
__device__ __forceinline__ float bf_lo(uint32_t v) { return __uint_as_float(v << 16); }
__device__ __forceinline__ float bf_hi(uint32_t v) { return __uint_as_float(v & 0xffff0000u); }
__device__ __forceinline__ float ex2(float x) { float y; asm("ex2.approx.ftz.f32 %0, %1;" : "=f"(y) : "f"(x)); return y; }
__device__ __forceinline__ float tanh_fast(float x) { float y; asm("tanh.approx.f32 %0, %1;" : "=f"(y) : "f"(x)); return y; }
__device__ __forceinline__ void stmatrix_x4(uint32_t addr, uint32_t a, uint32_t b, uint32_t c, uint32_t d) {
  asm volatile("stmatrix.sync.aligned.m8n8.x4.shared.b16 [%0], {%1, %2, %3, %4};" :: "r"(addr), "r"(a), "r"(b), "r"(c), "r"(d) : "memory");
}
__device__ __forceinline__ void ldmatrix_x4(uint32_t addr, uint32_t& a, uint32_t& b, uint32_t& c, uint32_t& d) {
  asm volatile("ldmatrix.sync.aligned.m8n8.x4.shared.b16 {%0, %1, %2, %3}, [%4];" : "=r"(a), "=r"(b), "=r"(c), "=r"(d) : "r"(addr) : "memory");
}
__device__ __forceinline__ uint32_t lane_id() { uint32_t l; asm volatile("mov.u32 %0, %%laneid;" : "=r"(l)); return l; }
__device__ __forceinline__ bool elect_one() {
  uint32_t r;
  asm volatile("{\n.reg .pred P;\nelect.sync _|P, 0xffffffff;\nselp.u32 %0, 1, 0, P;\n}" : "=r"(r));
  return r;
}

__device__ __forceinline__ void wgmma_m64n128k16_ss_tb0(float (&d)[64], uint64_t da, uint64_t db, int scale_d) {
  asm volatile("{\n.reg .pred p;\nsetp.ne.b32 p, %66, 0;\n"
    "wgmma.mma_async.sync.aligned.m64n128k16.f32.bf16.bf16 "
    "{%0, %1, %2, %3, %4, %5, %6, %7, %8, %9, %10, %11, %12, %13, %14, %15, %16, %17, %18, %19, %20, %21, %22, %23, %24, %25, %26, %27, %28, %29, %30, %31, %32, %33, %34, %35, %36, %37, %38, %39, %40, %41, %42, %43, %44, %45, %46, %47, %48, %49, %50, %51, %52, %53, %54, %55, %56, %57, %58, %59, %60, %61, %62, %63}, "
    "%64, %65, p, 1, 1, 0, 0;\n}\n"
    : "+f"(d[0]), "+f"(d[1]), "+f"(d[2]), "+f"(d[3]), "+f"(d[4]), "+f"(d[5]), "+f"(d[6]), "+f"(d[7]), "+f"(d[8]), "+f"(d[9]), "+f"(d[10]), "+f"(d[11]), "+f"(d[12]), "+f"(d[13]), "+f"(d[14]), "+f"(d[15]), "+f"(d[16]), "+f"(d[17]), "+f"(d[18]), "+f"(d[19]), "+f"(d[20]), "+f"(d[21]), "+f"(d[22]), "+f"(d[23]), "+f"(d[24]), "+f"(d[25]), "+f"(d[26]), "+f"(d[27]), "+f"(d[28]), "+f"(d[29]), "+f"(d[30]), "+f"(d[31]), "+f"(d[32]), "+f"(d[33]), "+f"(d[34]), "+f"(d[35]), "+f"(d[36]), "+f"(d[37]), "+f"(d[38]), "+f"(d[39]), "+f"(d[40]), "+f"(d[41]), "+f"(d[42]), "+f"(d[43]), "+f"(d[44]), "+f"(d[45]), "+f"(d[46]), "+f"(d[47]), "+f"(d[48]), "+f"(d[49]), "+f"(d[50]), "+f"(d[51]), "+f"(d[52]), "+f"(d[53]), "+f"(d[54]), "+f"(d[55]), "+f"(d[56]), "+f"(d[57]), "+f"(d[58]), "+f"(d[59]), "+f"(d[60]), "+f"(d[61]), "+f"(d[62]), "+f"(d[63])
    : "l"(da), "l"(db), "r"(scale_d));
}
__device__ __forceinline__ void wgmma_m64n256k16_ss_tb1(float (&d)[128], uint64_t da, uint64_t db, int scale_d) {
  asm volatile("{\n.reg .pred p;\nsetp.ne.b32 p, %130, 0;\n"
    "wgmma.mma_async.sync.aligned.m64n256k16.f32.bf16.bf16 "
    "{%0, %1, %2, %3, %4, %5, %6, %7, %8, %9, %10, %11, %12, %13, %14, %15, %16, %17, %18, %19, %20, %21, %22, %23, %24, %25, %26, %27, %28, %29, %30, %31, %32, %33, %34, %35, %36, %37, %38, %39, %40, %41, %42, %43, %44, %45, %46, %47, %48, %49, %50, %51, %52, %53, %54, %55, %56, %57, %58, %59, %60, %61, %62, %63, %64, %65, %66, %67, %68, %69, %70, %71, %72, %73, %74, %75, %76, %77, %78, %79, %80, %81, %82, %83, %84, %85, %86, %87, %88, %89, %90, %91, %92, %93, %94, %95, %96, %97, %98, %99, %100, %101, %102, %103, %104, %105, %106, %107, %108, %109, %110, %111, %112, %113, %114, %115, %116, %117, %118, %119, %120, %121, %122, %123, %124, %125, %126, %127}, "
    "%128, %129, p, 1, 1, 0, 1;\n}\n"
    : "+f"(d[0]), "+f"(d[1]), "+f"(d[2]), "+f"(d[3]), "+f"(d[4]), "+f"(d[5]), "+f"(d[6]), "+f"(d[7]), "+f"(d[8]), "+f"(d[9]), "+f"(d[10]), "+f"(d[11]), "+f"(d[12]), "+f"(d[13]), "+f"(d[14]), "+f"(d[15]), "+f"(d[16]), "+f"(d[17]), "+f"(d[18]), "+f"(d[19]), "+f"(d[20]), "+f"(d[21]), "+f"(d[22]), "+f"(d[23]), "+f"(d[24]), "+f"(d[25]), "+f"(d[26]), "+f"(d[27]), "+f"(d[28]), "+f"(d[29]), "+f"(d[30]), "+f"(d[31]), "+f"(d[32]), "+f"(d[33]), "+f"(d[34]), "+f"(d[35]), "+f"(d[36]), "+f"(d[37]), "+f"(d[38]), "+f"(d[39]), "+f"(d[40]), "+f"(d[41]), "+f"(d[42]), "+f"(d[43]), "+f"(d[44]), "+f"(d[45]), "+f"(d[46]), "+f"(d[47]), "+f"(d[48]), "+f"(d[49]), "+f"(d[50]), "+f"(d[51]), "+f"(d[52]), "+f"(d[53]), "+f"(d[54]), "+f"(d[55]), "+f"(d[56]), "+f"(d[57]), "+f"(d[58]), "+f"(d[59]), "+f"(d[60]), "+f"(d[61]), "+f"(d[62]), "+f"(d[63]), "+f"(d[64]), "+f"(d[65]), "+f"(d[66]), "+f"(d[67]), "+f"(d[68]), "+f"(d[69]), "+f"(d[70]), "+f"(d[71]), "+f"(d[72]), "+f"(d[73]), "+f"(d[74]), "+f"(d[75]), "+f"(d[76]), "+f"(d[77]), "+f"(d[78]), "+f"(d[79]), "+f"(d[80]), "+f"(d[81]), "+f"(d[82]), "+f"(d[83]), "+f"(d[84]), "+f"(d[85]), "+f"(d[86]), "+f"(d[87]), "+f"(d[88]), "+f"(d[89]), "+f"(d[90]), "+f"(d[91]), "+f"(d[92]), "+f"(d[93]), "+f"(d[94]), "+f"(d[95]), "+f"(d[96]), "+f"(d[97]), "+f"(d[98]), "+f"(d[99]), "+f"(d[100]), "+f"(d[101]), "+f"(d[102]), "+f"(d[103]), "+f"(d[104]), "+f"(d[105]), "+f"(d[106]), "+f"(d[107]), "+f"(d[108]), "+f"(d[109]), "+f"(d[110]), "+f"(d[111]), "+f"(d[112]), "+f"(d[113]), "+f"(d[114]), "+f"(d[115]), "+f"(d[116]), "+f"(d[117]), "+f"(d[118]), "+f"(d[119]), "+f"(d[120]), "+f"(d[121]), "+f"(d[122]), "+f"(d[123]), "+f"(d[124]), "+f"(d[125]), "+f"(d[126]), "+f"(d[127])
    : "l"(da), "l"(db), "r"(scale_d));
}
__device__ __forceinline__ void wgmma_m64n128k16_rs_tb1(float (&d)[64], uint32_t a0, uint32_t a1, uint32_t a2, uint32_t a3, uint64_t db, int scale_d) {
  asm volatile("{\n.reg .pred p;\nsetp.ne.b32 p, %69, 0;\n"
    "wgmma.mma_async.sync.aligned.m64n128k16.f32.bf16.bf16 "
    "{%0, %1, %2, %3, %4, %5, %6, %7, %8, %9, %10, %11, %12, %13, %14, %15, %16, %17, %18, %19, %20, %21, %22, %23, %24, %25, %26, %27, %28, %29, %30, %31, %32, %33, %34, %35, %36, %37, %38, %39, %40, %41, %42, %43, %44, %45, %46, %47, %48, %49, %50, %51, %52, %53, %54, %55, %56, %57, %58, %59, %60, %61, %62, %63}, "
    "{%64, %65, %66, %67}, %68, p, 1, 1, 1;\n}\n"
    : "+f"(d[0]), "+f"(d[1]), "+f"(d[2]), "+f"(d[3]), "+f"(d[4]), "+f"(d[5]), "+f"(d[6]), "+f"(d[7]), "+f"(d[8]), "+f"(d[9]), "+f"(d[10]), "+f"(d[11]), "+f"(d[12]), "+f"(d[13]), "+f"(d[14]), "+f"(d[15]), "+f"(d[16]), "+f"(d[17]), "+f"(d[18]), "+f"(d[19]), "+f"(d[20]), "+f"(d[21]), "+f"(d[22]), "+f"(d[23]), "+f"(d[24]), "+f"(d[25]), "+f"(d[26]), "+f"(d[27]), "+f"(d[28]), "+f"(d[29]), "+f"(d[30]), "+f"(d[31]), "+f"(d[32]), "+f"(d[33]), "+f"(d[34]), "+f"(d[35]), "+f"(d[36]), "+f"(d[37]), "+f"(d[38]), "+f"(d[39]), "+f"(d[40]), "+f"(d[41]), "+f"(d[42]), "+f"(d[43]), "+f"(d[44]), "+f"(d[45]), "+f"(d[46]), "+f"(d[47]), "+f"(d[48]), "+f"(d[49]), "+f"(d[50]), "+f"(d[51]), "+f"(d[52]), "+f"(d[53]), "+f"(d[54]), "+f"(d[55]), "+f"(d[56]), "+f"(d[57]), "+f"(d[58]), "+f"(d[59]), "+f"(d[60]), "+f"(d[61]), "+f"(d[62]), "+f"(d[63])
    : "r"(a0), "r"(a1), "r"(a2), "r"(a3), "l"(db), "r"(scale_d));
}
__device__ __forceinline__ void wgmma_m64n128k16_ss_tb1(float (&d)[64], uint64_t da, uint64_t db, int scale_d) {
  asm volatile("{\n.reg .pred p;\nsetp.ne.b32 p, %66, 0;\n"
    "wgmma.mma_async.sync.aligned.m64n128k16.f32.bf16.bf16 "
    "{%0, %1, %2, %3, %4, %5, %6, %7, %8, %9, %10, %11, %12, %13, %14, %15, %16, %17, %18, %19, %20, %21, %22, %23, %24, %25, %26, %27, %28, %29, %30, %31, %32, %33, %34, %35, %36, %37, %38, %39, %40, %41, %42, %43, %44, %45, %46, %47, %48, %49, %50, %51, %52, %53, %54, %55, %56, %57, %58, %59, %60, %61, %62, %63}, "
    "%64, %65, p, 1, 1, 0, 1;\n}\n"
    : "+f"(d[0]), "+f"(d[1]), "+f"(d[2]), "+f"(d[3]), "+f"(d[4]), "+f"(d[5]), "+f"(d[6]), "+f"(d[7]), "+f"(d[8]), "+f"(d[9]), "+f"(d[10]), "+f"(d[11]), "+f"(d[12]), "+f"(d[13]), "+f"(d[14]), "+f"(d[15]), "+f"(d[16]), "+f"(d[17]), "+f"(d[18]), "+f"(d[19]), "+f"(d[20]), "+f"(d[21]), "+f"(d[22]), "+f"(d[23]), "+f"(d[24]), "+f"(d[25]), "+f"(d[26]), "+f"(d[27]), "+f"(d[28]), "+f"(d[29]), "+f"(d[30]), "+f"(d[31]), "+f"(d[32]), "+f"(d[33]), "+f"(d[34]), "+f"(d[35]), "+f"(d[36]), "+f"(d[37]), "+f"(d[38]), "+f"(d[39]), "+f"(d[40]), "+f"(d[41]), "+f"(d[42]), "+f"(d[43]), "+f"(d[44]), "+f"(d[45]), "+f"(d[46]), "+f"(d[47]), "+f"(d[48]), "+f"(d[49]), "+f"(d[50]), "+f"(d[51]), "+f"(d[52]), "+f"(d[53]), "+f"(d[54]), "+f"(d[55]), "+f"(d[56]), "+f"(d[57]), "+f"(d[58]), "+f"(d[59]), "+f"(d[60]), "+f"(d[61]), "+f"(d[62]), "+f"(d[63])
    : "l"(da), "l"(db), "r"(scale_d));
}


enum { TM_XN, TM_WSP, TM_U, TM_O, TM_Q, TM_X, TM_SA, TM_G, TM_K, TM_V, TM_WO64,
       TM_WIN, TM_WQ, TM_Z2, TM_WOUT, TM_WO, TS_Q, TS_O, TS_Z2, TS_U, TS_SA, TS_G, TS_OUT, TM_COUNT };
enum { T_Z2 = 0, T_Q = 1, T_U = 2, T_ATT = 3, T_SA = 4, T_FIN = 5, T_END = 7 };
constexpr int NCLUSTER = 66, MAXI = 14;
struct alignas(64) Params {
  const bf16* x;
  const bf16* b_sp;
  CUtensorMap tm[TM_COUNT];
  uint16_t items[NCLUSTER][MAXI];
};

constexpr uint32_t G_STAGE = 49152, G_A = 16384, KV_SLOT = 32768;
constexpr uint32_t OFF_Q1 = 163840, OFF_Q0 = 196608, OFF_BAR = 229376, OFF_LN = OFF_BAR + 256, SMEM_BYTES = OFF_LN + 1024;
constexpr uint32_t B_GF = 0, B_GE = 32, B_KF = 64, B_KE = 104, B_QF = 144, B_QE = 160, B_XF = 176, B_XR = 184, B_STG = 192, B_FREE = 200;
constexpr uint32_t B_GO = 208, B_LN = 216, B_PUB = 248, B_TAG = 224, B_RDY = 228, B_PROG = 232;
constexpr int SA_HEADS = 18;
constexpr int SW_NS = 40;
constexpr int SW_ATT = 800;
constexpr int ST_ROWS = 16;
constexpr int ST_FLY = 2;
constexpr int KV_PF = 4;
constexpr int FIN_PREP = 8;
constexpr int OWN_OFF = 8;
constexpr int ACT_REP = 33;
constexpr int Q_DELAY = 4;
constexpr int Q_GAP = 4;
constexpr int QW = 2;
constexpr int Z_DELAY = 4;
constexpr int Z_GAP = 3;
constexpr int LN_SLEEP = 300;
constexpr int U_PACE = 200;
constexpr int Q_AT = 19;
constexpr int OUT_PF = 8;
constexpr int SA_STEPS = 2 * SA_HEADS;
static_assert(ST_ROWS == 16, "the per-warp stores of the last o tile use the same tensor map");
static_assert(SA_STEPS >= 36, "activation, gate store and hold-back have to fit into the second SA segment");
constexpr uint32_t FIN_SLOT0 = (0x0320u >> (4 * ((29 + SA_STEPS) & 3))) & 15;
constexpr float SM_C = 0.08838834764831845f * 1.4426950408889634f;
constexpr float GELU_A = 0.7978845608028654f, GELU_B = 0.7978845608028654f * 0.044715f;
constexpr float SM_LO = 1e-7f, SM_HI = 1e12f;
constexpr float SM_THR = 1024.f;


extern __shared__ __align__(1024) uint8_t smem_raw[];
__device__ __forceinline__ uint32_t smem_base() { return smem_u32(smem_raw); }

struct Ring { uint32_t s, ph; };
template <int N> __device__ __forceinline__ void ring_adv(Ring& r) { if (++r.s == N) { r.s = 0; r.ph ^= 1; } }

__device__ __forceinline__ int get_item(const Params& p, int i) {
  uint32_t b; asm volatile("mov.u32 %0, %%ctaid.x;" : "=r"(b));
  return p.items[b >> 1][i];
}
struct Cons {
  uint32_t sb;
  int warp;
  Ring g;
  uint32_t rot;
  uint32_t fph;
};

__device__ __forceinline__ void stage_acquire(const Cons& c) { mbar_spin(c.sb + OFF_BAR + B_FREE, c.fph); }
__device__ __forceinline__ void stage_commit(Cons& c) {
  __syncwarp();
  if (lane_id() == 0) mbar_arrive(c.sb + OFF_BAR + B_STG);
  c.fph ^= 1;
}

__device__ __forceinline__ void release_slot(const Cons& c, uint32_t bar) {
  if (lane_id() == 0 && (c.warp & 3) < 2) mbar_arrive_cta(bar, c.warp & 1);
}
constexpr uint64_t DESC_HI = (uint64_t)0x40000040u << 32;

template <bool FIRST> __device__ __forceinline__ void gemm_step(float (&acc)[128], Cons& c) {
  mbar_spin(c.sb + OFF_BAR + B_GF + 8 * c.g.s, c.g.ph);
  const uint32_t st = ((c.sb & 0x3FFFF) >> 4) + ((c.g.s + c.rot) & 3) * (G_STAGE >> 4);
  const uint32_t da = st + (c.warp >> 2) * 512 + (1u << 16), db = st + (G_A >> 4) + ((8192u >> 4) << 16);
  wgmma_fence();
#pragma unroll
  for (int kk = 0; kk < 4; kk++) wgmma_m64n256k16_ss_tb1(acc, DESC_HI | (da + kk * 2), DESC_HI | (db + kk * 128), !(FIRST && kk == 0));
  wgmma_commit();
}

template <int N> __device__ __forceinline__ void stage_chunks(uint32_t buf, uint32_t stride, const uint32_t* pk) {
  const uint32_t ln = lane_id();
  const uint32_t a = buf + ((ln & 15) << 7);
  const uint32_t x = ln & 7, hi = ln >> 4;
#pragma unroll
  for (int i = 0; i < 4 * N; i++) stmatrix_x4(a + (i >> 2) * stride + (((2 * (i & 3) + hi) ^ x) << 4), pk[4 * i], pk[4 * i + 1], pk[4 * i + 2], pk[4 * i + 3]);
}

__device__ __forceinline__ float act2_fn(float x, float a, float b) {
  return fmaf(x, tanh_fast(x * fmaf(x * x, b, a)), x);
}
__device__ __forceinline__ float quad_sum(float v) { v += __shfl_xor_sync(0xffffffffu, v, 1); v += __shfl_xor_sync(0xffffffffu, v, 2); return v; }
__device__ __forceinline__ float quad_max(float v) { v = fmaxf(v, __shfl_xor_sync(0xffffffffu, v, 1)); v = fmaxf(v, __shfl_xor_sync(0xffffffffu, v, 2)); return v; }

__device__ __forceinline__ uint32_t load_tag(const Cons& c) { uint32_t t; asm volatile("ld.volatile.shared.u32 %0, [%1];" : "=r"(t) : "r"(c.sb + OFF_BAR + B_TAG)); return t; }

struct Shadow {
  int act;
  int store;
};
__device__ __forceinline__ void rotate16(uint32_t (&h)[64]) {
#pragma unroll
  for (int i = 0; i < 16; i++)
    asm volatile("{\n.reg .b32 t;\nmov.b32 t, %0;\nmov.b32 %0, %1;\nmov.b32 %1, %2;\nmov.b32 %2, %3;\nmov.b32 %3, t;\n}" : "+r"(h[i]), "+r"(h[i + 16]), "+r"(h[i + 32]), "+r"(h[i + 48]));
}

template <int O>
__device__ __forceinline__ void act_block(uint32_t (&held)[64], float ca, float cb, bool first, float& u0, float& u1, float& s0, float& s1, float& q0, float& q1) {
#pragma unroll
  for (int i = O; i < O + 4; i += 2) {
    const float a0 = act2_fn(bf_lo(held[i]), ca, cb), a1 = act2_fn(bf_hi(held[i]), ca, cb);
    const float b0 = act2_fn(bf_lo(held[i + 1]), ca, cb), b1 = act2_fn(bf_hi(held[i + 1]), ca, cb);
    if (i == 0 && first) { u0 = a0; u1 = b0; }
    float d;
    d = a0 - u0; s0 += d; q0 = fmaf(d, d, q0); d = a1 - u0; s0 += d; q0 = fmaf(d, d, q0);
    d = b0 - u1; s1 += d; q1 = fmaf(d, d, q1); d = b1 - u1; s1 += d; q1 = fmaf(d, d, q1);
    held[i] = pack_bf16(a0, a1); held[i + 1] = pack_bf16(b0, b1);
  }
}

template <int O> __device__ __forceinline__ void stage_half(Cons& c, uint32_t (&held)[64], int mode) {
  if (mode == 2) {
    uint32_t a0, a1, r0, r1;
    const uint32_t la = c.sb + OFF_LN + (c.warp * 16 + (lane_id() >> 2)) * 8;
    mbar_spin(c.sb + OFF_BAR + B_LN, 0);
    asm volatile("ld.shared.v2.b32 {%0, %1}, [%2];" : "=r"(r0), "=r"(a0) : "r"(la));
    asm volatile("ld.shared.v2.b32 {%0, %1}, [%2];" : "=r"(r1), "=r"(a1) : "r"(la + 64));
#pragma unroll
    for (int i = O; i < O + 32; i += 2) { held[i] = bf2_mul(bf2_add(held[i], a0), r0); held[i + 1] = bf2_mul(bf2_add(held[i + 1], a1), r1); }
  }
  if (O == 0 && mode == 3) {
#pragma unroll
    for (int i = 0; i < 64; i++) held[i] = bf2_mul(held[i], BF2_HALF);
  }
  stage_acquire(c);
  stage_chunks<2>(c.sb + OFF_Q0 + c.warp * 2048, 16384, held + O);
  stage_commit(c);
}

__device__ __forceinline__ void gemm_seg(float (&acc)[128], uint32_t (&held)[64], Cons& c, const Params& p, Shadow& sh, int nsteps) {
  const bool elected = lane_id() == 0 && (c.warp & 3) < 2;
  uint32_t rel;
  asm("mapa.shared::cluster.u32 %0, %1, %2;" : "=r"(rel) : "r"(c.sb + OFF_BAR + B_GE), "r"((uint32_t)(c.warp & 1)));
  gemm_step<true>(acc, c);
  uint32_t prev = c.g.s;
  ring_adv<4>(c.g);
  int k = 1;
#define G_STEP()                                                                                                       \
  { gemm_step<false>(acc, c);                                                                                          \
    wgmma_wait<1>();                                                                                                   \
    if (elected) asm volatile("mbarrier.arrive.shared::cluster.b64 _, [%0];" :: "r"(rel + 8 * prev) : "memory");       \
    prev = c.g.s; ring_adv<4>(c.g);                                                                                    \
    k++; }
  if (sh.act != 0) {
    float u0 = 0.f, u1 = 0.f, s0 = 0.f, s1 = 0.f, q0 = 0.f, q1 = 0.f;
    const float ca = sh.act == 3 ? 0.5f : GELU_A, cb = sh.act == 3 ? 0.f : GELU_B;
    const int rb = nsteps >= ACT_REP ? 2 : 1, ra = sh.act == 2 ? 0 : rb;
#define G_STEPS(N) { _Pragma("unroll 1") for (int r = 0; r < (N); r++) G_STEP() }
#pragma unroll 1
    for (int q = 0;; q++) {
      act_block<0>(held, ca, cb, q == 0, u0, u1, s0, s1, q0, q1);
      G_STEPS(ra)
      act_block<4>(held, ca, cb, false, u0, u1, s0, s1, q0, q1);
      G_STEPS(rb)
      act_block<8>(held, ca, cb, false, u0, u1, s0, s1, q0, q1);
      G_STEPS(ra)
      act_block<12>(held, ca, cb, false, u0, u1, s0, s1, q0, q1);
      rotate16(held);
      if (q == 3) break;
      G_STEPS(rb)
    }
    if (sh.act == 2) {
      const int zi = get_item(p, 0);
      const int ln = lane_id(), row0 = (((zi >> 5) & 31) * 2 + (blockIdx.x & 1)) * 128 + c.warp * 16 + (ln >> 2), ql = ln & 3;
      const float m0 = fmaf(s0, 1.f / 64, u0), m1 = fmaf(s1, 1.f / 64, u1);
      q0 -= s0 * s0 * (1.f / 64); q1 -= s1 * s1 * (1.f / 64);
      const float mu0 = quad_sum(m0) * 0.25f, mu1 = quad_sum(m1) * 0.25f;
      q0 = quad_sum(fmaf(64.f * (m0 - mu0), m0 - mu0, q0)); q1 = quad_sum(fmaf(64.f * (m1 - mu1), m1 - mu1, q1));
      if (ql < 2) st_tagged(&g_stats[((row0 >> 7) * 8 + (zi & 31)) * 128 + (row0 & 127) + 8 * ql], ql ? mu1 : mu0, ql ? q1 : q0, load_tag(c));
      if (ln == 0) mbar_arrive(c.sb + OFF_BAR + B_PUB);
    }
  }
  const int s0 = sh.store == 0 ? -9 : k + (sh.store == 2 ? Z_DELAY : (sh.store == 1 ? Q_DELAY : 1)), s1 = sh.store == 3 ? -9 : s0 + (sh.store == 1 ? Q_GAP : Z_GAP);
#pragma unroll 1
  while (k < nsteps) {
    G_STEP()
    if (k == s0) stage_half<0>(c, held, sh.store);
    else if (k == s1) stage_half<32>(c, held, sh.store);
    if (k == nsteps - 2 && c.warp >= 4) named_sync(6);
  }
  if (c.warp < 4) asm volatile("bar.arrive 6, 256;" ::: "memory");
  wgmma_wait<0>();
  fence_regs(acc);
  if (elected) asm volatile("mbarrier.arrive.shared::cluster.b64 _, [%0];" :: "r"(rel + 8 * prev) : "memory");
  sh.store = sh.act = 0;
}

template <bool SUB> __device__ __forceinline__ void softmax_exp(const float (&S)[64], uint32_t (&P)[32], float m0, float m1, float& s0, float& s1) {
  float a0 = 0.f, a1 = 0.f, b0 = 0.f, b1 = 0.f;
#pragma unroll
  for (int j = 0; j < 16; j++) {
    const float p0 = ex2(SUB ? S[4 * j] - m0 : S[4 * j]), p1 = ex2(SUB ? S[4 * j + 1] - m0 : S[4 * j + 1]);
    const float p2 = ex2(SUB ? S[4 * j + 2] - m1 : S[4 * j + 2]), p3 = ex2(SUB ? S[4 * j + 3] - m1 : S[4 * j + 3]);
    a0 += p0; b0 += p1; a1 += p2; b1 += p3;
    P[2 * j] = pack_bf16(p0, p1); P[2 * j + 1] = pack_bf16(p2, p3);
  }
  s0 = a0 + b0; s1 = a1 + b1;
}
__device__ __forceinline__ void row_max(const float (&S)[64], float& x0, float& x1) {
  float a0 = fmaxf(S[0], S[1]), a1 = fmaxf(S[2], S[3]);
#pragma unroll
  for (int j = 1; j < 16; j++) { a0 = fmaxf(a0, fmaxf(S[4 * j], S[4 * j + 1])); a1 = fmaxf(a1, fmaxf(S[4 * j + 2], S[4 * j + 3])); }
  x0 = quad_max(a0); x1 = quad_max(a1);
}

__device__ __forceinline__ void issue_qk(float (&S)[64], uint32_t da, uint32_t db) {
#pragma unroll
  for (int kk = 0; kk < 8; kk++) {
    const uint32_t o = (kk >> 2) * 1024 + (kk & 3) * 2;
    wgmma_m64n128k16_ss_tb0(S, DESC_HI | (da + o), DESC_HI | (db + o), kk > 0);
  }
}
__device__ __forceinline__ void issue_pv(float (&O)[64], const uint32_t (&P)[32], uint32_t db, int acc) {
#pragma unroll
  for (int kk = 0; kk < 8; kk++) wgmma_m64n128k16_rs_tb1(O, P[4 * kk], P[4 * kk + 1], P[4 * kk + 2], P[4 * kk + 3], DESC_HI | (db + kk * 128), (acc || kk > 0));
}

__device__ __forceinline__ void att_pack(const float (&O)[64], uint32_t (&pk)[32], float i0, float i1) {
#pragma unroll
  for (int j = 0; j < 16; j++) {
    pk[2 * j] = pack_bf16(O[4 * j] * i0, O[4 * j + 1] * i0);
    pk[2 * j + 1] = pack_bf16(O[4 * j + 2] * i1, O[4 * j + 3] * i1);
  }
}
__device__ __forceinline__ void att_stage(Cons& c, const uint32_t (&pk)[32], uint32_t qbuf) {
  stage_chunks<2>(c.sb + (qbuf ? OFF_Q1 : OFF_Q0) + c.warp * 2048, 16384, pk);
  stage_commit(c);
}

#define ATT_ISSUE(PIN, ACC, PV)                                                                                        \
  wgmma_fence();                                                                                                       \
  issue_qk(S, qd, kd); wgmma_commit();                                                                                 \
  if (g > 1) release_slot(c, vrel);                                                                                    \
  vready = mbar_test(vbar, vph) && g >= 3 && g != 16;                                                                  \
  if (PV) {                                                                                                            \
    mbar_spin(vbar, vph);                                                                                              \
    wgmma_fence();                                                                                                     \
    issue_pv(O, PIN, vd, ACC); wgmma_commit();                                                                         \
  } else {                                                                                                             \
    asm volatile("wgmma.commit_group.sync.aligned; // empty" ::: "memory");                                            \
  }                                                                                                                    \
  krel = kbar + (B_KE - B_KF); vrel = vbar + (B_KE - B_KF);                                                            \
  g++;                                                                                                                 \
  if (g < total) { kd = kd0 + kv.s * (KV_SLOT >> 4); kbar = bars + B_KF + 8 * kv.s; kph = kv.ph; ring_adv<5>(kv); }    \
  vd = vd0 + kv.s * (KV_SLOT >> 4); vbar = bars + B_KF + 8 * kv.s; vph = kv.ph; ring_adv<5>(kv);

#define ATT_WAIT_S()                                                                                                   \
  wgmma_wait<1>();                                                                                                     \
  fence_regs(S);                                                                                                       \
  release_slot(c, krel);                                                                                               \
  if (c.warp == 2) asm volatile("st.volatile.shared.u32 [%0], %1;" :: "r"(bars + B_PROG), "r"(g) : "memory");

#define ATT_SOFTMAX(POUT, FIRST)                                                                                       \
  fresh = false;                                                                                                       \
  _Pragma("unroll 1")                                                                                                  \
  while (true) {                                                                                                       \
    if (__builtin_expect(fresh, 0)) {                                                                                  \
      float x0, x1;                                                                                                    \
      row_max(S, x0, x1);                                                                                              \
      if (FIRST) m0 = m1 = -1e38f;                                                                                     \
      x0 = fmaxf(x0, m0); x1 = fmaxf(x1, m1);                                                                          \
      f0 = ex2(m0 - x0); f1 = ex2(m1 - x1);                                                                            \
      m0 = x0; m1 = x1; l0 *= f0; l1 *= f1;                                                                            \
      zero = false;                                                                                                    \
    }                                                                                                                  \
    if (zero) {                                                                                                        \
      softmax_exp<false>(S, POUT, m0, m1, s0, s1);                                                                     \
      kready = mbar_test_a(kbar, kph);                                                                                 \
      bad = !(s0 <= SM_HI && s1 <= SM_HI) || ((FIRST) && (s0 < SM_LO || s1 < SM_LO));                                  \
    } else {                                                                                                           \
      softmax_exp<true>(S, POUT, m0, m1, s0, s1);                                                                      \
      kready = mbar_test(kbar, kph);                                                                                   \
      bad = !(s0 <= SM_THR && s1 <= SM_THR);                                                                           \
    }                                                                                                                  \
    kready = kready && vready;                                                                                         \
    slow = fresh || __any_sync(0xffffffffu, bad || !kready);                                                           \
    if (__builtin_expect(!slow, 1)) break;                                                                             \
    if (fresh || !__any_sync(0xffffffffu, bad)) break;                                                                 \
    fresh = true;                                                                                                      \
  }                                                                                                                    \
  l0 += s0; l1 += s1;                                                                                                  \
  wgmma_wait<0>(); fence_regs(O);

#define ATT_RESCALE()                                                                                                  \
  { _Pragma("unroll")                                                                                                  \
    for (int i = 0; i < 16; i++) { O[4 * i] *= f0; O[4 * i + 1] *= f0; O[4 * i + 2] *= f1; O[4 * i + 3] *= f1; } }

__device__ __forceinline__ void att_stagger(const Cons& c, int g) {
  if (c.warp >= 4)
    asm volatile("{\n.reg .pred p;\n.reg .s32 v;\nLOOP:\nld.volatile.shared.s32 v, [%0];\nsetp.le.s32 p, v, %1;\n@p bra LOOP;\n}" :: "r"(c.sb + OFF_BAR + B_PROG), "r"(g) : "memory");
}

__device__ __forceinline__ void att_run(Cons& c, const Params& p, int it, int n) {
  const uint32_t bars = c.sb + OFF_BAR;
  float S[64], O[64];
  uint32_t P0[32], P1[32];
#pragma unroll
  for (int i = 0; i < 64; i++) O[i] = 0.f;
#pragma unroll
  for (int i = 0; i < 32; i++) P0[i] = P1[i] = 0u;
  fence_regs(O); fence_regs(P0); fence_regs(P1);
  float m0 = 0.f, m1 = 0.f, l0 = 0.f, l1 = 0.f, f0 = 1.f, f1 = 1.f, s0, s1, pl0 = 0.f, pl1 = 0.f;
  const int total = 16 * n;
  int g = 0;
  Ring kv = {1, 0};
  uint32_t kbar = bars + B_KF, kph = 0, vbar = bars + B_KF, vph = 0, krel, vrel = 0;
  const uint32_t kd0 = (uint32_t)make_desc(c.sb, 16, 1024), vd0 = (uint32_t)make_desc(c.sb, 16384, 1024);
  uint32_t qd = kd0 + ((OFF_Q0 + (c.warp >> 2) * 8192) >> 4), kd = kd0, vd = vd0;
  bool fresh, kready, vready, bad, slow, zero = true;
  mbar_spin(bars + B_QF, 0);
  mbar_spin(bars + B_KF, 0);
  att_stagger(c, 0);
#pragma unroll 1
  while (true) {
    ATT_ISSUE(P1, 1, g > 0)
    const bool first = ((g - 1) & 15) == 0;
    ATT_WAIT_S()
    ATT_SOFTMAX(P0, first)
    if (__builtin_expect(slow || first, 0)) {
      if (first) {
        if (g > 1) {
          att_pack(O, P1, pl0, pl1);
          att_stage(c, P1, ((g >> 4) & 1) ^ 1);
        }
      } else if (fresh) ATT_RESCALE();
      if (slow) {
        mbar_spin(kbar, kph);
        if (__any_sync(0xffffffffu, !kready)) att_stagger(c, g);
      }
    }
    ATT_ISSUE(P0, !first, true)
    ATT_WAIT_S()
    ATT_SOFTMAX(P1, false)
    if (__builtin_expect(slow || ((g + QW) & 15) <= QW, 0)) {
      if (fresh) ATT_RESCALE();
      if (g == total) break;
      if (slow) {
        mbar_spin(kbar, kph);
        if (__any_sync(0xffffffffu, !kready)) att_stagger(c, g);
      }
      if (((g + QW) & 15) == 0 && g + QW < total) { const int t = (g + QW) >> 4; mbar_spin(bars + B_QF + 8 * (t & 1), (t >> 1) & 1); }
      if ((g & 15) == 0) {
        qd = kd0 + ((((g & 16) ? OFF_Q1 : OFF_Q0) + (c.warp >> 2) * 8192) >> 4);
        pl0 = __fdividef(1.f, quad_sum(l0)); pl1 = __fdividef(1.f, quad_sum(l1));
        m0 = m1 = l0 = l1 = 0.f; zero = true;
      }
    }
  }
  release_slot(c, vrel);
  mbar_spin(vbar, vph);
  wgmma_fence();
  issue_pv(O, P1, vd, 1); wgmma_commit();
  pl0 = __fdividef(1.f, quad_sum(l0)); pl1 = __fdividef(1.f, quad_sum(l1));
  wgmma_wait<0>();
  fence_regs(O);
  release_slot(c, vbar + (B_KE - B_KF));
  att_pack(O, P0, pl0, pl1);
  if ((get_item(p, it + n) >> 12) == T_END) {
    const uint32_t buf = c.sb + (((n - 1) & 1) ? OFF_Q1 : OFF_Q0) + c.warp * 2048;
    stage_chunks<2>(buf, 16384, P0);
    fence_async_smem();
    __syncwarp();
    if (elect_one()) {
      const int im = get_item(p, it + n - 1), col = ((im >> 5) & 31) * 128, row = ((im & 7) * 2 + (blockIdx.x & 1)) * 128 + c.warp * 16;
      tma_store_2d(&p.tm[TS_O], buf, col, row); tma_store_2d(&p.tm[TS_O], buf + 16384, col + 64, row);
      bulk_commit();
      bulk_wait<0>();
      mbar_arrive(bars + B_STG);
    }
    __syncwarp();
  } else {
    att_stage(c, P0, (n - 1) & 1);
  }
}

__global__ void __cluster_dims__(2, 1, 1) __launch_bounds__(384, 1) fused_kernel(const __grid_constant__ Params p) {
  const uint32_t sb = smem_base();
  const uint32_t bars = sb + OFF_BAR;
  const int tid = threadIdx.x, lane = tid & 31;
  const int warp_id = __shfl_sync(0xffffffffu, tid >> 5, 0), wg = warp_id >> 2;
  const uint32_t rank = blockIdx.x & 1;
  const uint16_t* items = p.items[blockIdx.x >> 1];
  const int gw = blockIdx.x * 8 + warp_id - 4;
  uint4 xv[2][4];
  if (wg != 0 && gw < SEQ / 2) {
#pragma unroll
    for (int rr = 0; rr < 2; rr++)
#pragma unroll
      for (int i = 0; i < 4; i++) xv[rr][i] = __ldg(reinterpret_cast<const uint4*>(p.x + (size_t)(gw * 2 + rr) * DM) + i * 32 + lane);
  }
  if (warp_id == 1 && lane < TM_COUNT) asm volatile("prefetch.tensormap [%0];" :: "l"(&p.tm[lane]) : "memory");
  if (tid == 0) {
    for (int i = 0; i < 4; i++) { mbar_init(bars + B_GF + 8 * i, 1); mbar_init(bars + B_GE + 8 * i, 4); }
    for (int i = 0; i < 5; i++) { mbar_init(bars + B_KF + 8 * i, 1); mbar_init(bars + B_KE + 8 * i, 4); }
    for (int i = 0; i < 2; i++) { mbar_init(bars + B_QF + 8 * i, 1); mbar_init(bars + B_QE + 8 * i, 1); }
    mbar_init(bars + B_XF, 2); mbar_init(bars + B_XR, 2); mbar_init(bars + B_STG, 8); mbar_init(bars + B_FREE, 1); mbar_init(bars + B_GO, 1); mbar_init(bars + B_LN, 2); mbar_init(bars + B_PUB, 8);
    asm volatile("fence.mbarrier_init.release.cluster;" ::: "memory");
  }
  asm volatile("barrier.cluster.arrive.relaxed.aligned;" ::: "memory");

  if (wg == 0) {
    asm volatile("setmaxnreg.dec.sync.aligned.u32 40;");
    asm volatile("barrier.cluster.wait.acquire.aligned;" ::: "memory");
    if (warp_id >= 2 && (items[0] >> 12) == T_Z2) {
      const int r = (warp_id - 2) * 64 + 2 * lane;
      const uint2* ps = &g_stats[(((items[0] >> 5) & 31) * 2 + rank) * 1024 + r];
      uint32_t tag = 0, cnt = 0;
#pragma unroll 1
      for (;;) {
        uint4 t[7];
        bool ok = cnt > 0;
#pragma unroll
        for (int i = 0; i < 7; i++) {
          t[i] = make_uint4(0, 0, 0, 0);
          if (cnt > 0) t[i] = ld_tagged2(ps + i * 128);
        }
        float u0 = 0.f, u1 = 0.f, v0 = 0.f, v1 = 0.f;
#pragma unroll
        for (int i = 0; i < 7; i++) { ok = ok && tag_ok(t[i].x, t[i].y, tag) && tag_ok(t[i].z, t[i].w, tag); u0 += untag(t[i].x); u1 += untag(t[i].z); }
        u0 *= 1.f / 7; u1 *= 1.f / 7;
#pragma unroll
        for (int i = 0; i < 7; i++) {
          const float d0 = untag(t[i].x) - u0, d1 = untag(t[i].z) - u1;
          v0 += fmaf(256.f * d0, d0, untag(t[i].y)); v1 += fmaf(256.f * d1, d1, untag(t[i].w));
        }
        const float r0 = rsqrtf(fmaxf(v0, 0.f) * (1.f / FH) + 4e-5f), r1 = rsqrtf(fmaxf(v1, 0.f) * (1.f / FH) + 4e-5f);
        asm volatile("st.shared.v4.b32 [%0], {%1, %2, %3, %4};" :: "r"(sb + OFF_LN + r * 8), "r"(pack_bf16(r0, r0)), "r"(pack_bf16(-u0, -u0)),
                     "r"(pack_bf16(r1, r1)), "r"(pack_bf16(-u1, -u1)) : "memory");
        if (__all_sync(0xffffffffu, ok)) break;
        if (cnt == 0) {
          if (lane == 0) mbar_wait_sleep(bars + B_PUB, 0, 50);
          __syncwarp();
          asm volatile("ld.volatile.shared.u32 %0, [%1];" : "=r"(tag) : "r"(bars + B_TAG));
          __nanosleep(LN_SLEEP);
        }
        trap_if(++cnt > SPIN_LIMIT);
      }
      __syncwarp();
      if (lane == 0) mbar_arrive(bars + B_LN);
      __syncwarp();
    }
    if (warp_id == 0) {
      trap_if(sb & 1023);
      Ring g = {0, 1};
      int it = 0;
      uint32_t xph = 0;
      if (elect_one()) {
#pragma unroll 1
        for (;; it++) {
          const int item = items[it], type = item >> 12, b = item & 31, row = (((item >> 5) & 31) * 2 + rank) * 128;
          if (type >= T_ATT) break;
#pragma unroll 1
          for (int seg = 0; seg < (type == T_U ? 2 : 1); seg++) {
            const CUtensorMap* tA = &p.tm[seg ? TM_WSP : TM_XN];
            const CUtensorMap* tB = &p.tm[seg ? TM_Z2 : (type == T_Q ? TM_WQ : TM_WIN)];
            const int bchunk = b * 4 + (type == T_Z2 ? 28 : 0) + rank * 2;
            const unsigned* fl = seg ? &g_flags[F_Z2 + b * 32] : &g_flags[F_XN + (row >> 2)];
            const unsigned tgt = seg ? 16 : 128;
            int k = 0;
            if (it == 0 && seg == 0) {
              for (; k < 4; k++) {
                mbar_expect_tx(bars + B_GF + 8 * k, G_STAGE);
                tma_load_3d_mc(sb + k * G_STAGE + G_A + rank * 16384, tB, k * 64, bchunk, bars + B_GF + 8 * k);
              }
              g.ph ^= 1;
            }
            if (seg || type != T_U) { flag_wait(fl, tgt); fence_async_global(); }
            for (int x = 0; x < k; x++) tma_load_2d(sb + x * G_STAGE, tA, x * 64, row, bars + B_GF + 8 * x);
            if (it == 0) asm volatile("st.volatile.shared.v4.u32 [%0], {%1, %2, %2, %2};" :: "r"(bars + B_TAG), "r"(__ldcg(&g_epoch) % 4095u + 1), "r"(0) : "memory");
#pragma unroll 1
            for (; k < (seg ? 32 : 16); k++) {
              mbar_wait(bars + B_GE + 8 * g.s, g.ph);
              const uint32_t st = sb + g.s * G_STAGE, fb = bars + B_GF + 8 * g.s;
              mbar_expect_tx(fb, G_STAGE);
              tma_load_2d(st, tA, k * 64, row, fb);
              tma_load_3d_mc(st + G_A + rank * 16384, tB, k * 64, bchunk, fb);
              ring_adv<4>(g);
            }
          }
        }
      }
      { const int e = __ffs(__ballot_sync(0xffffffffu, elect_one())) - 1; it = __shfl_sync(0xffffffffu, it, e); g.ph = __shfl_sync(0xffffffffu, g.ph, e); }
      const int n = ((items[it] >> 10) & 3) + 3;
      Ring kv = {0, 1};
      if (elect_one()) {
        int prow = 0;
        {
          const int im = items[it];
          tma_prefetch_2d(&p.tm[(im & 1) ? TM_V : TM_K], rank * 64, ((im >> 5) & 31) * SEQ + ((im & 7) >> 1) * 128);
        }
#pragma unroll 1
        for (int x = 0; x <= 32 * n; x++) {
          const int gb = x >> 1, t = gb >> 4;
          const int hrow = ((items[it + t] >> 5) & 31) * SEQ;
          const bool isv = (x & 1) || x == 32 * n;
          if (x != 1) {
            if (x == 0 || x == 2) mbar_wait(bars + B_GE + 4 * x, g.ph);
            if (x == 4) { mbar_wait(bars + B_XF, xph); xph ^= 1; }
            mbar_wait(bars + B_KE + 8 * kv.s, kv.ph);
            mbar_expect_tx(bars + B_KF + 8 * kv.s, KV_SLOT);
            tma_load_2d_mc(sb + kv.s * KV_SLOT + rank * 16384, &p.tm[isv ? TM_V : TM_K], rank * 64, isv ? prow : hrow + (gb & 15) * 128, bars + B_KF + 8 * kv.s);
            ring_adv<5>(kv);
          }
          {
            const int gp = gb + KV_PF, ip = items[it + (gp >> 4)];
            if (gp < 16 * n && ((gp ^ ip) & (7 >> ((ip >> 3) & 3))) == 0) tma_prefetch_2d(&p.tm[(x & 1) ? TM_V : TM_K], rank * 64, ((ip >> 5) & 31) * SEQ + (gp & 15) * 128);
          }
          if (x == 32 * n - 8) mbar_arrive(bars + B_GO);
          if (x & 1) prow = hrow + (gb & 15) * 128;
          if ((x & 31) == Q_AT && t + 1 < n) {
            const int tq = t + 1;
            const int im = items[it + tq], h = (im >> 5) & 31, m = (im & 7) * 2 + rank;
            const uint32_t qb = tq & 1;
            flag_wait(&g_flags[F_Q + m * 16 + (h >> 1)], 1);
            fence_async_global();
            mbar_wait(bars + B_QE + 8 * qb, ((tq - 1) >> 1) & 1);
            const uint32_t dst = sb + (qb ? OFF_Q1 : OFF_Q0), fb = bars + B_QF + 8 * qb;
            mbar_expect_tx(fb, 32768);
            tma_load_2d(dst, &p.tm[TM_Q], h * 128, m * 128, fb);
            tma_load_2d(dst + 16384, &p.tm[TM_Q], h * 128 + 64, m * 128, fb);
          }
        }
      }
      __syncwarp();
      it += n;
      uint32_t ready = 0;
      auto wait_head = [&](int h) {
        if ((ready >> h) & 1) return;
        uint32_t cnt = 0;
        while (true) {
          asm volatile("ld.acquire.cta.shared.u32 %0, [%1];" : "=r"(ready) : "r"(bars + B_RDY) : "memory");
          if ((ready >> h) & 1) break;
          trap_if(++cnt > SPIN_LIMIT * 8);
          __nanosleep(20);
        }
        fence_async_global();
      };
      int item = items[it];
      if ((item >> 12) == T_SA) {
        const int m = ((item >> 5) & 31) * 2 + rank, b = item & 31;
        Ring dr = kv;
        wait_head(0);
#pragma unroll 1
        for (int i = 0; i < 28 + SA_STEPS; i++) {
          {
            const bool so = i >= 28;
            const int k = so ? i - 28 : i;
            if (so) wait_head(k >> 1);
            if (elect_one()) {
              if (i < 4) { for (int x = 0; x < ((0x1022 >> (4 * i)) & 3); x++) { mbar_wait(bars + B_KE + 8 * dr.s, dr.ph); ring_adv<5>(dr); } }
              if (i == 2) { mbar_wait(bars + B_XF, xph); xph ^= 1; }
              mbar_wait(bars + B_GE + 8 * g.s, g.ph);
              const uint32_t st = sb + ((g.s + 1) & 3) * G_STAGE, fb = bars + B_GF + 8 * g.s;
              mbar_expect_tx(fb, G_STAGE);
              tma_load_2d(st, &p.tm[so ? TM_O : TM_U], k * 64, m * 128, fb);
              tma_load_3d_mc(st + G_A + rank * 16384, &p.tm[so ? TM_WO : TM_WOUT], k * 64, b * 4 + rank * 2, fb);
            }
            ring_adv<4>(g);
          }
          const int ip = i + OUT_PF;
          if (ip < 28 + SA_STEPS && elect_one()) {
            const bool so = ip >= 28;
            const int k = so ? ip - 28 : ip;
            if ((ip & 3) == b && (!so || ((ready >> (k >> 1)) & 1))) tma_prefetch_2d(&p.tm[so ? TM_O : TM_U], k * 64, m * 128);
            if ((ip & 7) == (m >> 1)) tma_prefetch_3d(&p.tm[so ? TM_WO : TM_WOUT], k * 64, b * 4 + rank * 2);
          }
          __syncwarp();
        }
        item = items[++it];
      }
      if ((item >> 12) == T_FIN) {
        const bool own = item & 4;
        const int m = ((item >> 5) & 31) * 2 + rank, col = (item & 3) * 256 + (own ? 128 : 0);
        uint32_t ps = own ? FIN_SLOT0 : kv.s;
#pragma unroll 1
        for (int i = SA_STEPS; i <= 2 * NH; i++) {
          const bool extra = i == 2 * NH - FIN_PREP;
          if (extra && own) continue;
          const int k = i > 2 * NH - FIN_PREP ? i - 1 : i;
          if (!extra) wait_head(k >> 1);
          if (elect_one()) {
            if (i == SA_STEPS) {
              for (int y = k; y < k + 4; y++) if ((ready >> (y >> 1)) & 1) tma_prefetch_2d(&p.tm[TM_O], y * 64, m * 128);
            }
            if (own && i < SA_STEPS + 5) {
              const uint32_t s0 = ((0x22100u >> (4 * ps)) - 1) & 3, s1 = ((0x32110u >> (4 * ps)) - 1) & 3;
              mbar_wait(bars + B_GE + 8 * s0, g.ph ^ (s0 < g.s)); mbar_wait(bars + B_GE + 8 * s1, g.ph ^ (s1 < g.s));
            }
            if (extra) { flag_wait(&g_flags[F_S + m * 4 + (item & 3)], 2); fence_async_global(); }
            mbar_wait(bars + B_KE + 8 * kv.s, kv.ph);
            const uint32_t dst = sb + ps * KV_SLOT, fb = bars + B_KF + 8 * kv.s;
            if (++ps == 5) ps = 0;
            mbar_expect_tx(fb, KV_SLOT);
            if (!extra) {
              tma_load_2d(dst, &p.tm[TM_O], k * 64, m * 128, fb);
              tma_load_2d_mc(dst + 16384 + rank * 8192, &p.tm[TM_WO64], col + rank * 64, k * 64, fb);
            } else {
              tma_load_2d(dst, &p.tm[TM_SA], col, m * 128, fb);
              tma_load_2d(dst + 16384, &p.tm[TM_SA], col + 64, m * 128, fb);
            }
            ring_adv<5>(kv);
          }
          __syncwarp();
        }
      }
      unsigned last = 0;
      if (lane == 0 && (item >> 12) == T_FIN) mbar_wait_sleep(bars + B_XR, 0, 100);
      if (lane == 0) { __threadfence(); last = atomicInc(&g_done, gridDim.x - 1) == gridDim.x - 1; }
      last = __shfl_sync(0xffffffffu, last, 0);
      if (last) {
        for (int i = lane; i < F_TOTAL / 4; i += 32) reinterpret_cast<uint4*>(g_flags)[i] = make_uint4(0, 0, 0, 0);
        if (lane == 0) g_epoch = g_epoch + 1;
      }
    } else if (warp_id == 1) {
      if (elect_one()) {
        uint32_t ph = 0;
        int t = 0;
#pragma unroll 1
        for (int it = 0;; it++) {
          const int item = items[it], type = item >> 12, a = (item >> 5) & 31, b = item & 31;
          if (type == T_END) break;
          const int nt = items[it + 1] >> 12;
          int row = (a * 2 + rank) * 128, col = b * 256;
          unsigned* f = &g_flags[F_S + (a * 2 + rank) * 4 + b];
          int tm = TS_G, npair = 2;
          bool quad = false;
          uint32_t src = sb + OFF_Q0;
          if (type == T_Z2) { tm = TS_Z2; f = &g_flags[F_Z2 + b * 32]; }
          else if (type == T_Q) { tm = TS_Q; f = &g_flags[F_Q + (a * 2 + rank) * 16 + b]; if (nt >= T_ATT) { npair = 0; quad = true; } }
          else if (type == T_U) { tm = TS_U; f = &g_flags[F_U + (a * 2 + rank) * 32]; npair = 0; quad = true; }
          else if (type == T_ATT) { tm = TS_O; f = &g_flags[F_O + ((b & 7) * 2 + rank) * 32 + a]; npair = 1; row = ((b & 7) * 2 + rank) * 128; col = a * 128; if (t & 1) src = sb + OFF_Q1; }
          else if (type == T_FIN) npair = 1;
          auto load_fin = [&](int fi, int tmi, uint32_t qb) {
            const int fc = (fi & 3) * 256 + ((fi & 4) ? 128 : 0), fr = (((fi >> 5) & 31) * 2 + rank) * 128;
            mbar_expect_tx(bars + B_QF + 8 * qb, 32768);
            tma_load_2d(sb + (qb ? OFF_Q1 : OFF_Q0), &p.tm[tmi], fc, fr, bars + B_QF + 8 * qb);
            tma_load_2d(sb + (qb ? OFF_Q1 : OFF_Q0) + 16384, &p.tm[tmi], fc + 64, fr, bars + B_QF + 8 * qb);
          };
          if (type == T_ATT && nt == T_FIN) load_fin(items[it + 1], TM_X, (t & 1) ^ 1);
          if (type == T_FIN) {
            if (!(item & 4)) { flag_wait(&g_flags[F_S + (a * 2 + rank) * 4 + (b & 3)], 1); fence_async_global(); load_fin(item, TM_G, (t & 1) ^ 1); }
            mbar_arrive(bars + B_XR);
          }
#pragma unroll 1
          for (int op = 0; op < npair + quad; op++) {
            const bool q = op == npair;
            const int c0 = (q || type == T_SA) ? col : col + op * 128;
            mbar_wait_sleep(bars + B_STG, ph, (type == T_ATT && nt == T_ATT) ? SW_ATT : SW_NS);
            if (type == T_FIN) break;
            ph ^= 1;
            fence_async_smem();
            if (type == T_SA && op == 1) { tm = TS_SA; load_fin(items[it + 1], TM_X, 1); }
            int c1 = c0;
            if (q) {
              const CUtensorMap* tb = &p.tm[type == T_U ? TM_U : TM_Q];
              tma_store_2d(tb, sb + 2 * G_STAGE, c0, row);
              tma_store_2d(tb, sb + 3 * G_STAGE, c0 + 64, row);
              bulk_commit();
              bulk_wait_read<0>();
              mbar_arrive_cta(bars + B_XF, 0); mbar_arrive_cta(bars + B_XF, 1);
              src = sb + OFF_Q1; c1 += 128;
            }
            if (nt != T_END) {
#pragma unroll 1
              for (int r = 0; r < 256; r += ST_ROWS) {
                tma_store_2d(&p.tm[tm], src + r * 128, c1 + (r >> 7) * 64, row + (r & 127));
                bulk_commit();
                bulk_wait_read<ST_FLY>();
                if (q) __nanosleep(U_PACE);
              }
            }
            bulk_wait_read<0>();
            mbar_arrive(bars + B_FREE);
            if (type == T_ATT && (t & 1) && (nt == T_SA || (items[it + 2] >> 12) == T_SA)) { mbar_arrive_cta(bars + B_XF, 0); mbar_arrive_cta(bars + B_XF, 1); }
            if (type == T_ATT) mbar_arrive(bars + B_QE + 8 * (t & 1));
            else if (nt == T_ATT) mbar_arrive(bars + B_QE + 8);
            if (op + 1 >= npair || type == T_SA) {
              bulk_wait<0>();
              red_release(f, 1);
            }
          }
          if (type == T_ATT) t++;
          else if (t == 0 && (items[it + 1] >> 12) < T_ATT && (items[it + 2] >> 12) == T_ATT) {
            const int im = items[it + 2], h = (im >> 5) & 31, m = (im & 7) * 2 + rank;
            flag_wait(&g_flags[F_Q + m * 16 + (h >> 1)], 1);
            fence_async_global();
            mbar_expect_tx(bars + B_QF, 32768);
            tma_load_2d(sb + OFF_Q0, &p.tm[TM_Q], h * 128, m * 128, bars + B_QF);
            tma_load_2d(sb + OFF_Q0 + 16384, &p.tm[TM_Q], h * 128 + 64, m * 128, bars + B_QF);
          }
        }
      }
      __syncwarp();
    } else if (warp_id == 2) {
      int it = 0;
      while ((items[it] >> 12) <= T_ATT) it++;
      if ((items[it] >> 12) != T_END) {
        const bool sa = (items[it] >> 12) == T_SA;
        const int m = ((items[it] >> 5) & 31) * 2 + rank;
        if (lane == 0) {
          mbar_wait_sleep(bars + B_GO, 0, 500);
          if (sa) {
            const int b = items[it] & 3;
            flag_wait(&g_flags[F_U + m * 32], 7);
            fence_async_global();
            for (int y = b; y < OUT_PF; y += 4) tma_prefetch_2d(&p.tm[TM_U], y * 64, m * 128);
            tma_prefetch_3d(&p.tm[TM_WOUT], (m >> 1) * 64, b * 4 + rank * 2);
          }
          if (!sa) for (int y = m * 4 + (items[it] & 3); y < 16 * (NH - SA_HEADS); y += 64) tma_prefetch_3d(&p.tm[TM_WO], (2 * SA_HEADS + (y >> 3)) * 64, (y & 7) * 2);
        }
        __syncwarp();
        uint32_t cnt = 0;
        while (true) {
          const uint32_t r = __ballot_sync(0xffffffffu, ld_acquire(&g_flags[F_O + m * 32 + lane]) != 0);
          if (lane == 0) asm volatile("st.release.cta.shared.u32 [%0], %1;" :: "r"(bars + B_RDY), "r"(r) : "memory");
          if (r == ~0u) break;
          trap_if(++cnt > SPIN_LIMIT);
          __nanosleep(r >> 28 ? 20 : 300);
        }
        if (lane == 0) mbar_arrive(bars + B_XR);
      }
      __syncwarp();
    }
    cluster_sync_relaxed();
  } else {
    Cons c;
    c.sb = sb; c.warp = warp_id - 4; c.g = {0, 0}; c.fph = 1; c.rot = 0;
    if (gw < SEQ / 2) {
      uint4* dst = reinterpret_cast<uint4*>(g_xn + (size_t)gw * 2 * DM) + lane;
      float f[2][32], s[2], q[2];
#pragma unroll
      for (int rr = 0; rr < 2; rr++) {
        const float pv = __shfl_sync(0xffffffffu, bf_lo(xv[rr][0].x), 0);
#pragma unroll
        for (int i = 0; i < 4; i++) {
          const uint4 v = xv[rr][i];
          f[rr][8 * i + 0] = bf_lo(v.x) - pv; f[rr][8 * i + 1] = bf_hi(v.x) - pv; f[rr][8 * i + 2] = bf_lo(v.y) - pv; f[rr][8 * i + 3] = bf_hi(v.y) - pv;
          f[rr][8 * i + 4] = bf_lo(v.z) - pv; f[rr][8 * i + 5] = bf_hi(v.z) - pv; f[rr][8 * i + 6] = bf_lo(v.w) - pv; f[rr][8 * i + 7] = bf_hi(v.w) - pv;
        }
        s[rr] = q[rr] = 0.f;
#pragma unroll
        for (int i = 0; i < 32; i++) { s[rr] += f[rr][i]; q[rr] = fmaf(f[rr][i], f[rr][i], q[rr]); }
      }
#pragma unroll
      for (int o = 16; o; o >>= 1)
#pragma unroll
        for (int rr = 0; rr < 2; rr++) { s[rr] += __shfl_xor_sync(0xffffffffu, s[rr], o); q[rr] += __shfl_xor_sync(0xffffffffu, q[rr], o); }
#pragma unroll
      for (int rr = 0; rr < 2; rr++) {
        const float mean = s[rr] * (1.f / DM);
        const float r = rsqrtf(fmaxf(q[rr] * (1.f / DM) - mean * mean, 0.f) + 1e-5f), a = -mean * r;
#pragma unroll
        for (int i = 0; i < 4; i++) {
          const float* y = &f[rr][8 * i];
          dst[rr * 128 + i * 32] = make_uint4(pack_bf16(fmaf(y[0], r, a), fmaf(y[1], r, a)), pack_bf16(fmaf(y[2], r, a), fmaf(y[3], r, a)),
                                              pack_bf16(fmaf(y[4], r, a), fmaf(y[5], r, a)), pack_bf16(fmaf(y[6], r, a), fmaf(y[7], r, a)));
        }
      }
      named_sync(7);
      if (tid == 128) red_release(&g_flags[F_XN + (gw >> 6) * 32], 16);
    }
    asm volatile("setmaxnreg.inc.sync.aligned.u32 232;");
    asm volatile("barrier.cluster.wait.acquire.aligned;" ::: "memory");
    int natt = 0;
    int it = 0;
    uint32_t held[64];
#pragma unroll
    for (int i = 0; i < 64; i++) held[i] = 0u;
    Shadow sh = {0, 0};
    float facc[64];
#pragma unroll 1
    while (true) {
      const int item = get_item(p, it), type = item >> 12, a = (item >> 5) & 31;
      c.warp = fresh_warp();
      if (type == T_ATT) {
        const int n = ((item >> 10) & 3) + 3;
        att_run(c, p, it, n);
#pragma unroll
        for (int i = 0; i < 64; i++) held[i] = 0u;
        natt = n;
        it += n;
        c.rot = 1;
        if ((get_item(p, it) >> 12) == T_SA) continue;
#pragma unroll
        for (int i = 0; i < 64; i++) facc[i] = 0.f;
        break;
      }
      float acc[128];
      const bool sa = type == T_SA;
      bool more = type >= T_U;
      int nsteps = sa ? 28 : 16;
      const bool direct = (get_item(p, it + 1) >> 12) >= T_ATT;
      uint32_t bias0 = 0, bias1 = 0;
#pragma unroll 1
      while (true) {
        gemm_seg(acc, held, c, p, sh, nsteps);
        if (!more && direct && !sa) pp_arrive(c.warp >= 4);
        if (type == T_Q) {
#pragma unroll
          for (int i = 0; i < 128; i++) acc[i] *= SM_C;
        }
        if (!more && direct) break;
#pragma unroll
        for (int i = 0; i < 64; i++) held[i] = pack_bf16(acc[2 * i], acc[2 * i + 1]);
        if (!more) break;
        more = false;
        nsteps = sa ? SA_STEPS : 32;
        sh.act = sa ? 3 : 1;
        if (sa) {
          sh.store = 3;
        } else {
          const int row0 = (a * 2 + rank) * 128 + c.warp * 16 + (lane_id() >> 2);
          asm volatile("ld.global.nc.u16 %0, [%1];" : "=r"(bias0) : "l"(p.b_sp + row0));
          asm volatile("ld.global.nc.u16 %0, [%1];" : "=r"(bias1) : "l"(p.b_sp + row0 + 8));
        }
      }
      c.warp = fresh_warp();
      if (direct) {
        const uint32_t hb0 = bf2_mul(bias0 * 0x10001u, BF2_HALF), hb1 = bf2_mul(bias1 * 0x10001u, BF2_HALF);
        stage_acquire(c);
#pragma unroll
        for (int h = 0; h < 2; h++) {
          uint32_t pk[32];
#pragma unroll
          for (int i = 0; i < 32; i++) pk[i] = pack_bf16(acc[64 * h + 2 * i], acc[64 * h + 2 * i + 1]);
          if (type == T_U) {
#pragma unroll
            for (int i = 0; i < 32; i++) pk[i] = bf2_mul(bf2_fma(pk[i], BF2_HALF, (i & 1) ? hb1 : hb0), held[32 * h + i]);
          }
          if (h) pp_sync(c.warp >= 4);
          stage_chunks<2>(sb + (h ? OFF_Q1 : (sa ? OFF_Q0 : 2 * G_STAGE)) + c.warp * 2048, (h || sa) ? 16384 : G_STAGE, pk);
          if (sa) break;
        }
        stage_commit(c);
        if (sa) {
#pragma unroll
          for (int i = 0; i < 64; i++) facc[i] = acc[64 + i];
          it++;
          break;
        }
      } else if (type == T_Q) {
        sh.store = 1;
      } else {
        sh.act = sh.store = 2;
      }
      it++;
    }
    const int fin = get_item(p, it);
    if ((fin >> 12) == T_FIN) {
      c.warp = fresh_warp();
      const bool own = fin & 4;
      Ring kv = {(uint32_t)(32 * natt) % 5, ((uint32_t)(32 * natt) / 5) & 1};
      uint32_t prev = 0, ps = own ? FIN_SLOT0 : kv.s;
      fence_regs(facc);
      auto fin_steps = [&](int k0, int k1) {
#pragma unroll 1
        for (int k = k0; k < k1; k++) {
          mbar_spin(bars + B_KF + 8 * kv.s, kv.ph);
          const uint32_t st = ((c.sb & 0x3FFFF) >> 4) + ps * (KV_SLOT >> 4);
          if (++ps == 5) ps = 0;
          const uint32_t da = st + (c.warp >> 2) * 512 + (1u << 16), db = st + 1024 + ((8192u >> 4) << 16);
          wgmma_fence();
#pragma unroll
          for (int kk = 0; kk < 4; kk++) wgmma_m64n128k16_ss_tb1(facc, DESC_HI | (da + kk * 2), DESC_HI | (db + kk * 128), 1);
          wgmma_commit();
          wgmma_wait<1>();
          if (k > SA_STEPS) release_slot(c, prev);
          prev = bars + B_KE + 8 * kv.s;
          ring_adv<5>(kv);
        }
      };
      const int kp = (own && ((fin >> 5) & 31) == 7) ? SA_STEPS + 5 : 2 * NH - FIN_PREP - (own ? OWN_OFF : 0);
      fin_steps(SA_STEPS, kp);
      const uint32_t ln = lane_id(), xb = own ? 1 : natt & 1;
      const uint32_t lo = c.warp * 2048 + ((ln & 15) << 7);
      uint32_t xs[32];
      auto load_tile = [&](uint32_t base, uint32_t* d) {
#pragma unroll
        for (int i = 0; i < 8; i++) ldmatrix_x4(base + lo + (i >> 2) * 16384 + (((2 * (i & 3) + (ln >> 4)) ^ (ln & 7)) << 4), d[4 * i], d[4 * i + 1], d[4 * i + 2], d[4 * i + 3]);
      };
      const uint32_t xa = sb + (xb ? OFF_Q1 : OFF_Q0);
      mbar_spin(bars + B_QF + 8 * xb, ((natt + 1 - xb) >> 1) & 1);
      load_tile(xa, xs);
      if (!own) {
        mbar_spin(bars + B_QF + 8 * (xb ^ 1), ((natt + xb) >> 1) & 1);
        load_tile(sb + (xb ? OFF_Q0 : OFF_Q1), held + 32);
      }
      float gf[64], rf[64];
#pragma unroll
      for (int i = 0; i < 32; i++) { gf[2 * i] = bf_lo(held[32 + i]); gf[2 * i + 1] = bf_hi(held[32 + i]); rf[2 * i] = bf_lo(xs[i]); rf[2 * i + 1] = bf_hi(xs[i]); }
      if (!own) {
        mbar_spin(bars + B_KF + 8 * kv.s, kv.ph);
#pragma unroll
        for (int i = 0; i < 8; i++) {
          uint32_t t[4];
          ldmatrix_x4(sb + ps * KV_SLOT + lo + (i >> 2) * 16384 + (((2 * (i & 3) + (ln >> 4)) ^ (ln & 7)) << 4), t[0], t[1], t[2], t[3]);
#pragma unroll
          for (int y = 0; y < 4; y++) {
            rf[8 * i + 2 * y] = fmaf(bf_lo(t[y]), gf[8 * i + 2 * y], rf[8 * i + 2 * y]);
            rf[8 * i + 2 * y + 1] = fmaf(bf_hi(t[y]), gf[8 * i + 2 * y + 1], rf[8 * i + 2 * y + 1]);
          }
        }
        wg_any(c.warp >= 4, false);
        release_slot(c, bars + B_KE + 8 * kv.s);
        if (++ps == 5) ps = 0;
        ring_adv<5>(kv);
      }
      fence_regs(gf); fence_regs(rf);
      fin_steps(kp, 2 * NH);
      wgmma_wait<0>();
      fence_regs(facc);
#pragma unroll
      for (int i = 0; i < 32; i++) xs[i] = pack_bf16(fmaf(facc[2 * i], gf[2 * i], rf[2 * i]), fmaf(facc[2 * i + 1], gf[2 * i + 1], rf[2 * i + 1]));
      __syncwarp();
      stage_chunks<2>(xa + c.warp * 2048, 16384, xs);
      fence_async_smem();
      __syncwarp();
      if (elect_one()) {
        const int col = (fin & 3) * 256 + (own ? 128 : 0), row = (((fin >> 5) & 31) * 2 + rank) * 128 + c.warp * 16;
        tma_store_2d(&p.tm[TS_OUT], xa + c.warp * 2048, col, row);
        tma_store_2d(&p.tm[TS_OUT], xa + c.warp * 2048 + 16384, col + 64, row);
        bulk_commit();
        mbar_arrive(bars + B_STG);
        bulk_wait_read<0>();
      }
    }
    __syncwarp();
    cluster_sync_relaxed();
  }
}

typedef CUresult (*PFN_encodeTiled)(CUtensorMap*, CUtensorMapDataType, cuuint32_t, void*, const cuuint64_t*, const cuuint64_t*, const cuuint32_t*, const cuuint32_t*,
                                    CUtensorMapInterleave, CUtensorMapSwizzle, CUtensorMapL2promotion, CUtensorMapFloatOOBfill);
static PFN_encodeTiled s_encode = nullptr;
static void tm_2d(CUtensorMap* tm, const void* ptr, uint64_t rows, uint64_t cols, uint32_t box_rows) {
  cuuint64_t dims[2] = {cols, rows}; cuuint64_t strides[1] = {cols * 2}; cuuint32_t box[2] = {64, box_rows}; cuuint32_t es[2] = {1, 1};
  CUresult r = s_encode(tm, CU_TENSOR_MAP_DATA_TYPE_BFLOAT16, 2, (void*)ptr, dims, strides, box, es, CU_TENSOR_MAP_INTERLEAVE_NONE,
                        CU_TENSOR_MAP_SWIZZLE_128B, CU_TENSOR_MAP_L2_PROMOTION_L2_128B, CU_TENSOR_MAP_FLOAT_OOB_FILL_NONE);
  if (r != CUDA_SUCCESS) fprintf(stderr, "tensor map encode failed (%d)\n", (int)r);
}
static void tm_3d(CUtensorMap* tm, const void* ptr, uint64_t rows, uint64_t cols) {
  cuuint64_t dims[3] = {64, rows, cols / 64}; cuuint64_t strides[2] = {cols * 2, 128}; cuuint32_t box[3] = {64, 64, 2}; cuuint32_t es[3] = {1, 1, 1};
  CUresult r = s_encode(tm, CU_TENSOR_MAP_DATA_TYPE_BFLOAT16, 3, (void*)ptr, dims, strides, box, es, CU_TENSOR_MAP_INTERLEAVE_NONE,
                        CU_TENSOR_MAP_SWIZZLE_128B, CU_TENSOR_MAP_L2_PROMOTION_L2_128B, CU_TENSOR_MAP_FLOAT_OOB_FILL_NONE);
  if (r != CUDA_SUCCESS) fprintf(stderr, "tensor map encode failed (%d)\n", (int)r);
}
static inline uint16_t mk(int type, int a, int b) { return (uint16_t)(type << 12 | a << 5 | b); }

static void build_schedule(Params& P) {
  int cnt[NCLUSTER];
  for (int c = 0; c < NCLUSTER; c++) { cnt[c] = 0; for (int i = 0; i < MAXI; i++) P.items[c][i] = mk(T_END, 0, 0); }
  auto phys = [](int c) { return c == 64 ? 9 : c == 65 ? 17 : c == 9 ? 64 : c == 17 ? 65 : c; };
  auto push = [&](int c, uint16_t v) { P.items[phys(c)][cnt[c]++] = v; };
  int natt[NCLUSTER], nq[NCLUSTER];
  for (int c = 0; c < NCLUSTER; c++) { natt[c] = c < 32 ? 3 : (c < 56 ? 5 : (c < 62 ? 4 : (c < 64 ? 3 : 5))); nq[c] = c < 56 ? 1 : (c < 62 ? 7 : (c < 64 ? 9 : 6)); }
  for (int c = 0; c < 56; c++) push(c, mk(T_Z2, c % 8, c / 8));
  int qi = 0;
  for (int slot = 0; slot < 9; slot++)
    for (int c = NCLUSTER - 1; c >= 0; c--) {
      const int first = c < 56 ? 1 : 0;
      if (slot >= first && slot < first + nq[c]) { push(c, mk(T_Q, qi % 8, qi / 8)); qi++; }
    }
  for (int c = 0; c < 56; c++) push(c, mk(T_U, c % 8, c / 8));
  int ai = 0, grp[256], own[256];
  for (int slot = 0; slot < 5; slot++)
    for (int c = 0; c < NCLUSTER; c++) {
      const int first = c < 32 ? 0 : 5 - natt[c];
      if (slot >= first && slot < first + natt[c]) { grp[ai] = slot * 2 + (c >= 64); own[ai++] = c; }
    }
  for (int i = 0; i < 256; i++) {
    int s = 0;
    for (int j = i & ~7; j < (i & ~7) + 8; j++) s += grp[j] == grp[i];
    const int share = s >= 8 ? 0 : s >= 4 ? 1 : s >= 2 ? 2 : 3;
    push(own[i], mk(T_ATT, i / 8, share << 3 | i % 8) | (natt[own[i]] - 3) << 10);
  }
  for (int c = 0; c < 32; c++) push(c, mk(T_SA, c % 8, c / 8));
  for (int c = 0; c < 64; c++) push(c, mk(T_FIN, c % 8, (c / 8) % 4 | (c < 32 ? 4 : 0)));
  if (qi != 128 || ai != 256) fprintf(stderr, "bad schedule %d %d\n", qi, ai);
}

static Params s_params;
extern "C" void kernel_launch(void* const* d_in, const int* in_sizes, int n_in, void* d_out, int out_size) {
  (void)in_sizes; (void)n_in; (void)out_size;
  if (!s_encode) {
    void* fn = nullptr; cudaDriverEntryPointQueryResult qr;
    cudaGetDriverEntryPoint("cuTensorMapEncodeTiled", &fn, cudaEnableDefault, &qr);
    s_encode = (PFN_encodeTiled)fn;
    cudaFuncSetAttribute(fused_kernel, cudaFuncAttributeMaxDynamicSharedMemorySize, SMEM_BYTES);
    build_schedule(s_params);
  }
  Params& P = s_params;
  void *xn, *q, *o, *z2, *u, *gg, *sa;
  cudaGetSymbolAddress(&gg, g_g); cudaGetSymbolAddress(&sa, g_sa);
  cudaGetSymbolAddress(&xn, g_xn); cudaGetSymbolAddress(&q, g_q); cudaGetSymbolAddress(&o, g_o);
  cudaGetSymbolAddress(&z2, g_z2); cudaGetSymbolAddress(&u, g_u);
  tm_2d(&P.tm[TM_XN], xn, SEQ, DM, 128); tm_2d(&P.tm[TM_WSP], d_in[7], SEQ, SEQ, 128); tm_2d(&P.tm[TM_U], u, SEQ, FH, 128);
  tm_2d(&P.tm[TM_O], o, SEQ, HD, 128); tm_2d(&P.tm[TM_Q], q, SEQ, HD, 128); tm_2d(&P.tm[TM_X], d_in[0], SEQ, DM, 128);
  tm_2d(&P.tm[TM_K], d_in[1], NH * SEQ, 128, 128); tm_2d(&P.tm[TM_V], d_in[2], NH * SEQ, 128, 128);
  tm_2d(&P.tm[TM_SA], sa, SEQ, DM, 128); tm_2d(&P.tm[TM_G], gg, SEQ, DM, 128); tm_2d(&P.tm[TM_WO64], d_in[4], HD, DM, 64);
  tm_3d(&P.tm[TM_WIN], d_in[6], DM, FF); tm_3d(&P.tm[TM_WQ], d_in[3], DM, HD); tm_3d(&P.tm[TM_Z2], z2, SEQ, FH);
  tm_3d(&P.tm[TM_WOUT], d_in[9], FH, DM); tm_3d(&P.tm[TM_WO], d_in[4], HD, DM);
  tm_2d(&P.tm[TS_Q], q, SEQ, HD, ST_ROWS); tm_2d(&P.tm[TS_O], o, SEQ, HD, ST_ROWS); tm_2d(&P.tm[TS_Z2], z2, SEQ, FH, ST_ROWS); tm_2d(&P.tm[TS_U], u, SEQ, FH, ST_ROWS);
  tm_2d(&P.tm[TS_SA], sa, SEQ, DM, ST_ROWS); tm_2d(&P.tm[TS_G], gg, SEQ, DM, ST_ROWS); tm_2d(&P.tm[TS_OUT], d_out, SEQ, DM, 16);
  P.x = (const bf16*)d_in[0]; P.b_sp = (const bf16*)d_in[8];
  fused_kernel<<<2 * NCLUSTER, 384, SMEM_BYTES, cudaStreamPerThread>>>(P);
}
```

```cpp
#include <cuda_runtime.h>
#include <cuda_bf16.h>
#include <cuda.h>
#include <stdint.h>
#include <stdio.h>

typedef __nv_bfloat16 bf16;

constexpr int SEQ = 2048, DM = 1024, NH = 32, HD = 4096, FF = 3584, FH = 1792;

__device__ __align__(1024) bf16 g_xn[SEQ * DM];
__device__ __align__(1024) bf16 g_q[SEQ * HD];
__device__ __align__(1024) bf16 g_o[SEQ * HD];
__device__ __align__(1024) bf16 g_z2[SEQ * FH];
__device__ __align__(1024) bf16 g_u[SEQ * FH];
__device__ __align__(1024) uint2 g_stats[SEQ * 8];
__device__ __align__(1024) bf16 g_g[SEQ * DM];
__device__ __align__(1024) bf16 g_sa[SEQ * DM];
constexpr int F_XN = 0;
constexpr int F_Z2 = 512;
constexpr int F_Q = 768;
constexpr int F_U = 1024;
constexpr int F_O = 1536;
constexpr int F_S = 2048;
constexpr int F_TOTAL = 2112;
__device__ __align__(1024) unsigned g_flags[F_TOTAL];
__device__ unsigned g_done;
__device__ unsigned g_epoch;

__device__ __forceinline__ uint32_t smem_u32(const void* p) { return (uint32_t)__cvta_generic_to_shared(p); }
__device__ __forceinline__ void mbar_init(uint32_t bar, uint32_t cnt) { asm volatile("mbarrier.init.shared::cta.b64 [%0], %1;" :: "r"(bar), "r"(cnt)); }
__device__ __forceinline__ void mbar_expect_tx(uint32_t bar, uint32_t bytes) { asm volatile("mbarrier.arrive.expect_tx.shared::cta.b64 _, [%0], %1;" :: "r"(bar), "r"(bytes) : "memory"); }
__device__ __forceinline__ void mbar_arrive(uint32_t bar) { asm volatile("mbarrier.arrive.shared::cta.b64 _, [%0];" :: "r"(bar) : "memory"); }
__device__ __forceinline__ void mbar_arrive_cta(uint32_t bar, uint32_t cta) {
  asm volatile("{\n.reg .b32 ra;\nmapa.shared::cluster.u32 ra, %0, %1;\nmbarrier.arrive.shared::cluster.b64 _, [ra];\n}" :: "r"(bar), "r"(cta) : "memory");
}
__device__ __forceinline__ bool mbar_test(uint32_t bar, uint32_t parity) {
  uint32_t ok;
  asm volatile("{\n.reg .pred P1;\nmbarrier.test_wait.parity.shared::cta.b64 P1, [%1], %2;\nselp.u32 %0, 1, 0, P1;\n}" : "=r"(ok) : "r"(bar), "r"(parity) : "memory");
  return ok;
}
__device__ __forceinline__ bool mbar_test_a(uint32_t bar, uint32_t parity) {
  uint32_t ok;
  asm volatile("{\n.reg .pred P2;\nmbarrier.test_wait.parity.shared::cta.b64 P2, [%1], %2;\nselp.u32 %0, 1, 0, P2;\n}" : "=r"(ok) : "r"(bar), "r"(parity) : "memory");
  return ok;
}
constexpr uint32_t SPIN_LIMIT = 1u << 22;
__device__ __forceinline__ void trap_if(bool c) { asm volatile("{\n.reg .pred P;\nsetp.ne.u32 P, %0, 0;\n@P trap;\n}" :: "r"((uint32_t)c)); }
__device__ __forceinline__ void mbar_wait(uint32_t bar, uint32_t parity) {
  asm volatile("{\n.reg .pred P1;\n.reg .u32 n;\nmbarrier.try_wait.parity.shared::cta.b64 P1, [%0], %1;\n@P1 bra DONE;\nmov.u32 n, 0;\n"
               "LOOP:\nmbarrier.try_wait.parity.shared::cta.b64 P1, [%0], %1;\n@P1 bra DONE;\nadd.u32 n, n, 1;\nsetp.gt.u32 P1, n, %2;\n@P1 trap;\nbra LOOP;\nDONE:\n}"
               :: "r"(bar), "r"(parity), "n"(SPIN_LIMIT) : "memory");
}
__device__ __forceinline__ void mbar_spin(uint32_t bar, uint32_t parity) {
  asm volatile("{\n.reg .pred P1;\nLOOP:\nmbarrier.try_wait.parity.shared::cta.b64 P1, [%0], %1;\n@!P1 bra LOOP;\n}" :: "r"(bar), "r"(parity) : "memory");
}
__device__ __forceinline__ void mbar_wait_sleep(uint32_t bar, uint32_t parity, uint32_t ns) {
  uint32_t n = 0;
  while (!mbar_test(bar, parity)) { trap_if(++n > SPIN_LIMIT * 4); __nanosleep(ns); }
}
__device__ __forceinline__ void tma_load_2d(uint32_t dst, const CUtensorMap* tm, int c0, int c1, uint32_t bar) {
  asm volatile("cp.async.bulk.tensor.2d.shared::cluster.global.mbarrier::complete_tx::bytes [%0], [%1, {%3, %4}], [%2];"
    :: "r"(dst), "l"(tm), "r"(bar), "r"(c0), "r"(c1) : "memory");
}
__device__ __forceinline__ void tma_load_2d_mc(uint32_t dst, const CUtensorMap* tm, int c0, int c1, uint32_t bar) {
  asm volatile("cp.async.bulk.tensor.2d.shared::cluster.global.mbarrier::complete_tx::bytes.multicast::cluster [%0], [%1, {%3, %4}], [%2], %5;"
    :: "r"(dst), "l"(tm), "r"(bar), "r"(c0), "r"(c1), "h"((uint16_t)3) : "memory");
}
__device__ __forceinline__ void tma_prefetch_2d(const CUtensorMap* tm, int c0, int c1) {
  asm volatile("cp.async.bulk.prefetch.tensor.2d.L2.global [%0, {%1, %2}];" :: "l"(tm), "r"(c0), "r"(c1) : "memory");
}
__device__ __forceinline__ void tma_prefetch_3d(const CUtensorMap* tm, int c1, int c2) {
  asm volatile("cp.async.bulk.prefetch.tensor.3d.L2.global [%0, {%1, %2, %3}];" :: "l"(tm), "r"(0), "r"(c1), "r"(c2) : "memory");
}
__device__ __forceinline__ void tma_load_3d_mc(uint32_t dst, const CUtensorMap* tm, int c1, int c2, uint32_t bar) {
  asm volatile("cp.async.bulk.tensor.3d.shared::cluster.global.mbarrier::complete_tx::bytes.multicast::cluster [%0], [%1, {%3, %4, %5}], [%2], %6;"
    :: "r"(dst), "l"(tm), "r"(bar), "r"(0), "r"(c1), "r"(c2), "h"((uint16_t)3) : "memory");
}
__device__ __forceinline__ void tma_store_2d(const CUtensorMap* tm, uint32_t src, int c0, int c1) {
  asm volatile("cp.async.bulk.tensor.2d.global.shared::cta.bulk_group [%0, {%2, %3}], [%1];" :: "l"(tm), "r"(src), "r"(c0), "r"(c1) : "memory");
}
__device__ __forceinline__ void bulk_commit() { asm volatile("cp.async.bulk.commit_group;" ::: "memory"); }
template <int N> __device__ __forceinline__ void bulk_wait_read() { asm volatile("cp.async.bulk.wait_group.read %0;" :: "n"(N) : "memory"); }
template <int N> __device__ __forceinline__ void bulk_wait() { asm volatile("cp.async.bulk.wait_group %0;" :: "n"(N) : "memory"); }
__device__ __forceinline__ void fence_async_smem() { asm volatile("fence.proxy.async.shared::cta;" ::: "memory"); }
__device__ __forceinline__ void fence_async_global() { asm volatile("fence.proxy.async.global;" ::: "memory"); }
__device__ __forceinline__ void wgmma_fence() { asm volatile("wgmma.fence.sync.aligned;" ::: "memory"); }
__device__ __forceinline__ void wgmma_commit() { asm volatile("wgmma.commit_group.sync.aligned;" ::: "memory"); }
template <int N> __device__ __forceinline__ void wgmma_wait() { asm volatile("wgmma.wait_group.sync.aligned %0;" :: "n"(N) : "memory"); }
__device__ __forceinline__ uint64_t make_desc(uint32_t addr, uint32_t lbo, uint32_t sbo) {
  return (uint64_t)((addr & 0x3FFFF) >> 4) | ((uint64_t)(lbo >> 4) << 16) | ((uint64_t)(sbo >> 4) << 32) | (1ull << 62);
}
template <int N> __device__ __forceinline__ void fence_regs(float (&d)[N]) {
#pragma unroll
  for (int i = 0; i < N; i++) asm volatile("" : "+f"(d[i]) :: "memory");
}
template <int N> __device__ __forceinline__ void fence_regs(uint32_t (&d)[N]) {
#pragma unroll
  for (int i = 0; i < N; i++) asm volatile("" : "+r"(d[i]) :: "memory");
}
__device__ __forceinline__ void named_sync(int id) { asm volatile("bar.sync %0, 256;" :: "r"(id) : "memory"); }
__device__ __forceinline__ void pp_sync(bool w) { asm volatile("{\n.reg .pred p;\nsetp.ne.u32 p, %0, 0;\n@p bar.sync 2, 256;\n@!p bar.sync 1, 256;\n}" :: "r"((uint32_t)w) : "memory"); }
__device__ __forceinline__ void pp_arrive(bool w) { asm volatile("{\n.reg .pred p;\nsetp.ne.u32 p, %0, 0;\n@p bar.arrive 1, 256;\n@!p bar.arrive 2, 256;\n}" :: "r"((uint32_t)w) : "memory"); }
__device__ __forceinline__ bool wg_any(bool w, bool v) {
  uint32_t r;
  asm volatile("{\n.reg .pred p, q;\nsetp.ne.u32 p, %1, 0;\nbar.red.or.pred q, %2, 128, p;\nselp.u32 %0, 1, 0, q;\n}" : "=r"(r) : "r"((uint32_t)v), "r"(w ? 4 : 3) : "memory");
  return __any_sync(0xffffffffu, r);
}
__device__ __forceinline__ int fresh_warp() { uint32_t t; asm volatile("mov.u32 %0, %%tid.x;" : "=r"(t)); return __shfl_sync(0xffffffffu, (int)(t >> 5) - 4, 0); }
__device__ __forceinline__ void cluster_sync_relaxed() { asm volatile("barrier.cluster.arrive.relaxed.aligned;\nbarrier.cluster.wait.aligned;" ::: "memory"); }
__device__ __forceinline__ unsigned ld_acquire(const unsigned* p) { unsigned v; asm volatile("ld.acquire.gpu.global.u32 %0, [%1];" : "=r"(v) : "l"(p) : "memory"); return v; }
__device__ __forceinline__ void red_release(unsigned* p, unsigned v) { asm volatile("red.release.gpu.global.add.u32 [%0], %1;" :: "l"(p), "r"(v) : "memory"); }
__device__ __forceinline__ void flag_wait(const unsigned* p, unsigned target) {
  uint32_t n = 0;
  while (ld_acquire(p) < target) { trap_if(++n > SPIN_LIMIT); __nanosleep(20); }
}
__device__ __forceinline__ void st_tagged(uint2* p, float a, float b, uint32_t tag) {
  asm volatile("{\n.reg .b64 x;\nmov.b64 x, {%1, %2};\nst.relaxed.gpu.global.b64 [%0], x;\n}" :: "l"(p),
               "r"((__float_as_uint(a) & ~63u) | (tag & 63u)), "r"((__float_as_uint(b) & ~63u) | (tag >> 6)) : "memory");
}
__device__ __forceinline__ uint4 ld_tagged2(const uint2* p) {
  uint4 v;
  asm volatile("{\n.reg .b64 x, y;\nld.relaxed.gpu.global.v2.b64 {x, y}, [%4];\nmov.b64 {%0, %1}, x;\nmov.b64 {%2, %3}, y;\n}" : "=r"(v.x), "=r"(v.y), "=r"(v.z), "=r"(v.w) : "l"(p) : "memory");
  return v;
}
__device__ __forceinline__ bool tag_ok(uint32_t a, uint32_t b, uint32_t tag) { return ((a & 63u) | ((b & 63u) << 6)) == tag; }
__device__ __forceinline__ float untag(uint32_t v) { return __uint_as_float(v & ~63u); }
__device__ __forceinline__ uint32_t pack_bf16(float lo, float hi) { uint32_t r; asm("cvt.rn.bf16x2.f32 %0, %1, %2;" : "=r"(r) : "f"(hi), "f"(lo)); return r; }
__device__ __forceinline__ uint32_t bf2_fma(uint32_t a, uint32_t b, uint32_t c) { uint32_t r; asm("fma.rn.bf16x2 %0, %1, %2, %3;" : "=r"(r) : "r"(a), "r"(b), "r"(c)); return r; }
__device__ __forceinline__ uint32_t bf2_mul(uint32_t a, uint32_t b) { uint32_t r; asm("mul.rn.bf16x2 %0, %1, %2;" : "=r"(r) : "r"(a), "r"(b)); return r; }
__device__ __forceinline__ uint32_t bf2_add(uint32_t a, uint32_t b) { uint32_t r; asm("add.rn.bf16x2 %0, %1, %2;" : "=r"(r) : "r"(a), "r"(b)); return r; }
constexpr uint32_t BF2_HALF = 0x3f003f00u;
__device__ __forceinline__ float bf_lo(uint32_t v) { return __uint_as_float(v << 16); }
__device__ __forceinline__ float bf_hi(uint32_t v) { return __uint_as_float(v & 0xffff0000u); }
__device__ __forceinline__ float ex2(float x) { float y; asm("ex2.approx.ftz.f32 %0, %1;" : "=f"(y) : "f"(x)); return y; }
__device__ __forceinline__ float tanh_fast(float x) { float y; asm("tanh.approx.f32 %0, %1;" : "=f"(y) : "f"(x)); return y; }
__device__ __forceinline__ void stmatrix_x4(uint32_t addr, uint32_t a, uint32_t b, uint32_t c, uint32_t d) {
  asm volatile("stmatrix.sync.aligned.m8n8.x4.shared.b16 [%0], {%1, %2, %3, %4};" :: "r"(addr), "r"(a), "r"(b), "r"(c), "r"(d) : "memory");
}
__device__ __forceinline__ void ldmatrix_x4(uint32_t addr, uint32_t& a, uint32_t& b, uint32_t& c, uint32_t& d) {
  asm volatile("ldmatrix.sync.aligned.m8n8.x4.shared.b16 {%0, %1, %2, %3}, [%4];" : "=r"(a), "=r"(b), "=r"(c), "=r"(d) : "r"(addr) : "memory");
}
__device__ __forceinline__ uint32_t lane_id() { uint32_t l; asm volatile("mov.u32 %0, %%laneid;" : "=r"(l)); return l; }
__device__ __forceinline__ bool elect_one() {
  uint32_t r;
  asm volatile("{\n.reg .pred P;\nelect.sync _|P, 0xffffffff;\nselp.u32 %0, 1, 0, P;\n}" : "=r"(r));
  return r;
}

__device__ __forceinline__ void wgmma_m64n128k16_ss_tb0(float (&d)[64], uint64_t da, uint64_t db, int scale_d) {
  asm volatile("{\n.reg .pred p;\nsetp.ne.b32 p, %66, 0;\n"
    "wgmma.mma_async.sync.aligned.m64n128k16.f32.bf16.bf16 "
    "{%0, %1, %2, %3, %4, %5, %6, %7, %8, %9, %10, %11, %12, %13, %14, %15, %16, %17, %18, %19, %20, %21, %22, %23, %24, %25, %26, %27, %28, %29, %30, %31, %32, %33, %34, %35, %36, %37, %38, %39, %40, %41, %42, %43, %44, %45, %46, %47, %48, %49, %50, %51, %52, %53, %54, %55, %56, %57, %58, %59, %60, %61, %62, %63}, "
    "%64, %65, p, 1, 1, 0, 0;\n}\n"
    : "+f"(d[0]), "+f"(d[1]), "+f"(d[2]), "+f"(d[3]), "+f"(d[4]), "+f"(d[5]), "+f"(d[6]), "+f"(d[7]), "+f"(d[8]), "+f"(d[9]), "+f"(d[10]), "+f"(d[11]), "+f"(d[12]), "+f"(d[13]), "+f"(d[14]), "+f"(d[15]), "+f"(d[16]), "+f"(d[17]), "+f"(d[18]), "+f"(d[19]), "+f"(d[20]), "+f"(d[21]), "+f"(d[22]), "+f"(d[23]), "+f"(d[24]), "+f"(d[25]), "+f"(d[26]), "+f"(d[27]), "+f"(d[28]), "+f"(d[29]), "+f"(d[30]), "+f"(d[31]), "+f"(d[32]), "+f"(d[33]), "+f"(d[34]), "+f"(d[35]), "+f"(d[36]), "+f"(d[37]), "+f"(d[38]), "+f"(d[39]), "+f"(d[40]), "+f"(d[41]), "+f"(d[42]), "+f"(d[43]), "+f"(d[44]), "+f"(d[45]), "+f"(d[46]), "+f"(d[47]), "+f"(d[48]), "+f"(d[49]), "+f"(d[50]), "+f"(d[51]), "+f"(d[52]), "+f"(d[53]), "+f"(d[54]), "+f"(d[55]), "+f"(d[56]), "+f"(d[57]), "+f"(d[58]), "+f"(d[59]), "+f"(d[60]), "+f"(d[61]), "+f"(d[62]), "+f"(d[63])
    : "l"(da), "l"(db), "r"(scale_d));
}
__device__ __forceinline__ void wgmma_m64n256k16_ss_tb1(float (&d)[128], uint64_t da, uint64_t db, int scale_d) {
  asm volatile("{\n.reg .pred p;\nsetp.ne.b32 p, %130, 0;\n"
    "wgmma.mma_async.sync.aligned.m64n256k16.f32.bf16.bf16 "
    "{%0, %1, %2, %3, %4, %5, %6, %7, %8, %9, %10, %11, %12, %13, %14, %15, %16, %17, %18, %19, %20, %21, %22, %23, %24, %25, %26, %27, %28, %29, %30, %31, %32, %33, %34, %35, %36, %37, %38, %39, %40, %41, %42, %43, %44, %45, %46, %47, %48, %49, %50, %51, %52, %53, %54, %55, %56, %57, %58, %59, %60, %61, %62, %63, %64, %65, %66, %67, %68, %69, %70, %71, %72, %73, %74, %75, %76, %77, %78, %79, %80, %81, %82, %83, %84, %85, %86, %87, %88, %89, %90, %91, %92, %93, %94, %95, %96, %97, %98, %99, %100, %101, %102, %103, %104, %105, %106, %107, %108, %109, %110, %111, %112, %113, %114, %115, %116, %117, %118, %119, %120, %121, %122, %123, %124, %125, %126, %127}, "
    "%128, %129, p, 1, 1, 0, 1;\n}\n"
    : "+f"(d[0]), "+f"(d[1]), "+f"(d[2]), "+f"(d[3]), "+f"(d[4]), "+f"(d[5]), "+f"(d[6]), "+f"(d[7]), "+f"(d[8]), "+f"(d[9]), "+f"(d[10]), "+f"(d[11]), "+f"(d[12]), "+f"(d[13]), "+f"(d[14]), "+f"(d[15]), "+f"(d[16]), "+f"(d[17]), "+f"(d[18]), "+f"(d[19]), "+f"(d[20]), "+f"(d[21]), "+f"(d[22]), "+f"(d[23]), "+f"(d[24]), "+f"(d[25]), "+f"(d[26]), "+f"(d[27]), "+f"(d[28]), "+f"(d[29]), "+f"(d[30]), "+f"(d[31]), "+f"(d[32]), "+f"(d[33]), "+f"(d[34]), "+f"(d[35]), "+f"(d[36]), "+f"(d[37]), "+f"(d[38]), "+f"(d[39]), "+f"(d[40]), "+f"(d[41]), "+f"(d[42]), "+f"(d[43]), "+f"(d[44]), "+f"(d[45]), "+f"(d[46]), "+f"(d[47]), "+f"(d[48]), "+f"(d[49]), "+f"(d[50]), "+f"(d[51]), "+f"(d[52]), "+f"(d[53]), "+f"(d[54]), "+f"(d[55]), "+f"(d[56]), "+f"(d[57]), "+f"(d[58]), "+f"(d[59]), "+f"(d[60]), "+f"(d[61]), "+f"(d[62]), "+f"(d[63]), "+f"(d[64]), "+f"(d[65]), "+f"(d[66]), "+f"(d[67]), "+f"(d[68]), "+f"(d[69]), "+f"(d[70]), "+f"(d[71]), "+f"(d[72]), "+f"(d[73]), "+f"(d[74]), "+f"(d[75]), "+f"(d[76]), "+f"(d[77]), "+f"(d[78]), "+f"(d[79]), "+f"(d[80]), "+f"(d[81]), "+f"(d[82]), "+f"(d[83]), "+f"(d[84]), "+f"(d[85]), "+f"(d[86]), "+f"(d[87]), "+f"(d[88]), "+f"(d[89]), "+f"(d[90]), "+f"(d[91]), "+f"(d[92]), "+f"(d[93]), "+f"(d[94]), "+f"(d[95]), "+f"(d[96]), "+f"(d[97]), "+f"(d[98]), "+f"(d[99]), "+f"(d[100]), "+f"(d[101]), "+f"(d[102]), "+f"(d[103]), "+f"(d[104]), "+f"(d[105]), "+f"(d[106]), "+f"(d[107]), "+f"(d[108]), "+f"(d[109]), "+f"(d[110]), "+f"(d[111]), "+f"(d[112]), "+f"(d[113]), "+f"(d[114]), "+f"(d[115]), "+f"(d[116]), "+f"(d[117]), "+f"(d[118]), "+f"(d[119]), "+f"(d[120]), "+f"(d[121]), "+f"(d[122]), "+f"(d[123]), "+f"(d[124]), "+f"(d[125]), "+f"(d[126]), "+f"(d[127])
    : "l"(da), "l"(db), "r"(scale_d));
}
__device__ __forceinline__ void wgmma_m64n128k16_rs_tb1(float (&d)[64], uint32_t a0, uint32_t a1, uint32_t a2, uint32_t a3, uint64_t db, int scale_d) {
  asm volatile("{\n.reg .pred p;\nsetp.ne.b32 p, %69, 0;\n"
    "wgmma.mma_async.sync.aligned.m64n128k16.f32.bf16.bf16 "
    "{%0, %1, %2, %3, %4, %5, %6, %7, %8, %9, %10, %11, %12, %13, %14, %15, %16, %17, %18, %19, %20, %21, %22, %23, %24, %25, %26, %27, %28, %29, %30, %31, %32, %33, %34, %35, %36, %37, %38, %39, %40, %41, %42, %43, %44, %45, %46, %47, %48, %49, %50, %51, %52, %53, %54, %55, %56, %57, %58, %59, %60, %61, %62, %63}, "
    "{%64, %65, %66, %67}, %68, p, 1, 1, 1;\n}\n"
    : "+f"(d[0]), "+f"(d[1]), "+f"(d[2]), "+f"(d[3]), "+f"(d[4]), "+f"(d[5]), "+f"(d[6]), "+f"(d[7]), "+f"(d[8]), "+f"(d[9]), "+f"(d[10]), "+f"(d[11]), "+f"(d[12]), "+f"(d[13]), "+f"(d[14]), "+f"(d[15]), "+f"(d[16]), "+f"(d[17]), "+f"(d[18]), "+f"(d[19]), "+f"(d[20]), "+f"(d[21]), "+f"(d[22]), "+f"(d[23]), "+f"(d[24]), "+f"(d[25]), "+f"(d[26]), "+f"(d[27]), "+f"(d[28]), "+f"(d[29]), "+f"(d[30]), "+f"(d[31]), "+f"(d[32]), "+f"(d[33]), "+f"(d[34]), "+f"(d[35]), "+f"(d[36]), "+f"(d[37]), "+f"(d[38]), "+f"(d[39]), "+f"(d[40]), "+f"(d[41]), "+f"(d[42]), "+f"(d[43]), "+f"(d[44]), "+f"(d[45]), "+f"(d[46]), "+f"(d[47]), "+f"(d[48]), "+f"(d[49]), "+f"(d[50]), "+f"(d[51]), "+f"(d[52]), "+f"(d[53]), "+f"(d[54]), "+f"(d[55]), "+f"(d[56]), "+f"(d[57]), "+f"(d[58]), "+f"(d[59]), "+f"(d[60]), "+f"(d[61]), "+f"(d[62]), "+f"(d[63])
    : "r"(a0), "r"(a1), "r"(a2), "r"(a3), "l"(db), "r"(scale_d));
}
__device__ __forceinline__ void wgmma_m64n128k16_ss_tb1(float (&d)[64], uint64_t da, uint64_t db, int scale_d) {
  asm volatile("{\n.reg .pred p;\nsetp.ne.b32 p, %66, 0;\n"
    "wgmma.mma_async.sync.aligned.m64n128k16.f32.bf16.bf16 "
    "{%0, %1, %2, %3, %4, %5, %6, %7, %8, %9, %10, %11, %12, %13, %14, %15, %16, %17, %18, %19, %20, %21, %22, %23, %24, %25, %26, %27, %28, %29, %30, %31, %32, %33, %34, %35, %36, %37, %38, %39, %40, %41, %42, %43, %44, %45, %46, %47, %48, %49, %50, %51, %52, %53, %54, %55, %56, %57, %58, %59, %60, %61, %62, %63}, "
    "%64, %65, p, 1, 1, 0, 1;\n}\n"
    : "+f"(d[0]), "+f"(d[1]), "+f"(d[2]), "+f"(d[3]), "+f"(d[4]), "+f"(d[5]), "+f"(d[6]), "+f"(d[7]), "+f"(d[8]), "+f"(d[9]), "+f"(d[10]), "+f"(d[11]), "+f"(d[12]), "+f"(d[13]), "+f"(d[14]), "+f"(d[15]), "+f"(d[16]), "+f"(d[17]), "+f"(d[18]), "+f"(d[19]), "+f"(d[20]), "+f"(d[21]), "+f"(d[22]), "+f"(d[23]), "+f"(d[24]), "+f"(d[25]), "+f"(d[26]), "+f"(d[27]), "+f"(d[28]), "+f"(d[29]), "+f"(d[30]), "+f"(d[31]), "+f"(d[32]), "+f"(d[33]), "+f"(d[34]), "+f"(d[35]), "+f"(d[36]), "+f"(d[37]), "+f"(d[38]), "+f"(d[39]), "+f"(d[40]), "+f"(d[41]), "+f"(d[42]), "+f"(d[43]), "+f"(d[44]), "+f"(d[45]), "+f"(d[46]), "+f"(d[47]), "+f"(d[48]), "+f"(d[49]), "+f"(d[50]), "+f"(d[51]), "+f"(d[52]), "+f"(d[53]), "+f"(d[54]), "+f"(d[55]), "+f"(d[56]), "+f"(d[57]), "+f"(d[58]), "+f"(d[59]), "+f"(d[60]), "+f"(d[61]), "+f"(d[62]), "+f"(d[63])
    : "l"(da), "l"(db), "r"(scale_d));
}


enum { TM_XN, TM_WSP, TM_U, TM_O, TM_Q, TM_X, TM_SA, TM_G, TM_K, TM_V, TM_WO64,
       TM_WIN, TM_WQ, TM_Z2, TM_WOUT, TM_WO, TS_Q, TS_O, TS_Z2, TS_U, TS_SA, TS_G, TS_OUT, TM_COUNT };
enum { T_Z2 = 0, T_Q = 1, T_U = 2, T_ATT = 3, T_SA = 4, T_FIN = 5, T_END = 7 };
constexpr int NCLUSTER = 66, MAXI = 14;
struct alignas(64) Params {
  const bf16* x;
  const bf16* b_sp;
  CUtensorMap tm[TM_COUNT];
  uint16_t items[NCLUSTER][MAXI];
};

constexpr uint32_t G_STAGE = 49152, G_A = 16384, KV_SLOT = 32768;
constexpr uint32_t OFF_Q1 = 163840, OFF_Q0 = 196608, OFF_BAR = 229376, OFF_LN = OFF_BAR + 256, SMEM_BYTES = OFF_LN + 1024;
constexpr uint32_t B_GF = 0, B_GE = 32, B_KF = 64, B_KE = 104, B_QF = 144, B_QE = 160, B_XF = 176, B_XR = 184, B_STG = 192, B_FREE = 200;
constexpr uint32_t B_GO = 208, B_LN = 216, B_PUB = 248, B_TAG = 224, B_RDY = 228, B_PROG = 232;
constexpr int SA_HEADS = 18;
constexpr int SW_NS = 40;
constexpr int SW_ATT = 800;
constexpr int ST_ROWS = 16;
constexpr int ST_FLY = 2;
constexpr int KV_PF = 4;
constexpr int FIN_PREP = 8;
constexpr int OWN_OFF = 8;
constexpr int ACT_REP = 33;
constexpr int Q_DELAY = 4;
constexpr int Q_GAP = 4;
constexpr int QW = 2;
constexpr int Z_DELAY = 4;
constexpr int Z_GAP = 3;
constexpr int LN_SLEEP = 300;
constexpr int U_PACE = 200;
constexpr int Q_AT = 19;
constexpr int OUT_PF = 8;
constexpr int SA_STEPS = 2 * SA_HEADS;
static_assert(ST_ROWS == 16, "the per-warp stores of the last o tile use the same tensor map");
static_assert(SA_STEPS >= 36, "activation, gate store and hold-back have to fit into the second SA segment");
constexpr uint32_t FIN_SLOT0 = (0x0320u >> (4 * ((29 + SA_STEPS) & 3))) & 15;
constexpr float SM_C = 0.08838834764831845f * 1.4426950408889634f;
constexpr float GELU_A = 0.7978845608028654f, GELU_B = 0.7978845608028654f * 0.044715f;
constexpr float SM_LO = 1e-5f, SM_HI = 1e7f;
constexpr float SM_THR = 1024.f;


extern __shared__ __align__(1024) uint8_t smem_raw[];
__device__ __forceinline__ uint32_t smem_base() { return smem_u32(smem_raw); }

struct Ring { uint32_t s, ph; };
template <int N> __device__ __forceinline__ void ring_adv(Ring& r) { if (++r.s == N) { r.s = 0; r.ph ^= 1; } }

__device__ __forceinline__ int get_item(const Params& p, int i) {
  uint32_t b; asm volatile("mov.u32 %0, %%ctaid.x;" : "=r"(b));
  return p.items[b >> 1][i];
}
struct Cons {
  uint32_t sb;
  int warp;
  Ring g;
  uint32_t rot;
  uint32_t fph;
};

__device__ __forceinline__ void stage_acquire(const Cons& c) { mbar_spin(c.sb + OFF_BAR + B_FREE, c.fph); }
__device__ __forceinline__ void stage_commit(Cons& c) {
  __syncwarp();
  if (lane_id() == 0) mbar_arrive(c.sb + OFF_BAR + B_STG);
  c.fph ^= 1;
}

__device__ __forceinline__ void release_slot(const Cons& c, uint32_t bar) {
  if (lane_id() == 0 && (c.warp & 3) < 2) mbar_arrive_cta(bar, c.warp & 1);
}
constexpr uint64_t DESC_HI = (uint64_t)0x40000040u << 32;

template <bool FIRST> __device__ __forceinline__ void gemm_step(float (&acc)[128], Cons& c) {
  mbar_spin(c.sb + OFF_BAR + B_GF + 8 * c.g.s, c.g.ph);
  const uint32_t st = ((c.sb & 0x3FFFF) >> 4) + ((c.g.s + c.rot) & 3) * (G_STAGE >> 4);
  const uint32_t da = st + (c.warp >> 2) * 512 + (1u << 16), db = st + (G_A >> 4) + ((8192u >> 4) << 16);
  wgmma_fence();
#pragma unroll
  for (int kk = 0; kk < 4; kk++) wgmma_m64n256k16_ss_tb1(acc, DESC_HI | (da + kk * 2), DESC_HI | (db + kk * 128), !(FIRST && kk == 0));
  wgmma_commit();
}

template <int N> __device__ __forceinline__ void stage_chunks(uint32_t buf, uint32_t stride, const uint32_t* pk) {
  const uint32_t ln = lane_id();
  const uint32_t a = buf + ((ln & 15) << 7);
  const uint32_t x = ln & 7, hi = ln >> 4;
#pragma unroll
  for (int i = 0; i < 4 * N; i++) stmatrix_x4(a + (i >> 2) * stride + (((2 * (i & 3) + hi) ^ x) << 4), pk[4 * i], pk[4 * i + 1], pk[4 * i + 2], pk[4 * i + 3]);
}

__device__ __forceinline__ float act2_fn(float x, float a, float b) {
  return fmaf(x, tanh_fast(x * fmaf(x * x, b, a)), x);
}
__device__ __forceinline__ float quad_sum(float v) { v += __shfl_xor_sync(0xffffffffu, v, 1); v += __shfl_xor_sync(0xffffffffu, v, 2); return v; }
__device__ __forceinline__ float quad_max(float v) { v = fmaxf(v, __shfl_xor_sync(0xffffffffu, v, 1)); v = fmaxf(v, __shfl_xor_sync(0xffffffffu, v, 2)); return v; }

__device__ __forceinline__ uint32_t load_tag(const Cons& c) { uint32_t t; asm volatile("ld.volatile.shared.u32 %0, [%1];" : "=r"(t) : "r"(c.sb + OFF_BAR + B_TAG)); return t; }

struct Shadow {
  int act;
  int store;
};
__device__ __forceinline__ void shift16(uint32_t (&h)[64], int i, uint32_t v) {
  asm volatile("mov.b32 %0, %1;\nmov.b32 %1, %2;\nmov.b32 %2, %3;\nmov.b32 %3, %4;" : "=&r"(h[i]), "+r"(h[i + 16]), "+r"(h[i + 32]), "+r"(h[i + 48]) : "r"(v));
}

template <int O>
__device__ __forceinline__ void act_block(uint32_t (&held)[64], float ca, float cb, bool first, float& u0, float& u1, float& s0, float& s1, float& q0, float& q1) {
#pragma unroll
  for (int i = O; i < O + 4; i += 2) {
    const float a0 = act2_fn(bf_lo(held[i]), ca, cb), a1 = act2_fn(bf_hi(held[i]), ca, cb);
    const float b0 = act2_fn(bf_lo(held[i + 1]), ca, cb), b1 = act2_fn(bf_hi(held[i + 1]), ca, cb);
    if (i == 0 && first) { u0 = a0; u1 = b0; }
    float d;
    d = a0 - u0; s0 += d; q0 = fmaf(d, d, q0); d = a1 - u0; s0 += d; q0 = fmaf(d, d, q0);
    d = b0 - u1; s1 += d; q1 = fmaf(d, d, q1); d = b1 - u1; s1 += d; q1 = fmaf(d, d, q1);
    shift16(held, i, pack_bf16(a0, a1)); shift16(held, i + 1, pack_bf16(b0, b1));
  }
}

template <int O> __device__ __forceinline__ void stage_half(Cons& c, uint32_t (&held)[64], int mode) {
  if (mode == 2) {
    uint32_t a0, a1, r0, r1;
    const uint32_t la = c.sb + OFF_LN + (c.warp * 16 + (lane_id() >> 2)) * 8;
    mbar_spin(c.sb + OFF_BAR + B_LN, 0);
    asm volatile("ld.shared.v2.b32 {%0, %1}, [%2];" : "=r"(r0), "=r"(a0) : "r"(la));
    asm volatile("ld.shared.v2.b32 {%0, %1}, [%2];" : "=r"(r1), "=r"(a1) : "r"(la + 64));
#pragma unroll
    for (int i = O; i < O + 32; i += 2) { held[i] = bf2_mul(bf2_add(held[i], a0), r0); held[i + 1] = bf2_mul(bf2_add(held[i + 1], a1), r1); }
  }
  if (O == 0 && mode == 3) {
#pragma unroll
    for (int i = 0; i < 64; i++) held[i] = bf2_mul(held[i], BF2_HALF);
  }
  stage_acquire(c);
  stage_chunks<2>(c.sb + OFF_Q0 + c.warp * 2048, 16384, held + O);
  stage_commit(c);
}

__device__ __forceinline__ void gemm_seg(float (&acc)[128], uint32_t (&held)[64], Cons& c, const Params& p, Shadow& sh, int nsteps) {
  const bool elected = lane_id() == 0 && (c.warp & 3) < 2;
  uint32_t rel;
  asm("mapa.shared::cluster.u32 %0, %1, %2;" : "=r"(rel) : "r"(c.sb + OFF_BAR + B_GE), "r"((uint32_t)(c.warp & 1)));
  gemm_step<true>(acc, c);
  uint32_t prev = c.g.s;
  ring_adv<4>(c.g);
  int k = 1;
#define G_STEP()                                                                                                       \
  { gemm_step<false>(acc, c);                                                                                          \
    wgmma_wait<1>();                                                                                                   \
    if (elected) asm volatile("mbarrier.arrive.shared::cluster.b64 _, [%0];" :: "r"(rel + 8 * prev) : "memory");       \
    prev = c.g.s; ring_adv<4>(c.g);                                                                                    \
    k++; }
  if (sh.act != 0) {
    float u0 = 0.f, u1 = 0.f, s0 = 0.f, s1 = 0.f, q0 = 0.f, q1 = 0.f;
    const float ca = sh.act == 3 ? 0.5f : GELU_A, cb = sh.act == 3 ? 0.f : GELU_B;
    const int rb = nsteps >= ACT_REP ? 2 : 1, ra = sh.act == 2 ? 0 : rb;
#define G_STEPS(N) { _Pragma("unroll 1") for (int r = 0; r < (N); r++) G_STEP() }
#pragma unroll 1
    for (int q = 0;; q++) {
      act_block<0>(held, ca, cb, q == 0, u0, u1, s0, s1, q0, q1);
      G_STEPS(ra)
      act_block<4>(held, ca, cb, false, u0, u1, s0, s1, q0, q1);
      G_STEPS(rb)
      act_block<8>(held, ca, cb, false, u0, u1, s0, s1, q0, q1);
      G_STEPS(ra)
      act_block<12>(held, ca, cb, false, u0, u1, s0, s1, q0, q1);
      if (q == 3) break;
      G_STEPS(rb)
    }
    if (sh.act == 2) {
      const int zi = get_item(p, 0);
      const int ln = lane_id(), row0 = (((zi >> 5) & 31) * 2 + (blockIdx.x & 1)) * 128 + c.warp * 16 + (ln >> 2), ql = ln & 3;
      const float m0 = fmaf(s0, 1.f / 64, u0), m1 = fmaf(s1, 1.f / 64, u1);
      q0 -= s0 * s0 * (1.f / 64); q1 -= s1 * s1 * (1.f / 64);
      const float mu0 = quad_sum(m0) * 0.25f, mu1 = quad_sum(m1) * 0.25f;
      q0 = quad_sum(fmaf(64.f * (m0 - mu0), m0 - mu0, q0)); q1 = quad_sum(fmaf(64.f * (m1 - mu1), m1 - mu1, q1));
      if (ql < 2) st_tagged(&g_stats[((row0 >> 7) * 8 + (zi & 31)) * 128 + (row0 & 127) + 8 * ql], ql ? mu1 : mu0, ql ? q1 : q0, load_tag(c));
      if (ln == 0) mbar_arrive(c.sb + OFF_BAR + B_PUB);
    }
  }
  const int s0 = sh.store == 0 ? -9 : k + (sh.store == 2 ? Z_DELAY : (sh.store == 1 ? Q_DELAY : 1)), s1 = sh.store == 3 ? -9 : s0 + (sh.store == 1 ? Q_GAP : Z_GAP);
#pragma unroll 1
  while (k < nsteps) {
    G_STEP()
    if (k == s0) stage_half<0>(c, held, sh.store);
    else if (k == s1) stage_half<32>(c, held, sh.store);
    if (k == nsteps - 2 && c.warp >= 4) named_sync(6);
  }
  if (c.warp < 4) asm volatile("bar.arrive 6, 256;" ::: "memory");
  wgmma_wait<0>();
  fence_regs(acc);
  if (elected) asm volatile("mbarrier.arrive.shared::cluster.b64 _, [%0];" :: "r"(rel + 8 * prev) : "memory");
  sh.store = sh.act = 0;
}

template <bool SUB> __device__ __forceinline__ void softmax_exp(const float (&S)[64], uint32_t (&P)[32], float m0, float m1, float& s0, float& s1) {
  float a0 = 0.f, a1 = 0.f, b0 = 0.f, b1 = 0.f;
#pragma unroll
  for (int j = 0; j < 16; j++) {
    const float p0 = ex2(SUB ? S[4 * j] - m0 : S[4 * j]), p1 = ex2(SUB ? S[4 * j + 1] - m0 : S[4 * j + 1]);
    const float p2 = ex2(SUB ? S[4 * j + 2] - m1 : S[4 * j + 2]), p3 = ex2(SUB ? S[4 * j + 3] - m1 : S[4 * j + 3]);
    a0 += p0; b0 += p1; a1 += p2; b1 += p3;
    P[2 * j] = pack_bf16(p0, p1); P[2 * j + 1] = pack_bf16(p2, p3);
  }
  s0 = a0 + b0; s1 = a1 + b1;
}
__device__ __forceinline__ void row_max(const float (&S)[64], float& x0, float& x1) {
  float a0 = fmaxf(S[0], S[1]), a1 = fmaxf(S[2], S[3]);
#pragma unroll
  for (int j = 1; j < 16; j++) { a0 = fmaxf(a0, fmaxf(S[4 * j], S[4 * j + 1])); a1 = fmaxf(a1, fmaxf(S[4 * j + 2], S[4 * j + 3])); }
  x0 = quad_max(a0); x1 = quad_max(a1);
}

__device__ __forceinline__ void issue_qk(float (&S)[64], uint32_t da, uint32_t db) {
#pragma unroll
  for (int kk = 0; kk < 8; kk++) {
    const uint32_t o = (kk >> 2) * 1024 + (kk & 3) * 2;
    wgmma_m64n128k16_ss_tb0(S, DESC_HI | (da + o), DESC_HI | (db + o), kk > 0);
  }
}
__device__ __forceinline__ void issue_pv(float (&O)[64], const uint32_t (&P)[32], uint32_t db, int acc) {
#pragma unroll
  for (int kk = 0; kk < 8; kk++) wgmma_m64n128k16_rs_tb1(O, P[4 * kk], P[4 * kk + 1], P[4 * kk + 2], P[4 * kk + 3], DESC_HI | (db + kk * 128), (acc || kk > 0));
}

__device__ __forceinline__ void att_pack(const float (&O)[64], uint32_t (&pk)[32], float i0, float i1) {
#pragma unroll
  for (int j = 0; j < 16; j++) {
    pk[2 * j] = pack_bf16(O[4 * j] * i0, O[4 * j + 1] * i0);
    pk[2 * j + 1] = pack_bf16(O[4 * j + 2] * i1, O[4 * j + 3] * i1);
  }
}
__device__ __forceinline__ void att_stage(Cons& c, const uint32_t (&pk)[32], uint32_t qbuf) {
  stage_chunks<2>(c.sb + (qbuf ? OFF_Q1 : OFF_Q0) + c.warp * 2048, 16384, pk);
  stage_commit(c);
}

#define ATT_ISSUE(PIN, ACC, PV)                                                                                        \
  wgmma_fence();                                                                                                       \
  issue_qk(S, qd, kd); wgmma_commit();                                                                                 \
  if (g > 1) release_slot(c, vrel);                                                                                    \
  vready = mbar_test(vbar, vph) && g >= 3 && g != 16;                                                                  \
  if (PV) {                                                                                                            \
    mbar_spin(vbar, vph);                                                                                              \
    wgmma_fence();                                                                                                     \
    issue_pv(O, PIN, vd, ACC); wgmma_commit();                                                                         \
  } else {                                                                                                             \
    asm volatile("wgmma.commit_group.sync.aligned; // empty" ::: "memory");                                            \
  }                                                                                                                    \
  krel = kbar + (B_KE - B_KF); vrel = vbar + (B_KE - B_KF);                                                            \
  g++;                                                                                                                 \
  if (g < total) { kd = kd0 + kv.s * (KV_SLOT >> 4); kbar = bars + B_KF + 8 * kv.s; kph = kv.ph; ring_adv<5>(kv); }    \
  vd = vd0 + kv.s * (KV_SLOT >> 4); vbar = bars + B_KF + 8 * kv.s; vph = kv.ph; ring_adv<5>(kv);

#define ATT_WAIT_S()                                                                                                   \
  wgmma_wait<1>();                                                                                                     \
  fence_regs(S);                                                                                                       \
  release_slot(c, krel);                                                                                               \
  if (c.warp == 2) asm volatile("st.volatile.shared.u32 [%0], %1;" :: "r"(bars + B_PROG), "r"(g) : "memory");

#define ATT_SOFTMAX(POUT, FIRST)                                                                                       \
  fresh = false;                                                                                                       \
  _Pragma("unroll 1")                                                                                                  \
  while (true) {                                                                                                       \
    if (__builtin_expect(fresh, 0)) {                                                                                  \
      float x0, x1;                                                                                                    \
      row_max(S, x0, x1);                                                                                              \
      if (FIRST) m0 = m1 = -1e38f;                                                                                     \
      x0 = fmaxf(x0, m0); x1 = fmaxf(x1, m1);                                                                          \
      f0 = ex2(m0 - x0); f1 = ex2(m1 - x1);                                                                            \
      m0 = x0; m1 = x1; l0 *= f0; l1 *= f1;                                                                            \
      zero = false;                                                                                                    \
    }                                                                                                                  \
    if (zero) {                                                                                                        \
      softmax_exp<false>(S, POUT, m0, m1, s0, s1);                                                                     \
      kready = mbar_test_a(kbar, kph);                                                                                 \
      bad = !(s0 <= SM_HI && s1 <= SM_HI) || ((FIRST) && (s0 < SM_LO || s1 < SM_LO));                                  \
    } else {                                                                                                           \
      softmax_exp<true>(S, POUT, m0, m1, s0, s1);                                                                      \
      kready = mbar_test(kbar, kph);                                                                                   \
      bad = !(s0 <= SM_THR && s1 <= SM_THR);                                                                           \
    }                                                                                                                  \
    kready = kready && vready;                                                                                         \
    slow = fresh || __any_sync(0xffffffffu, bad || !kready);                                                           \
    if (__builtin_expect(!slow, 1)) break;                                                                             \
    if (fresh || !__any_sync(0xffffffffu, bad)) break;                                                                 \
    fresh = true;                                                                                                      \
  }                                                                                                                    \
  l0 += s0; l1 += s1;                                                                                                  \
  wgmma_wait<0>(); fence_regs(O);

#define ATT_RESCALE()                                                                                                  \
  { _Pragma("unroll")                                                                                                  \
    for (int i = 0; i < 16; i++) { O[4 * i] *= f0; O[4 * i + 1] *= f0; O[4 * i + 2] *= f1; O[4 * i + 3] *= f1; } }

__device__ __forceinline__ void att_stagger(const Cons& c, int g) {
  if (c.warp >= 4)
    asm volatile("{\n.reg .pred p;\n.reg .s32 v;\nLOOP:\nld.volatile.shared.s32 v, [%0];\nsetp.le.s32 p, v, %1;\n@p bra LOOP;\n}" :: "r"(c.sb + OFF_BAR + B_PROG), "r"(g) : "memory");
}

__device__ __forceinline__ void att_run(Cons& c, const Params& p, int it, int n) {
  const uint32_t bars = c.sb + OFF_BAR;
  float S[64], O[64];
  uint32_t P0[32], P1[32];
#pragma unroll
  for (int i = 0; i < 64; i++) O[i] = 0.f;
#pragma unroll
  for (int i = 0; i < 32; i++) P0[i] = P1[i] = 0u;
  fence_regs(O); fence_regs(P0); fence_regs(P1);
  float m0 = 0.f, m1 = 0.f, l0 = 0.f, l1 = 0.f, f0 = 1.f, f1 = 1.f, s0, s1, pl0 = 0.f, pl1 = 0.f;
  const int total = 16 * n;
  int g = 0;
  Ring kv = {1, 0};
  uint32_t kbar = bars + B_KF, kph = 0, vbar = bars + B_KF, vph = 0, krel, vrel = 0;
  const uint32_t kd0 = (uint32_t)make_desc(c.sb, 16, 1024), vd0 = (uint32_t)make_desc(c.sb, 16384, 1024);
  uint32_t qd = kd0 + ((OFF_Q0 + (c.warp >> 2) * 8192) >> 4), kd = kd0, vd = vd0;
  bool fresh, kready, vready, bad, slow, zero = true;
  mbar_spin(bars + B_QF, 0);
  mbar_spin(bars + B_KF, 0);
  att_stagger(c, 0);
#pragma unroll 1
  while (true) {
    ATT_ISSUE(P1, 1, g > 0)
    const bool first = ((g - 1) & 15) == 0;
    ATT_WAIT_S()
    ATT_SOFTMAX(P0, first)
    if (__builtin_expect(slow || first, 0)) {
      if (first) {
        if (g > 1) {
          att_pack(O, P1, pl0, pl1);
          att_stage(c, P1, ((g >> 4) & 1) ^ 1);
        }
      } else if (fresh) ATT_RESCALE();
      if (slow) {
        mbar_spin(kbar, kph);
        if (__any_sync(0xffffffffu, !kready)) att_stagger(c, g);
      }
    }
    ATT_ISSUE(P0, !first, true)
    ATT_WAIT_S()
    ATT_SOFTMAX(P1, false)
    if (__builtin_expect(slow || ((g + QW) & 15) <= QW, 0)) {
      if (fresh) ATT_RESCALE();
      if (g == total) break;
      if (slow) {
        mbar_spin(kbar, kph);
        if (__any_sync(0xffffffffu, !kready)) att_stagger(c, g);
      }
      if (((g + QW) & 15) == 0 && g + QW < total) { const int t = (g + QW) >> 4; mbar_spin(bars + B_QF + 8 * (t & 1), (t >> 1) & 1); }
      if ((g & 15) == 0) {
        qd = kd0 + ((((g & 16) ? OFF_Q1 : OFF_Q0) + (c.warp >> 2) * 8192) >> 4);
        pl0 = __fdividef(1.f, quad_sum(l0)); pl1 = __fdividef(1.f, quad_sum(l1));
        m0 = m1 = l0 = l1 = 0.f; zero = true;
      }
    }
  }
  release_slot(c, vrel);
  mbar_spin(vbar, vph);
  wgmma_fence();
  issue_pv(O, P1, vd, 1); wgmma_commit();
  pl0 = __fdividef(1.f, quad_sum(l0)); pl1 = __fdividef(1.f, quad_sum(l1));
  wgmma_wait<0>();
  fence_regs(O);
  release_slot(c, vbar + (B_KE - B_KF));
  att_pack(O, P0, pl0, pl1);
  if ((get_item(p, it + n) >> 12) == T_END) {
    const uint32_t buf = c.sb + (((n - 1) & 1) ? OFF_Q1 : OFF_Q0) + c.warp * 2048;
    stage_chunks<2>(buf, 16384, P0);
    fence_async_smem();
    __syncwarp();
    if (elect_one()) {
      const int im = get_item(p, it + n - 1), col = ((im >> 5) & 31) * 128, row = ((im & 7) * 2 + (blockIdx.x & 1)) * 128 + c.warp * 16;
      tma_store_2d(&p.tm[TS_O], buf, col, row); tma_store_2d(&p.tm[TS_O], buf + 16384, col + 64, row);
      bulk_commit();
      bulk_wait<0>();
      mbar_arrive(bars + B_STG);
    }
    __syncwarp();
  } else {
    att_stage(c, P0, (n - 1) & 1);
  }
}

__global__ void __cluster_dims__(2, 1, 1) __launch_bounds__(384, 1) fused_kernel(const __grid_constant__ Params p) {
  const uint32_t sb = smem_base();
  const uint32_t bars = sb + OFF_BAR;
  const int tid = threadIdx.x, lane = tid & 31;
  const int warp_id = __shfl_sync(0xffffffffu, tid >> 5, 0), wg = warp_id >> 2;
  const uint32_t rank = blockIdx.x & 1;
  const uint16_t* items = p.items[blockIdx.x >> 1];
  const int gw = blockIdx.x * 8 + warp_id - 4;
  uint4 xv[2][4];
  if (wg != 0 && gw < SEQ / 2) {
#pragma unroll
    for (int rr = 0; rr < 2; rr++)
#pragma unroll
      for (int i = 0; i < 4; i++) xv[rr][i] = __ldg(reinterpret_cast<const uint4*>(p.x + (size_t)(gw * 2 + rr) * DM) + i * 32 + lane);
  }
  if (warp_id == 1 && lane < TM_COUNT) asm volatile("prefetch.tensormap [%0];" :: "l"(&p.tm[lane]) : "memory");
  if (tid == 0) {
    for (int i = 0; i < 4; i++) { mbar_init(bars + B_GF + 8 * i, 1); mbar_init(bars + B_GE + 8 * i, 4); }
    for (int i = 0; i < 5; i++) { mbar_init(bars + B_KF + 8 * i, 1); mbar_init(bars + B_KE + 8 * i, 4); }
    for (int i = 0; i < 2; i++) { mbar_init(bars + B_QF + 8 * i, 1); mbar_init(bars + B_QE + 8 * i, 1); }
    mbar_init(bars + B_XF, 2); mbar_init(bars + B_XR, 2); mbar_init(bars + B_STG, 8); mbar_init(bars + B_FREE, 1); mbar_init(bars + B_GO, 1); mbar_init(bars + B_LN, 2); mbar_init(bars + B_PUB, 8);
    asm volatile("fence.mbarrier_init.release.cluster;" ::: "memory");
  }
  asm volatile("barrier.cluster.arrive.relaxed.aligned;" ::: "memory");

  if (wg == 0) {
    asm volatile("setmaxnreg.dec.sync.aligned.u32 40;");
    asm volatile("barrier.cluster.wait.acquire.aligned;" ::: "memory");
    if (warp_id >= 2 && (items[0] >> 12) == T_Z2) {
      const int r = (warp_id - 2) * 64 + 2 * lane;
      const uint2* ps = &g_stats[(((items[0] >> 5) & 31) * 2 + rank) * 1024 + r];
      uint32_t tag = 0, cnt = 0;
#pragma unroll 1
      for (;;) {
        uint4 t[7];
        bool ok = cnt > 0;
#pragma unroll
        for (int i = 0; i < 7; i++) {
          t[i] = make_uint4(0, 0, 0, 0);
          if (cnt > 0) t[i] = ld_tagged2(ps + i * 128);
        }
        float u0 = 0.f, u1 = 0.f, v0 = 0.f, v1 = 0.f;
#pragma unroll
        for (int i = 0; i < 7; i++) { ok = ok && tag_ok(t[i].x, t[i].y, tag) && tag_ok(t[i].z, t[i].w, tag); u0 += untag(t[i].x); u1 += untag(t[i].z); }
        u0 *= 1.f / 7; u1 *= 1.f / 7;
#pragma unroll
        for (int i = 0; i < 7; i++) {
          const float d0 = untag(t[i].x) - u0, d1 = untag(t[i].z) - u1;
          v0 += fmaf(256.f * d0, d0, untag(t[i].y)); v1 += fmaf(256.f * d1, d1, untag(t[i].w));
        }
        const float r0 = rsqrtf(fmaxf(v0, 0.f) * (1.f / FH) + 4e-5f), r1 = rsqrtf(fmaxf(v1, 0.f) * (1.f / FH) + 4e-5f);
        asm volatile("st.shared.v4.b32 [%0], {%1, %2, %3, %4};" :: "r"(sb + OFF_LN + r * 8), "r"(pack_bf16(r0, r0)), "r"(pack_bf16(-u0, -u0)),
                     "r"(pack_bf16(r1, r1)), "r"(pack_bf16(-u1, -u1)) : "memory");
        if (__all_sync(0xffffffffu, ok)) break;
        if (cnt == 0) {
          if (lane == 0) mbar_wait_sleep(bars + B_PUB, 0, 50);
          __syncwarp();
          asm volatile("ld.volatile.shared.u32 %0, [%1];" : "=r"(tag) : "r"(bars + B_TAG));
          __nanosleep(LN_SLEEP);
        }
        trap_if(++cnt > SPIN_LIMIT);
      }
      __syncwarp();
      if (lane == 0) mbar_arrive(bars + B_LN);
      __syncwarp();
    }
    if (warp_id == 0) {
      trap_if(sb & 1023);
      Ring g = {0, 1};
      int it = 0;
      uint32_t xph = 0;
      if (elect_one()) {
#pragma unroll 1
        for (;; it++) {
          const int item = items[it], type = item >> 12, b = item & 31, row = (((item >> 5) & 31) * 2 + rank) * 128;
          if (type >= T_ATT) break;
#pragma unroll 1
          for (int seg = 0; seg < (type == T_U ? 2 : 1); seg++) {
            const CUtensorMap* tA = &p.tm[seg ? TM_WSP : TM_XN];
            const CUtensorMap* tB = &p.tm[seg ? TM_Z2 : (type == T_Q ? TM_WQ : TM_WIN)];
            const int bchunk = b * 4 + (type == T_Z2 ? 28 : 0) + rank * 2;
            const unsigned* fl = seg ? &g_flags[F_Z2 + b * 32] : &g_flags[F_XN + (row >> 2)];
            const unsigned tgt = seg ? 16 : 128;
            int k = 0;
            if (it == 0 && seg == 0) {
              for (; k < 4; k++) {
                mbar_expect_tx(bars + B_GF + 8 * k, G_STAGE);
                tma_load_3d_mc(sb + k * G_STAGE + G_A + rank * 16384, tB, k * 64, bchunk, bars + B_GF + 8 * k);
              }
              g.ph ^= 1;
            }
            if (seg || type != T_U) { flag_wait(fl, tgt); fence_async_global(); }
            for (int x = 0; x < k; x++) tma_load_2d(sb + x * G_STAGE, tA, x * 64, row, bars + B_GF + 8 * x);
            if (it == 0) asm volatile("st.volatile.shared.v4.u32 [%0], {%1, %2, %2, %2};" :: "r"(bars + B_TAG), "r"(__ldcg(&g_epoch) % 4095u + 1), "r"(0) : "memory");
#pragma unroll 1
            for (; k < (seg ? 32 : 16); k++) {
              mbar_wait(bars + B_GE + 8 * g.s, g.ph);
              const uint32_t st = sb + g.s * G_STAGE, fb = bars + B_GF + 8 * g.s;
              mbar_expect_tx(fb, G_STAGE);
              tma_load_2d(st, tA, k * 64, row, fb);
              tma_load_3d_mc(st + G_A + rank * 16384, tB, k * 64, bchunk, fb);
              ring_adv<4>(g);
            }
          }
        }
      }
      { const int e = __ffs(__ballot_sync(0xffffffffu, elect_one())) - 1; it = __shfl_sync(0xffffffffu, it, e); g.ph = __shfl_sync(0xffffffffu, g.ph, e); }
      const int n = ((items[it] >> 10) & 3) + 3;
      Ring kv = {0, 1};
      if (elect_one()) {
        int prow = 0;
        {
          const int im = items[it];
          tma_prefetch_2d(&p.tm[(im & 1) ? TM_V : TM_K], rank * 64, ((im >> 5) & 31) * SEQ + ((im & 7) >> 1) * 128);
        }
#pragma unroll 1
        for (int x = 0; x <= 32 * n; x++) {
          const int gb = x >> 1, t = gb >> 4;
          const int hrow = ((items[it + t] >> 5) & 31) * SEQ;
          const bool isv = (x & 1) || x == 32 * n;
          if (x != 1) {
            if (x == 0 || x == 2) mbar_wait(bars + B_GE + 4 * x, g.ph);
            if (x == 4) { mbar_wait(bars + B_XF, xph); xph ^= 1; }
            mbar_wait(bars + B_KE + 8 * kv.s, kv.ph);
            mbar_expect_tx(bars + B_KF + 8 * kv.s, KV_SLOT);
            tma_load_2d_mc(sb + kv.s * KV_SLOT + rank * 16384, &p.tm[isv ? TM_V : TM_K], rank * 64, isv ? prow : hrow + (gb & 15) * 128, bars + B_KF + 8 * kv.s);
            ring_adv<5>(kv);
          }
          {
            const int gp = gb + KV_PF, ip = items[it + (gp >> 4)];
            if (gp < 16 * n && ((gp ^ ip) & (7 >> ((ip >> 3) & 3))) == 0) tma_prefetch_2d(&p.tm[(x & 1) ? TM_V : TM_K], rank * 64, ((ip >> 5) & 31) * SEQ + (gp & 15) * 128);
          }
          if (x == 32 * n - 8) mbar_arrive(bars + B_GO);
          if (x & 1) prow = hrow + (gb & 15) * 128;
          if ((x & 31) == Q_AT && t + 1 < n) {
            const int tq = t + 1;
            const int im = items[it + tq], h = (im >> 5) & 31, m = (im & 7) * 2 + rank;
            const uint32_t qb = tq & 1;
            flag_wait(&g_flags[F_Q + m * 16 + (h >> 1)], 1);
            fence_async_global();
            mbar_wait(bars + B_QE + 8 * qb, ((tq - 1) >> 1) & 1);
            const uint32_t dst = sb + (qb ? OFF_Q1 : OFF_Q0), fb = bars + B_QF + 8 * qb;
            mbar_expect_tx(fb, 32768);
            tma_load_2d(dst, &p.tm[TM_Q], h * 128, m * 128, fb);
            tma_load_2d(dst + 16384, &p.tm[TM_Q], h * 128 + 64, m * 128, fb);
          }
        }
      }
      __syncwarp();
      it += n;
      uint32_t ready = 0;
      auto wait_head = [&](int h) {
        if ((ready >> h) & 1) return;
        uint32_t cnt = 0;
        while (true) {
          asm volatile("ld.acquire.cta.shared.u32 %0, [%1];" : "=r"(ready) : "r"(bars + B_RDY) : "memory");
          if ((ready >> h) & 1) break;
          trap_if(++cnt > SPIN_LIMIT * 8);
          __nanosleep(20);
        }
        fence_async_global();
      };
      int item = items[it];
      if ((item >> 12) == T_SA) {
        const int m = ((item >> 5) & 31) * 2 + rank, b = item & 31;
        Ring dr = kv;
        wait_head(0);
#pragma unroll 1
        for (int i = 0; i < 28 + SA_STEPS; i++) {
          {
            const bool so = i >= 28;
            const int k = so ? i - 28 : i;
            if (so) wait_head(k >> 1);
            if (elect_one()) {
              if (i < 4) { for (int x = 0; x < ((0x1022 >> (4 * i)) & 3); x++) { mbar_wait(bars + B_KE + 8 * dr.s, dr.ph); ring_adv<5>(dr); } }
              if (i == 2) { mbar_wait(bars + B_XF, xph); xph ^= 1; }
              mbar_wait(bars + B_GE + 8 * g.s, g.ph);
              const uint32_t st = sb + ((g.s + 1) & 3) * G_STAGE, fb = bars + B_GF + 8 * g.s;
              mbar_expect_tx(fb, G_STAGE);
              tma_load_2d(st, &p.tm[so ? TM_O : TM_U], k * 64, m * 128, fb);
              tma_load_3d_mc(st + G_A + rank * 16384, &p.tm[so ? TM_WO : TM_WOUT], k * 64, b * 4 + rank * 2, fb);
            }
            ring_adv<4>(g);
          }
          const int ip = i + OUT_PF;
          if (ip < 28 + SA_STEPS && elect_one()) {
            const bool so = ip >= 28;
            const int k = so ? ip - 28 : ip;
            if ((ip & 3) == b && (!so || ((ready >> (k >> 1)) & 1))) tma_prefetch_2d(&p.tm[so ? TM_O : TM_U], k * 64, m * 128);
            if ((ip & 7) == (m >> 1)) tma_prefetch_3d(&p.tm[so ? TM_WO : TM_WOUT], k * 64, b * 4 + rank * 2);
          }
          __syncwarp();
        }
        item = items[++it];
      }
      if ((item >> 12) == T_FIN) {
        const bool own = item & 4;
        const int m = ((item >> 5) & 31) * 2 + rank, col = (item & 3) * 256 + (own ? 128 : 0);
        uint32_t ps = own ? FIN_SLOT0 : kv.s;
#pragma unroll 1
        for (int i = SA_STEPS; i <= 2 * NH; i++) {
          const bool extra = i == 2 * NH - FIN_PREP;
          if (extra && own) continue;
          const int k = i > 2 * NH - FIN_PREP ? i - 1 : i;
          if (!extra) wait_head(k >> 1);
          if (elect_one()) {
            if (i == SA_STEPS) {
              for (int y = k; y < k + 4; y++) if ((ready >> (y >> 1)) & 1) tma_prefetch_2d(&p.tm[TM_O], y * 64, m * 128);
            }
            if (own && i < SA_STEPS + 5) {
              const uint32_t s0 = ((0x22100u >> (4 * ps)) - 1) & 3, s1 = ((0x32110u >> (4 * ps)) - 1) & 3;
              mbar_wait(bars + B_GE + 8 * s0, g.ph ^ (s0 < g.s)); mbar_wait(bars + B_GE + 8 * s1, g.ph ^ (s1 < g.s));
            }
            if (extra) { flag_wait(&g_flags[F_S + m * 4 + (item & 3)], 2); fence_async_global(); }
            mbar_wait(bars + B_KE + 8 * kv.s, kv.ph);
            const uint32_t dst = sb + ps * KV_SLOT, fb = bars + B_KF + 8 * kv.s;
            if (++ps == 5) ps = 0;
            mbar_expect_tx(fb, KV_SLOT);
            if (!extra) {
              tma_load_2d(dst, &p.tm[TM_O], k * 64, m * 128, fb);
              tma_load_2d_mc(dst + 16384 + rank * 8192, &p.tm[TM_WO64], col + rank * 64, k * 64, fb);
            } else {
              tma_load_2d(dst, &p.tm[TM_SA], col, m * 128, fb);
              tma_load_2d(dst + 16384, &p.tm[TM_SA], col + 64, m * 128, fb);
            }
            ring_adv<5>(kv);
          }
          __syncwarp();
        }
      }
      unsigned last = 0;
      if (lane == 0 && (item >> 12) == T_FIN) mbar_wait_sleep(bars + B_XR, 0, 100);
      if (lane == 0) { __threadfence(); last = atomicInc(&g_done, gridDim.x - 1) == gridDim.x - 1; }
      last = __shfl_sync(0xffffffffu, last, 0);
      if (last) {
        for (int i = lane; i < F_TOTAL / 4; i += 32) reinterpret_cast<uint4*>(g_flags)[i] = make_uint4(0, 0, 0, 0);
        if (lane == 0) g_epoch = g_epoch + 1;
      }
    } else if (warp_id == 1) {
      if (elect_one()) {
        uint32_t ph = 0;
        int t = 0;
#pragma unroll 1
        for (int it = 0;; it++) {
          const int item = items[it], type = item >> 12, a = (item >> 5) & 31, b = item & 31;
          if (type == T_END) break;
          const int nt = items[it + 1] >> 12;
          int row = (a * 2 + rank) * 128, col = b * 256;
          unsigned* f = &g_flags[F_S + (a * 2 + rank) * 4 + b];
          int tm = TS_G, npair = 2;
          bool quad = false;
          uint32_t src = sb + OFF_Q0;
          if (type == T_Z2) { tm = TS_Z2; f = &g_flags[F_Z2 + b * 32]; }
          else if (type == T_Q) { tm = TS_Q; f = &g_flags[F_Q + (a * 2 + rank) * 16 + b]; if (nt >= T_ATT) { npair = 0; quad = true; } }
          else if (type == T_U) { tm = TS_U; f = &g_flags[F_U + (a * 2 + rank) * 32]; npair = 0; quad = true; }
          else if (type == T_ATT) { tm = TS_O; f = &g_flags[F_O + ((b & 7) * 2 + rank) * 32 + a]; npair = 1; row = ((b & 7) * 2 + rank) * 128; col = a * 128; if (t & 1) src = sb + OFF_Q1; }
          else if (type == T_FIN) npair = 1;
          auto load_fin = [&](int fi, int tmi, uint32_t qb) {
            const int fc = (fi & 3) * 256 + ((fi & 4) ? 128 : 0), fr = (((fi >> 5) & 31) * 2 + rank) * 128;
            mbar_expect_tx(bars + B_QF + 8 * qb, 32768);
            tma_load_2d(sb + (qb ? OFF_Q1 : OFF_Q0), &p.tm[tmi], fc, fr, bars + B_QF + 8 * qb);
            tma_load_2d(sb + (qb ? OFF_Q1 : OFF_Q0) + 16384, &p.tm[tmi], fc + 64, fr, bars + B_QF + 8 * qb);
          };
          if (type == T_ATT && nt == T_FIN) load_fin(items[it + 1], TM_X, (t & 1) ^ 1);
          if (type == T_FIN) {
            if (!(item & 4)) { flag_wait(&g_flags[F_S + (a * 2 + rank) * 4 + (b & 3)], 1); fence_async_global(); load_fin(item, TM_G, (t & 1) ^ 1); }
            mbar_arrive(bars + B_XR);
          }
#pragma unroll 1
          for (int op = 0; op < npair + quad; op++) {
            const bool q = op == npair;
            const int c0 = (q || type == T_SA) ? col : col + op * 128;
            mbar_wait_sleep(bars + B_STG, ph, (type == T_ATT && nt == T_ATT) ? SW_ATT : SW_NS);
            if (type == T_FIN) break;
            ph ^= 1;
            fence_async_smem();
            if (type == T_SA && op == 1) { tm = TS_SA; load_fin(items[it + 1], TM_X, 1); }
            int c1 = c0;
            if (q) {
              const CUtensorMap* tb = &p.tm[type == T_U ? TM_U : TM_Q];
              tma_store_2d(tb, sb + 2 * G_STAGE, c0, row);
              tma_store_2d(tb, sb + 3 * G_STAGE, c0 + 64, row);
              bulk_commit();
              bulk_wait_read<0>();
              mbar_arrive_cta(bars + B_XF, 0); mbar_arrive_cta(bars + B_XF, 1);
              src = sb + OFF_Q1; c1 += 128;
            }
            if (nt != T_END) {
#pragma unroll 1
              for (int r = 0; r < 256; r += ST_ROWS) {
                tma_store_2d(&p.tm[tm], src + r * 128, c1 + (r >> 7) * 64, row + (r & 127));
                bulk_commit();
                bulk_wait_read<ST_FLY>();
                if (q) __nanosleep(U_PACE);
              }
            }
            bulk_wait_read<0>();
            mbar_arrive(bars + B_FREE);
            if (type == T_ATT && (t & 1) && (nt == T_SA || (items[it + 2] >> 12) == T_SA)) { mbar_arrive_cta(bars + B_XF, 0); mbar_arrive_cta(bars + B_XF, 1); }
            if (type == T_ATT) mbar_arrive(bars + B_QE + 8 * (t & 1));
            else if (nt == T_ATT) mbar_arrive(bars + B_QE + 8);
            if (op + 1 >= npair || type == T_SA) {
              bulk_wait<0>();
              red_release(f, 1);
            }
          }
          if (type == T_ATT) t++;
          else if (t == 0 && (items[it + 1] >> 12) < T_ATT && (items[it + 2] >> 12) == T_ATT) {
            const int im = items[it + 2], h = (im >> 5) & 31, m = (im & 7) * 2 + rank;
            flag_wait(&g_flags[F_Q + m * 16 + (h >> 1)], 1);
            fence_async_global();
            mbar_expect_tx(bars + B_QF, 32768);
            tma_load_2d(sb + OFF_Q0, &p.tm[TM_Q], h * 128, m * 128, bars + B_QF);
            tma_load_2d(sb + OFF_Q0 + 16384, &p.tm[TM_Q], h * 128 + 64, m * 128, bars + B_QF);
          }
        }
      }
      __syncwarp();
    } else if (warp_id == 2) {
      int it = 0;
      while ((items[it] >> 12) <= T_ATT) it++;
      if ((items[it] >> 12) != T_END) {
        const bool sa = (items[it] >> 12) == T_SA;
        const int m = ((items[it] >> 5) & 31) * 2 + rank;
        if (lane == 0) {
          mbar_wait_sleep(bars + B_GO, 0, 500);
          if (sa) {
            const int b = items[it] & 3;
            flag_wait(&g_flags[F_U + m * 32], 7);
            fence_async_global();
            for (int y = b; y < OUT_PF; y += 4) tma_prefetch_2d(&p.tm[TM_U], y * 64, m * 128);
            tma_prefetch_3d(&p.tm[TM_WOUT], (m >> 1) * 64, b * 4 + rank * 2);
          }
          if (!sa) for (int y = m * 4 + (items[it] & 3); y < 16 * (NH - SA_HEADS); y += 64) tma_prefetch_3d(&p.tm[TM_WO], (2 * SA_HEADS + (y >> 3)) * 64, (y & 7) * 2);
        }
        __syncwarp();
        uint32_t cnt = 0;
        while (true) {
          const uint32_t r = __ballot_sync(0xffffffffu, ld_acquire(&g_flags[F_O + m * 32 + lane]) != 0);
          if (lane == 0) asm volatile("st.release.cta.shared.u32 [%0], %1;" :: "r"(bars + B_RDY), "r"(r) : "memory");
          if (r == ~0u) break;
          trap_if(++cnt > SPIN_LIMIT);
          __nanosleep(r >> 28 ? 20 : 300);
        }
        if (lane == 0) mbar_arrive(bars + B_XR);
      }
      __syncwarp();
    }
    cluster_sync_relaxed();
  } else {
    Cons c;
    c.sb = sb; c.warp = warp_id - 4; c.g = {0, 0}; c.fph = 1; c.rot = 0;
    if (gw < SEQ / 2) {
      uint4* dst = reinterpret_cast<uint4*>(g_xn + (size_t)gw * 2 * DM) + lane;
      float f[2][32], s[2], q[2];
#pragma unroll
      for (int rr = 0; rr < 2; rr++) {
        const float pv = __shfl_sync(0xffffffffu, bf_lo(xv[rr][0].x), 0);
#pragma unroll
        for (int i = 0; i < 4; i++) {
          const uint4 v = xv[rr][i];
          f[rr][8 * i + 0] = bf_lo(v.x) - pv; f[rr][8 * i + 1] = bf_hi(v.x) - pv; f[rr][8 * i + 2] = bf_lo(v.y) - pv; f[rr][8 * i + 3] = bf_hi(v.y) - pv;
          f[rr][8 * i + 4] = bf_lo(v.z) - pv; f[rr][8 * i + 5] = bf_hi(v.z) - pv; f[rr][8 * i + 6] = bf_lo(v.w) - pv; f[rr][8 * i + 7] = bf_hi(v.w) - pv;
        }
        s[rr] = q[rr] = 0.f;
#pragma unroll
        for (int i = 0; i < 32; i++) { s[rr] += f[rr][i]; q[rr] = fmaf(f[rr][i], f[rr][i], q[rr]); }
      }
#pragma unroll
      for (int o = 16; o; o >>= 1)
#pragma unroll
        for (int rr = 0; rr < 2; rr++) { s[rr] += __shfl_xor_sync(0xffffffffu, s[rr], o); q[rr] += __shfl_xor_sync(0xffffffffu, q[rr], o); }
#pragma unroll
      for (int rr = 0; rr < 2; rr++) {
        const float mean = s[rr] * (1.f / DM);
        const float r = rsqrtf(fmaxf(q[rr] * (1.f / DM) - mean * mean, 0.f) + 1e-5f), a = -mean * r;
#pragma unroll
        for (int i = 0; i < 4; i++) {
          const float* y = &f[rr][8 * i];
          dst[rr * 128 + i * 32] = make_uint4(pack_bf16(fmaf(y[0], r, a), fmaf(y[1], r, a)), pack_bf16(fmaf(y[2], r, a), fmaf(y[3], r, a)),
                                              pack_bf16(fmaf(y[4], r, a), fmaf(y[5], r, a)), pack_bf16(fmaf(y[6], r, a), fmaf(y[7], r, a)));
        }
      }
      named_sync(7);
      if (tid == 128) red_release(&g_flags[F_XN + (gw >> 6) * 32], 16);
    }
    asm volatile("setmaxnreg.inc.sync.aligned.u32 232;");
    asm volatile("barrier.cluster.wait.acquire.aligned;" ::: "memory");
    int natt = 0;
    int it = 0;
    uint32_t held[64];
#pragma unroll
    for (int i = 0; i < 64; i++) held[i] = 0u;
    Shadow sh = {0, 0};
    float facc[64];
#pragma unroll 1
    while (true) {
      const int item = get_item(p, it), type = item >> 12, a = (item >> 5) & 31;
      c.warp = fresh_warp();
      if (type == T_ATT) {
        const int n = ((item >> 10) & 3) + 3;
        att_run(c, p, it, n);
#pragma unroll
        for (int i = 0; i < 64; i++) held[i] = 0u;
        natt = n;
        it += n;
        c.rot = 1;
        if ((get_item(p, it) >> 12) == T_SA) continue;
#pragma unroll
        for (int i = 0; i < 64; i++) facc[i] = 0.f;
        break;
      }
      float acc[128];
      const bool sa = type == T_SA;
      bool more = type >= T_U;
      int nsteps = sa ? 28 : 16;
      const bool direct = (get_item(p, it + 1) >> 12) >= T_ATT;
      uint32_t bias0 = 0, bias1 = 0;
#pragma unroll 1
      while (true) {
        gemm_seg(acc, held, c, p, sh, nsteps);
        if (!more && direct && !sa) pp_arrive(c.warp >= 4);
        if (type == T_Q) {
#pragma unroll
          for (int i = 0; i < 128; i++) acc[i] *= SM_C;
        }
        if (!more && direct) break;
#pragma unroll
        for (int i = 0; i < 64; i++) held[i] = pack_bf16(acc[2 * i], acc[2 * i + 1]);
        if (!more) break;
        more = false;
        nsteps = sa ? SA_STEPS : 32;
        sh.act = sa ? 3 : 1;
        if (sa) {
          sh.store = 3;
        } else {
          const int row0 = (a * 2 + rank) * 128 + c.warp * 16 + (lane_id() >> 2);
          asm volatile("ld.global.nc.u16 %0, [%1];" : "=r"(bias0) : "l"(p.b_sp + row0));
          asm volatile("ld.global.nc.u16 %0, [%1];" : "=r"(bias1) : "l"(p.b_sp + row0 + 8));
        }
      }
      c.warp = fresh_warp();
      if (direct) {
        const uint32_t hb0 = bf2_mul(bias0 * 0x10001u, BF2_HALF), hb1 = bf2_mul(bias1 * 0x10001u, BF2_HALF);
        stage_acquire(c);
#pragma unroll
        for (int h = 0; h < 2; h++) {
          uint32_t pk[32];
#pragma unroll
          for (int i = 0; i < 32; i++) pk[i] = pack_bf16(acc[64 * h + 2 * i], acc[64 * h + 2 * i + 1]);
          if (type == T_U) {
#pragma unroll
            for (int i = 0; i < 32; i++) pk[i] = bf2_mul(bf2_fma(pk[i], BF2_HALF, (i & 1) ? hb1 : hb0), held[32 * h + i]);
          }
          if (h) pp_sync(c.warp >= 4);
          stage_chunks<2>(sb + (h ? OFF_Q1 : (sa ? OFF_Q0 : 2 * G_STAGE)) + c.warp * 2048, (h || sa) ? 16384 : G_STAGE, pk);
          if (sa) break;
        }
        stage_commit(c);
        if (sa) {
#pragma unroll
          for (int i = 0; i < 64; i++) facc[i] = acc[64 + i];
          it++;
          break;
        }
      } else if (type == T_Q) {
        sh.store = 1;
      } else {
        sh.act = sh.store = 2;
      }
      it++;
    }
    const int fin = get_item(p, it);
    if ((fin >> 12) == T_FIN) {
      c.warp = fresh_warp();
      const bool own = fin & 4;
      Ring kv = {(uint32_t)(32 * natt) % 5, ((uint32_t)(32 * natt) / 5) & 1};
      uint32_t prev = 0, ps = own ? FIN_SLOT0 : kv.s;
      fence_regs(facc);
      auto fin_steps = [&](int k0, int k1) {
#pragma unroll 1
        for (int k = k0; k < k1; k++) {
          mbar_spin(bars + B_KF + 8 * kv.s, kv.ph);
          const uint32_t st = ((c.sb & 0x3FFFF) >> 4) + ps * (KV_SLOT >> 4);
          if (++ps == 5) ps = 0;
          const uint32_t da = st + (c.warp >> 2) * 512 + (1u << 16), db = st + 1024 + ((8192u >> 4) << 16);
          wgmma_fence();
#pragma unroll
          for (int kk = 0; kk < 4; kk++) wgmma_m64n128k16_ss_tb1(facc, DESC_HI | (da + kk * 2), DESC_HI | (db + kk * 128), 1);
          wgmma_commit();
          wgmma_wait<1>();
          if (k > SA_STEPS) release_slot(c, prev);
          prev = bars + B_KE + 8 * kv.s;
          ring_adv<5>(kv);
        }
      };
      const int kp = (own && ((fin >> 5) & 31) == 7) ? SA_STEPS + 5 : 2 * NH - FIN_PREP - (own ? OWN_OFF : 0);
      fin_steps(SA_STEPS, kp);
      const uint32_t ln = lane_id(), xb = own ? 1 : natt & 1;
      const uint32_t lo = c.warp * 2048 + ((ln & 15) << 7);
      uint32_t xs[32];
      auto load_tile = [&](uint32_t base, uint32_t* d) {
#pragma unroll
        for (int i = 0; i < 8; i++) ldmatrix_x4(base + lo + (i >> 2) * 16384 + (((2 * (i & 3) + (ln >> 4)) ^ (ln & 7)) << 4), d[4 * i], d[4 * i + 1], d[4 * i + 2], d[4 * i + 3]);
      };
      const uint32_t xa = sb + (xb ? OFF_Q1 : OFF_Q0);
      mbar_spin(bars + B_QF + 8 * xb, ((natt + 1 - xb) >> 1) & 1);
      load_tile(xa, xs);
      if (!own) {
        mbar_spin(bars + B_QF + 8 * (xb ^ 1), ((natt + xb) >> 1) & 1);
        load_tile(sb + (xb ? OFF_Q0 : OFF_Q1), held + 32);
      }
      float gf[64], rf[64];
#pragma unroll
      for (int i = 0; i < 32; i++) { gf[2 * i] = bf_lo(held[32 + i]); gf[2 * i + 1] = bf_hi(held[32 + i]); rf[2 * i] = bf_lo(xs[i]); rf[2 * i + 1] = bf_hi(xs[i]); }
      if (!own) {
        mbar_spin(bars + B_KF + 8 * kv.s, kv.ph);
#pragma unroll
        for (int i = 0; i < 8; i++) {
          uint32_t t[4];
          ldmatrix_x4(sb + ps * KV_SLOT + lo + (i >> 2) * 16384 + (((2 * (i & 3) + (ln >> 4)) ^ (ln & 7)) << 4), t[0], t[1], t[2], t[3]);
#pragma unroll
          for (int y = 0; y < 4; y++) {
            rf[8 * i + 2 * y] = fmaf(bf_lo(t[y]), gf[8 * i + 2 * y], rf[8 * i + 2 * y]);
            rf[8 * i + 2 * y + 1] = fmaf(bf_hi(t[y]), gf[8 * i + 2 * y + 1], rf[8 * i + 2 * y + 1]);
          }
        }
        wg_any(c.warp >= 4, false);
        release_slot(c, bars + B_KE + 8 * kv.s);
        if (++ps == 5) ps = 0;
        ring_adv<5>(kv);
      }
      fence_regs(gf); fence_regs(rf);
      fin_steps(kp, 2 * NH);
      wgmma_wait<0>();
      fence_regs(facc);
#pragma unroll
      for (int i = 0; i < 32; i++) xs[i] = pack_bf16(fmaf(facc[2 * i], gf[2 * i], rf[2 * i]), fmaf(facc[2 * i + 1], gf[2 * i + 1], rf[2 * i + 1]));
      __syncwarp();
      stage_chunks<2>(xa + c.warp * 2048, 16384, xs);
      fence_async_smem();
      __syncwarp();
      if (elect_one()) {
        const int col = (fin & 3) * 256 + (own ? 128 : 0), row = (((fin >> 5) & 31) * 2 + rank) * 128 + c.warp * 16;
        tma_store_2d(&p.tm[TS_OUT], xa + c.warp * 2048, col, row);
        tma_store_2d(&p.tm[TS_OUT], xa + c.warp * 2048 + 16384, col + 64, row);
        bulk_commit();
        mbar_arrive(bars + B_STG);
        bulk_wait_read<0>();
      }
    }
    __syncwarp();
    cluster_sync_relaxed();
  }
}

typedef CUresult (*PFN_encodeTiled)(CUtensorMap*, CUtensorMapDataType, cuuint32_t, void*, const cuuint64_t*, const cuuint64_t*, const cuuint32_t*, const cuuint32_t*,
                                    CUtensorMapInterleave, CUtensorMapSwizzle, CUtensorMapL2promotion, CUtensorMapFloatOOBfill);
static PFN_encodeTiled s_encode = nullptr;
static void tm_2d(CUtensorMap* tm, const void* ptr, uint64_t rows, uint64_t cols, uint32_t box_rows) {
  cuuint64_t dims[2] = {cols, rows}; cuuint64_t strides[1] = {cols * 2}; cuuint32_t box[2] = {64, box_rows}; cuuint32_t es[2] = {1, 1};
  CUresult r = s_encode(tm, CU_TENSOR_MAP_DATA_TYPE_BFLOAT16, 2, (void*)ptr, dims, strides, box, es, CU_TENSOR_MAP_INTERLEAVE_NONE,
                        CU_TENSOR_MAP_SWIZZLE_128B, CU_TENSOR_MAP_L2_PROMOTION_L2_128B, CU_TENSOR_MAP_FLOAT_OOB_FILL_NONE);
  if (r != CUDA_SUCCESS) fprintf(stderr, "tensor map encode failed (%d)\n", (int)r);
}
static void tm_3d(CUtensorMap* tm, const void* ptr, uint64_t rows, uint64_t cols) {
  cuuint64_t dims[3] = {64, rows, cols / 64}; cuuint64_t strides[2] = {cols * 2, 128}; cuuint32_t box[3] = {64, 64, 2}; cuuint32_t es[3] = {1, 1, 1};
  CUresult r = s_encode(tm, CU_TENSOR_MAP_DATA_TYPE_BFLOAT16, 3, (void*)ptr, dims, strides, box, es, CU_TENSOR_MAP_INTERLEAVE_NONE,
                        CU_TENSOR_MAP_SWIZZLE_128B, CU_TENSOR_MAP_L2_PROMOTION_L2_128B, CU_TENSOR_MAP_FLOAT_OOB_FILL_NONE);
  if (r != CUDA_SUCCESS) fprintf(stderr, "tensor map encode failed (%d)\n", (int)r);
}
static inline uint16_t mk(int type, int a, int b) { return (uint16_t)(type << 12 | a << 5 | b); }

static void build_schedule(Params& P) {
  int cnt[NCLUSTER];
  for (int c = 0; c < NCLUSTER; c++) { cnt[c] = 0; for (int i = 0; i < MAXI; i++) P.items[c][i] = mk(T_END, 0, 0); }
  auto phys = [](int c) { return c == 64 ? 9 : c == 65 ? 17 : c == 9 ? 64 : c == 17 ? 65 : c; };
  auto push = [&](int c, uint16_t v) { P.items[phys(c)][cnt[c]++] = v; };
  int natt[NCLUSTER], nq[NCLUSTER];
  for (int c = 0; c < NCLUSTER; c++) { natt[c] = c < 32 ? 3 : (c < 56 ? 5 : (c < 62 ? 4 : (c < 64 ? 3 : 5))); nq[c] = c < 56 ? 1 : (c < 62 ? 7 : (c < 64 ? 9 : 6)); }
  for (int c = 0; c < 56; c++) push(c, mk(T_Z2, c % 8, c / 8));
  int qi = 0;
  for (int slot = 0; slot < 9; slot++)
    for (int c = NCLUSTER - 1; c >= 0; c--) {
      const int first = c < 56 ? 1 : 0;
      if (slot >= first && slot < first + nq[c]) { push(c, mk(T_Q, qi % 8, qi / 8)); qi++; }
    }
  for (int c = 0; c < 56; c++) push(c, mk(T_U, c % 8, c / 8));
  int ai = 0, grp[256], own[256];
  for (int slot = 0; slot < 5; slot++)
    for (int c = 0; c < NCLUSTER; c++) {
      const int first = c < 32 ? 0 : 5 - natt[c];
      if (slot >= first && slot < first + natt[c]) { grp[ai] = slot * 2 + (c >= 64); own[ai++] = c; }
    }
  for (int i = 0; i < 256; i++) {
    int s = 0;
    for (int j = i & ~7; j < (i & ~7) + 8; j++) s += grp[j] == grp[i];
    const int share = s >= 8 ? 0 : s >= 4 ? 1 : s >= 2 ? 2 : 3;
    push(own[i], mk(T_ATT, i / 8, share << 3 | i % 8) | (natt[own[i]] - 3) << 10);
  }
  for (int c = 0; c < 32; c++) push(c, mk(T_SA, c % 8, c / 8));
  for (int c = 0; c < 64; c++) push(c, mk(T_FIN, c % 8, (c / 8) % 4 | (c < 32 ? 4 : 0)));
  if (qi != 128 || ai != 256) fprintf(stderr, "bad schedule %d %d\n", qi, ai);
}

static Params s_params;
extern "C" void kernel_launch(void* const* d_in, const int* in_sizes, int n_in, void* d_out, int out_size) {
  (void)in_sizes; (void)n_in; (void)out_size;
  if (!s_encode) {
    void* fn = nullptr; cudaDriverEntryPointQueryResult qr;
    cudaGetDriverEntryPoint("cuTensorMapEncodeTiled", &fn, cudaEnableDefault, &qr);
    s_encode = (PFN_encodeTiled)fn;
    cudaFuncSetAttribute(fused_kernel, cudaFuncAttributeMaxDynamicSharedMemorySize, SMEM_BYTES);
    build_schedule(s_params);
  }
  Params& P = s_params;
  void *xn, *q, *o, *z2, *u, *gg, *sa;
  cudaGetSymbolAddress(&gg, g_g); cudaGetSymbolAddress(&sa, g_sa);
  cudaGetSymbolAddress(&xn, g_xn); cudaGetSymbolAddress(&q, g_q); cudaGetSymbolAddress(&o, g_o);
  cudaGetSymbolAddress(&z2, g_z2); cudaGetSymbolAddress(&u, g_u);
  tm_2d(&P.tm[TM_XN], xn, SEQ, DM, 128); tm_2d(&P.tm[TM_WSP], d_in[7], SEQ, SEQ, 128); tm_2d(&P.tm[TM_U], u, SEQ, FH, 128);
  tm_2d(&P.tm[TM_O], o, SEQ, HD, 128); tm_2d(&P.tm[TM_Q], q, SEQ, HD, 128); tm_2d(&P.tm[TM_X], d_in[0], SEQ, DM, 128);
  tm_2d(&P.tm[TM_K], d_in[1], NH * SEQ, 128, 128); tm_2d(&P.tm[TM_V], d_in[2], NH * SEQ, 128, 128);
  tm_2d(&P.tm[TM_SA], sa, SEQ, DM, 128); tm_2d(&P.tm[TM_G], gg, SEQ, DM, 128); tm_2d(&P.tm[TM_WO64], d_in[4], HD, DM, 64);
  tm_3d(&P.tm[TM_WIN], d_in[6], DM, FF); tm_3d(&P.tm[TM_WQ], d_in[3], DM, HD); tm_3d(&P.tm[TM_Z2], z2, SEQ, FH);
  tm_3d(&P.tm[TM_WOUT], d_in[9], FH, DM); tm_3d(&P.tm[TM_WO], d_in[4], HD, DM);
  tm_2d(&P.tm[TS_Q], q, SEQ, HD, ST_ROWS); tm_2d(&P.tm[TS_O], o, SEQ, HD, ST_ROWS); tm_2d(&P.tm[TS_Z2], z2, SEQ, FH, ST_ROWS); tm_2d(&P.tm[TS_U], u, SEQ, FH, ST_ROWS);
  tm_2d(&P.tm[TS_SA], sa, SEQ, DM, ST_ROWS); tm_2d(&P.tm[TS_G], gg, SEQ, DM, ST_ROWS); tm_2d(&P.tm[TS_OUT], d_out, SEQ, DM, 16);
  P.x = (const bf16*)d_in[0]; P.b_sp = (const bf16*)d_in[8];
  fused_kernel<<<2 * NCLUSTER, 384, SMEM_BYTES, cudaStreamPerThread>>>(P);
}
```
